```python
import torch

def _softmax(x, axis=-1):
    return torch.softmax(x, dim=axis)

def _gelu(x):
    return torch.nn.functional.gelu(x, approximate='tanh')

def _silu(x):
    return torch.nn.functional.silu(x)

def _sigmoid(x):
    return torch.sigmoid(x)

def _layernorm(x, axis=-1, eps=1e-05):
    m = x.mean(dim=axis, keepdim=True)
    v = x.var(dim=axis, keepdim=True, unbiased=False)
    return (x - m) / torch.sqrt(v + eps)

def _scatter_add(tgt, idx, src, axis=0):
    return tgt.clone().index_add_(axis, idx, src)

def _segment_sum(src, seg, n):
    out = torch.zeros((n,) + src.shape[1:], dtype=src.dtype)
    return out.index_add_(0, seg, src)

def _pad(x, pw):
    flat = tuple((v for pair in reversed(pw) for v in pair))
    return torch.nn.functional.pad(x, flat)
kernel_name = 'concat_heads__compressed_kv_cla__memory_aug_recurrent_mem_tr__prompt'

def setup_inputs():

    _w = lambda a: (lambda t: t.to(torch.bfloat16) if t.is_floating_point() else t)(torch.as_tensor(a))

    def _A_setup():
        B, H, Sq, Sk, D, M = (1, 32, 2048, 2048, 128, 576)
        Dc = 4 * D
        return {'x': _w((lambda *s: torch.randn(*s, dtype=torch.bfloat16) * 1.6)(B, Sq, M)), 'c_kv': _w((lambda *s: torch.randn(*s, dtype=torch.bfloat16) * 0.2)(B, Sk, Dc)), 'w_q': _w((lambda *s: torch.randn(*s, dtype=torch.bfloat16) * 3.2)(M, H, D) * M ** (-0.5)), 'w_uk': _w((lambda *s: torch.randn(*s, dtype=torch.bfloat16) * 3.2)(Dc, H, D) * Dc ** (-0.5)), 'w_uv': _w((lambda *s: torch.randn(*s, dtype=torch.bfloat16) * 0.2)(Dc, H, D) * Dc ** (-0.5)), 'w_o': _w((lambda *s: torch.randn(*s, dtype=torch.bfloat16) * 0.2)(H, D, M) * (H * D) ** (-0.5))}
    _A_in = _A_setup()

    def _B_setup():
        B, S, Dm = (1, 2048, 576)
        H, Dh = (32, 128)
        M, seg = (8, 32)
        seg = min(seg, S)
        S = S // seg * seg
        return {'x': _w((lambda *s: torch.randn(*s, dtype=torch.bfloat16) * 0.05)(B, S, Dm)), 'mem0': _w((lambda *s: torch.randn(*s, dtype=torch.bfloat16) * 0.4)(B, M, Dm)), 'Wq': _w((lambda *s: torch.randn(*s, dtype=torch.bfloat16) * 6.4)(Dm, H, Dh) * Dm ** (-0.5)), 'Wk': _w((lambda *s: torch.randn(*s, dtype=torch.bfloat16) * 6.4)(Dm, H, Dh) * Dm ** (-0.5)), 'Wv': _w((lambda *s: torch.randn(*s, dtype=torch.bfloat16) * 0.4)(Dm, H, Dh) * Dm ** (-0.5)), 'Wo': _w((lambda *s: torch.randn(*s, dtype=torch.bfloat16) * 0.4)(H, Dh, Dm) * (H * Dh) ** (-0.5)), 'seg_len': seg}
    _B_in = _B_setup()
    return {'A_x': _A_in['x'], 'A_c_kv': _A_in['c_kv'], 'A_w_q': _A_in['w_q'], 'A_w_uk': _A_in['w_uk'], 'A_w_uv': _A_in['w_uv'], 'A_w_o': _A_in['w_o'], 'B_x': _B_in['x'], 'B_mem0': _B_in['mem0'], 'B_Wq': _B_in['Wq'], 'B_Wk': _B_in['Wk'], 'B_Wv': _B_in['Wv'], 'B_Wo': _B_in['Wo'], 'B_seg_len': _B_in['seg_len']}

def reference(A_x, A_c_kv, A_w_q, A_w_uk, A_w_uv, A_w_o, B_x, B_mem0, B_Wq, B_Wk, B_Wv, B_Wo, B_seg_len):

    def _A_ref(x, c_kv, w_q, w_uk, w_uv, w_o):
        B, Sq, M = (x.shape[0], x.shape[1], x.shape[2])
        Sk = c_kv.shape[1]
        H, D = (w_q.shape[1], w_q.shape[2])
        q = torch.einsum('bqm,mhd->bhqd', x, w_q)
        k = torch.einsum('bkc,chd->bhkd', c_kv, w_uk)
        v = torch.einsum('bkc,chd->bhkd', c_kv, w_uv)
        scores = torch.einsum('bhqd,bhkd->bhqk', q, k) * D ** (-0.5)
        off = Sk - Sq
        qi = torch.arange(Sq)[:, None]
        kj = torch.arange(Sk)[None, :]
        cmask = kj <= qi + off
        scores = torch.where(cmask[None, None], scores, -1000000000.0)
        p = _softmax(scores, axis=-1)
        ctx = torch.einsum('bhqk,bhkd->bhqd', p, v)
        return torch.einsum('bhqd,hdm->bqm', ctx, w_o)

    def _B_ref(x, mem0, Wq, Wk, Wv, Wo, seg_len):
        B, S, Dm = x.shape
        H, Dh = (Wq.shape[1], Wq.shape[2])
        M = mem0.shape[1]
        scale = Dh ** (-0.5)
        n_seg = S // seg_len
        L = M + seg_len
        idx = torch.arange(L)
        mask = (idx[:, None] < M) | (idx[:, None] >= idx[None, :])
        mem = mem0
        outs = []
        for s in range(n_seg):
            xs = x[:, s * seg_len:(s + 1) * seg_len, :].clone()
            h = torch.concatenate([mem, xs], axis=1)
            q = torch.einsum('btd,dhe->bhte', h, Wq)
            k = torch.einsum('btd,dhe->bhte', h, Wk)
            v = torch.einsum('btd,dhe->bhte', h, Wv)
            scores = torch.einsum('bhqe,bhke->bhqk', q, k) * scale
            scores = torch.where(mask[None, None], scores, -1000000000.0)
            p = _softmax(scores, axis=-1)
            o = torch.einsum('bhqk,bhke->bhqe', p, v)
            o = torch.einsum('bhte,hed->btd', o, Wo)
            mem = o[:, :M, :].clone()
            outs.append(o[:, M:, :])
        return torch.concatenate(outs, axis=1)
    a = _A_ref(A_x, A_c_kv, A_w_q, A_w_uk, A_w_uv, A_w_o)
    b = _B_ref(B_x, B_mem0, B_Wq, B_Wk, B_Wv, B_Wo, B_seg_len)
    return torch.concatenate([a, b], axis=-1)
```

```cpp
#include <cuda_runtime.h>
#include <cuda_bf16.h>
#include <cuda.h>
#include <stdint.h>
#ifdef DEV_ORDER
#include <stdio.h>
#include <stdlib.h>
#endif

namespace {

constexpr int SEQ = 2048, DM = 576, HDALL = 4096;

__device__ __nv_bfloat16 g_scr[4ull * SEQ * HDALL];
constexpr int SY_Q = 0, SY_EXIT = 16, SY_KV = 32, SY_CTX = 32 + 256, SY_OX = 32 + 512, SY_N = 32 + 512 + 32;
__device__ unsigned g_sync[SY_N];

#ifdef DEV_TRACE
__device__ long long g_trace[132 * 4096];
#ifdef DEV_TRF
#define TRF(slot) do { if (w4 == 0 && ti < 60) { uint32_t c_; asm volatile("mov.u32 %0, %%clock;" : "=r"(c_)::"memory"); if (elect()) g_trace[blockIdx.x * 4096 + 2048 + ti * 32 + wg * 16 + (slot)] = c_; __syncwarp(); } } while (0)
#else
#define TRF(slot)
#endif
#define TRM(slot) do { if ((threadIdx.x & 31) == 0) { long long c_; asm volatile("mov.u64 %0, %%globaltimer;" : "=l"(c_)); g_trace[blockIdx.x * 4096 + 4080 + (slot)] = c_; } } while (0)
#else
#define TRM(slot)
#define TRF(slot)
#endif

__device__ __forceinline__ void wgmma_ss_n256_a0b1(float (&d)[128], uint64_t da, uint64_t db, int sc) {
  asm volatile("{.reg .pred p; setp.ne.b32 p, %130, 0; wgmma.mma_async.sync.aligned.m64n256k16.f32.bf16.bf16 {%0,%1,%2,%3,%4,%5,%6,%7,%8,%9,%10,%11,%12,%13,%14,%15,%16,%17,%18,%19,%20,%21,%22,%23,%24,%25,%26,%27,%28,%29,%30,%31,%32,%33,%34,%35,%36,%37,%38,%39,%40,%41,%42,%43,%44,%45,%46,%47,%48,%49,%50,%51,%52,%53,%54,%55,%56,%57,%58,%59,%60,%61,%62,%63,%64,%65,%66,%67,%68,%69,%70,%71,%72,%73,%74,%75,%76,%77,%78,%79,%80,%81,%82,%83,%84,%85,%86,%87,%88,%89,%90,%91,%92,%93,%94,%95,%96,%97,%98,%99,%100,%101,%102,%103,%104,%105,%106,%107,%108,%109,%110,%111,%112,%113,%114,%115,%116,%117,%118,%119,%120,%121,%122,%123,%124,%125,%126,%127}, %128, %129, p, 1, 1, 0, 1;}"
    : "+f"(d[0]),"+f"(d[1]),"+f"(d[2]),"+f"(d[3]),"+f"(d[4]),"+f"(d[5]),"+f"(d[6]),"+f"(d[7]),"+f"(d[8]),"+f"(d[9]),"+f"(d[10]),"+f"(d[11]),"+f"(d[12]),"+f"(d[13]),"+f"(d[14]),"+f"(d[15]),"+f"(d[16]),"+f"(d[17]),"+f"(d[18]),"+f"(d[19]),"+f"(d[20]),"+f"(d[21]),"+f"(d[22]),"+f"(d[23]),"+f"(d[24]),"+f"(d[25]),"+f"(d[26]),"+f"(d[27]),"+f"(d[28]),"+f"(d[29]),"+f"(d[30]),"+f"(d[31]),"+f"(d[32]),"+f"(d[33]),"+f"(d[34]),"+f"(d[35]),"+f"(d[36]),"+f"(d[37]),"+f"(d[38]),"+f"(d[39]),"+f"(d[40]),"+f"(d[41]),"+f"(d[42]),"+f"(d[43]),"+f"(d[44]),"+f"(d[45]),"+f"(d[46]),"+f"(d[47]),"+f"(d[48]),"+f"(d[49]),"+f"(d[50]),"+f"(d[51]),"+f"(d[52]),"+f"(d[53]),"+f"(d[54]),"+f"(d[55]),"+f"(d[56]),"+f"(d[57]),"+f"(d[58]),"+f"(d[59]),"+f"(d[60]),"+f"(d[61]),"+f"(d[62]),"+f"(d[63]),"+f"(d[64]),"+f"(d[65]),"+f"(d[66]),"+f"(d[67]),"+f"(d[68]),"+f"(d[69]),"+f"(d[70]),"+f"(d[71]),"+f"(d[72]),"+f"(d[73]),"+f"(d[74]),"+f"(d[75]),"+f"(d[76]),"+f"(d[77]),"+f"(d[78]),"+f"(d[79]),"+f"(d[80]),"+f"(d[81]),"+f"(d[82]),"+f"(d[83]),"+f"(d[84]),"+f"(d[85]),"+f"(d[86]),"+f"(d[87]),"+f"(d[88]),"+f"(d[89]),"+f"(d[90]),"+f"(d[91]),"+f"(d[92]),"+f"(d[93]),"+f"(d[94]),"+f"(d[95]),"+f"(d[96]),"+f"(d[97]),"+f"(d[98]),"+f"(d[99]),"+f"(d[100]),"+f"(d[101]),"+f"(d[102]),"+f"(d[103]),"+f"(d[104]),"+f"(d[105]),"+f"(d[106]),"+f"(d[107]),"+f"(d[108]),"+f"(d[109]),"+f"(d[110]),"+f"(d[111]),"+f"(d[112]),"+f"(d[113]),"+f"(d[114]),"+f"(d[115]),"+f"(d[116]),"+f"(d[117]),"+f"(d[118]),"+f"(d[119]),"+f"(d[120]),"+f"(d[121]),"+f"(d[122]),"+f"(d[123]),"+f"(d[124]),"+f"(d[125]),"+f"(d[126]),"+f"(d[127])
    : "l"(da), "l"(db), "r"(sc));
}
__device__ __forceinline__ void wgmma_ss_n192_a0b1(float (&d)[96], uint64_t da, uint64_t db, int sc) {
  asm volatile("{.reg .pred p; setp.ne.b32 p, %98, 0; wgmma.mma_async.sync.aligned.m64n192k16.f32.bf16.bf16 {%0,%1,%2,%3,%4,%5,%6,%7,%8,%9,%10,%11,%12,%13,%14,%15,%16,%17,%18,%19,%20,%21,%22,%23,%24,%25,%26,%27,%28,%29,%30,%31,%32,%33,%34,%35,%36,%37,%38,%39,%40,%41,%42,%43,%44,%45,%46,%47,%48,%49,%50,%51,%52,%53,%54,%55,%56,%57,%58,%59,%60,%61,%62,%63,%64,%65,%66,%67,%68,%69,%70,%71,%72,%73,%74,%75,%76,%77,%78,%79,%80,%81,%82,%83,%84,%85,%86,%87,%88,%89,%90,%91,%92,%93,%94,%95}, %96, %97, p, 1, 1, 0, 1;}"
    : "+f"(d[0]),"+f"(d[1]),"+f"(d[2]),"+f"(d[3]),"+f"(d[4]),"+f"(d[5]),"+f"(d[6]),"+f"(d[7]),"+f"(d[8]),"+f"(d[9]),"+f"(d[10]),"+f"(d[11]),"+f"(d[12]),"+f"(d[13]),"+f"(d[14]),"+f"(d[15]),"+f"(d[16]),"+f"(d[17]),"+f"(d[18]),"+f"(d[19]),"+f"(d[20]),"+f"(d[21]),"+f"(d[22]),"+f"(d[23]),"+f"(d[24]),"+f"(d[25]),"+f"(d[26]),"+f"(d[27]),"+f"(d[28]),"+f"(d[29]),"+f"(d[30]),"+f"(d[31]),"+f"(d[32]),"+f"(d[33]),"+f"(d[34]),"+f"(d[35]),"+f"(d[36]),"+f"(d[37]),"+f"(d[38]),"+f"(d[39]),"+f"(d[40]),"+f"(d[41]),"+f"(d[42]),"+f"(d[43]),"+f"(d[44]),"+f"(d[45]),"+f"(d[46]),"+f"(d[47]),"+f"(d[48]),"+f"(d[49]),"+f"(d[50]),"+f"(d[51]),"+f"(d[52]),"+f"(d[53]),"+f"(d[54]),"+f"(d[55]),"+f"(d[56]),"+f"(d[57]),"+f"(d[58]),"+f"(d[59]),"+f"(d[60]),"+f"(d[61]),"+f"(d[62]),"+f"(d[63]),"+f"(d[64]),"+f"(d[65]),"+f"(d[66]),"+f"(d[67]),"+f"(d[68]),"+f"(d[69]),"+f"(d[70]),"+f"(d[71]),"+f"(d[72]),"+f"(d[73]),"+f"(d[74]),"+f"(d[75]),"+f"(d[76]),"+f"(d[77]),"+f"(d[78]),"+f"(d[79]),"+f"(d[80]),"+f"(d[81]),"+f"(d[82]),"+f"(d[83]),"+f"(d[84]),"+f"(d[85]),"+f"(d[86]),"+f"(d[87]),"+f"(d[88]),"+f"(d[89]),"+f"(d[90]),"+f"(d[91]),"+f"(d[92]),"+f"(d[93]),"+f"(d[94]),"+f"(d[95])
    : "l"(da), "l"(db), "r"(sc));
}
__device__ __forceinline__ void wgmma_ss_n64_a0b1(float (&d)[32], uint64_t da, uint64_t db, int sc) {
  asm volatile("{.reg .pred p; setp.ne.b32 p, %34, 0; wgmma.mma_async.sync.aligned.m64n64k16.f32.bf16.bf16 {%0,%1,%2,%3,%4,%5,%6,%7,%8,%9,%10,%11,%12,%13,%14,%15,%16,%17,%18,%19,%20,%21,%22,%23,%24,%25,%26,%27,%28,%29,%30,%31}, %32, %33, p, 1, 1, 0, 1;}"
    : "+f"(d[0]),"+f"(d[1]),"+f"(d[2]),"+f"(d[3]),"+f"(d[4]),"+f"(d[5]),"+f"(d[6]),"+f"(d[7]),"+f"(d[8]),"+f"(d[9]),"+f"(d[10]),"+f"(d[11]),"+f"(d[12]),"+f"(d[13]),"+f"(d[14]),"+f"(d[15]),"+f"(d[16]),"+f"(d[17]),"+f"(d[18]),"+f"(d[19]),"+f"(d[20]),"+f"(d[21]),"+f"(d[22]),"+f"(d[23]),"+f"(d[24]),"+f"(d[25]),"+f"(d[26]),"+f"(d[27]),"+f"(d[28]),"+f"(d[29]),"+f"(d[30]),"+f"(d[31])
    : "l"(da), "l"(db), "r"(sc));
}
__device__ __forceinline__ void wgmma_rs_n64_b0(float (&d)[32], uint32_t a0, uint32_t a1, uint32_t a2, uint32_t a3, uint64_t db, int sc) {
  asm volatile("{.reg .pred p; setp.ne.b32 p, %37, 0; wgmma.mma_async.sync.aligned.m64n64k16.f32.bf16.bf16 {%0,%1,%2,%3,%4,%5,%6,%7,%8,%9,%10,%11,%12,%13,%14,%15,%16,%17,%18,%19,%20,%21,%22,%23,%24,%25,%26,%27,%28,%29,%30,%31}, {%32,%33,%34,%35}, %36, p, 1, 1, 0;}"
    : "+f"(d[0]),"+f"(d[1]),"+f"(d[2]),"+f"(d[3]),"+f"(d[4]),"+f"(d[5]),"+f"(d[6]),"+f"(d[7]),"+f"(d[8]),"+f"(d[9]),"+f"(d[10]),"+f"(d[11]),"+f"(d[12]),"+f"(d[13]),"+f"(d[14]),"+f"(d[15]),"+f"(d[16]),"+f"(d[17]),"+f"(d[18]),"+f"(d[19]),"+f"(d[20]),"+f"(d[21]),"+f"(d[22]),"+f"(d[23]),"+f"(d[24]),"+f"(d[25]),"+f"(d[26]),"+f"(d[27]),"+f"(d[28]),"+f"(d[29]),"+f"(d[30]),"+f"(d[31])
    : "r"(a0), "r"(a1), "r"(a2), "r"(a3), "l"(db), "r"(sc));
}
__device__ __forceinline__ void wgmma_ss_n128_a0b1(float (&d)[64], uint64_t da, uint64_t db, int sc) {
  asm volatile("{.reg .pred p; setp.ne.b32 p, %66, 0; wgmma.mma_async.sync.aligned.m64n128k16.f32.bf16.bf16 {%0,%1,%2,%3,%4,%5,%6,%7,%8,%9,%10,%11,%12,%13,%14,%15,%16,%17,%18,%19,%20,%21,%22,%23,%24,%25,%26,%27,%28,%29,%30,%31,%32,%33,%34,%35,%36,%37,%38,%39,%40,%41,%42,%43,%44,%45,%46,%47,%48,%49,%50,%51,%52,%53,%54,%55,%56,%57,%58,%59,%60,%61,%62,%63}, %64, %65, p, 1, 1, 0, 1;}"
    : "+f"(d[0]),"+f"(d[1]),"+f"(d[2]),"+f"(d[3]),"+f"(d[4]),"+f"(d[5]),"+f"(d[6]),"+f"(d[7]),"+f"(d[8]),"+f"(d[9]),"+f"(d[10]),"+f"(d[11]),"+f"(d[12]),"+f"(d[13]),"+f"(d[14]),"+f"(d[15]),"+f"(d[16]),"+f"(d[17]),"+f"(d[18]),"+f"(d[19]),"+f"(d[20]),"+f"(d[21]),"+f"(d[22]),"+f"(d[23]),"+f"(d[24]),"+f"(d[25]),"+f"(d[26]),"+f"(d[27]),"+f"(d[28]),"+f"(d[29]),"+f"(d[30]),"+f"(d[31]),"+f"(d[32]),"+f"(d[33]),"+f"(d[34]),"+f"(d[35]),"+f"(d[36]),"+f"(d[37]),"+f"(d[38]),"+f"(d[39]),"+f"(d[40]),"+f"(d[41]),"+f"(d[42]),"+f"(d[43]),"+f"(d[44]),"+f"(d[45]),"+f"(d[46]),"+f"(d[47]),"+f"(d[48]),"+f"(d[49]),"+f"(d[50]),"+f"(d[51]),"+f"(d[52]),"+f"(d[53]),"+f"(d[54]),"+f"(d[55]),"+f"(d[56]),"+f"(d[57]),"+f"(d[58]),"+f"(d[59]),"+f"(d[60]),"+f"(d[61]),"+f"(d[62]),"+f"(d[63])
    : "l"(da), "l"(db), "r"(sc));
}
__device__ __forceinline__ void wgmma_rs_n128_b0(float (&d)[64], uint32_t a0, uint32_t a1, uint32_t a2, uint32_t a3, uint64_t db, int sc) {
  asm volatile("{.reg .pred p; setp.ne.b32 p, %69, 0; wgmma.mma_async.sync.aligned.m64n128k16.f32.bf16.bf16 {%0,%1,%2,%3,%4,%5,%6,%7,%8,%9,%10,%11,%12,%13,%14,%15,%16,%17,%18,%19,%20,%21,%22,%23,%24,%25,%26,%27,%28,%29,%30,%31,%32,%33,%34,%35,%36,%37,%38,%39,%40,%41,%42,%43,%44,%45,%46,%47,%48,%49,%50,%51,%52,%53,%54,%55,%56,%57,%58,%59,%60,%61,%62,%63}, {%64,%65,%66,%67}, %68, p, 1, 1, 0;}"
    : "+f"(d[0]),"+f"(d[1]),"+f"(d[2]),"+f"(d[3]),"+f"(d[4]),"+f"(d[5]),"+f"(d[6]),"+f"(d[7]),"+f"(d[8]),"+f"(d[9]),"+f"(d[10]),"+f"(d[11]),"+f"(d[12]),"+f"(d[13]),"+f"(d[14]),"+f"(d[15]),"+f"(d[16]),"+f"(d[17]),"+f"(d[18]),"+f"(d[19]),"+f"(d[20]),"+f"(d[21]),"+f"(d[22]),"+f"(d[23]),"+f"(d[24]),"+f"(d[25]),"+f"(d[26]),"+f"(d[27]),"+f"(d[28]),"+f"(d[29]),"+f"(d[30]),"+f"(d[31]),"+f"(d[32]),"+f"(d[33]),"+f"(d[34]),"+f"(d[35]),"+f"(d[36]),"+f"(d[37]),"+f"(d[38]),"+f"(d[39]),"+f"(d[40]),"+f"(d[41]),"+f"(d[42]),"+f"(d[43]),"+f"(d[44]),"+f"(d[45]),"+f"(d[46]),"+f"(d[47]),"+f"(d[48]),"+f"(d[49]),"+f"(d[50]),"+f"(d[51]),"+f"(d[52]),"+f"(d[53]),"+f"(d[54]),"+f"(d[55]),"+f"(d[56]),"+f"(d[57]),"+f"(d[58]),"+f"(d[59]),"+f"(d[60]),"+f"(d[61]),"+f"(d[62]),"+f"(d[63])
    : "r"(a0), "r"(a1), "r"(a2), "r"(a3), "l"(db), "r"(sc));
}
__device__ __forceinline__ void wgmma_rs_n128_b1(float (&d)[64], uint32_t a0, uint32_t a1, uint32_t a2, uint32_t a3, uint64_t db, int sc) {
  asm volatile("{.reg .pred p; setp.ne.b32 p, %69, 0; wgmma.mma_async.sync.aligned.m64n128k16.f32.bf16.bf16 {%0,%1,%2,%3,%4,%5,%6,%7,%8,%9,%10,%11,%12,%13,%14,%15,%16,%17,%18,%19,%20,%21,%22,%23,%24,%25,%26,%27,%28,%29,%30,%31,%32,%33,%34,%35,%36,%37,%38,%39,%40,%41,%42,%43,%44,%45,%46,%47,%48,%49,%50,%51,%52,%53,%54,%55,%56,%57,%58,%59,%60,%61,%62,%63}, {%64,%65,%66,%67}, %68, p, 1, 1, 1;}"
    : "+f"(d[0]),"+f"(d[1]),"+f"(d[2]),"+f"(d[3]),"+f"(d[4]),"+f"(d[5]),"+f"(d[6]),"+f"(d[7]),"+f"(d[8]),"+f"(d[9]),"+f"(d[10]),"+f"(d[11]),"+f"(d[12]),"+f"(d[13]),"+f"(d[14]),"+f"(d[15]),"+f"(d[16]),"+f"(d[17]),"+f"(d[18]),"+f"(d[19]),"+f"(d[20]),"+f"(d[21]),"+f"(d[22]),"+f"(d[23]),"+f"(d[24]),"+f"(d[25]),"+f"(d[26]),"+f"(d[27]),"+f"(d[28]),"+f"(d[29]),"+f"(d[30]),"+f"(d[31]),"+f"(d[32]),"+f"(d[33]),"+f"(d[34]),"+f"(d[35]),"+f"(d[36]),"+f"(d[37]),"+f"(d[38]),"+f"(d[39]),"+f"(d[40]),"+f"(d[41]),"+f"(d[42]),"+f"(d[43]),"+f"(d[44]),"+f"(d[45]),"+f"(d[46]),"+f"(d[47]),"+f"(d[48]),"+f"(d[49]),"+f"(d[50]),"+f"(d[51]),"+f"(d[52]),"+f"(d[53]),"+f"(d[54]),"+f"(d[55]),"+f"(d[56]),"+f"(d[57]),"+f"(d[58]),"+f"(d[59]),"+f"(d[60]),"+f"(d[61]),"+f"(d[62]),"+f"(d[63])
    : "r"(a0), "r"(a1), "r"(a2), "r"(a3), "l"(db), "r"(sc));
}
__device__ __forceinline__ void wgmma_rs_n32_b0(float (&d)[16], uint32_t a0, uint32_t a1, uint32_t a2, uint32_t a3, uint64_t db, int sc) {
  asm volatile("{.reg .pred p; setp.ne.b32 p, %21, 0; wgmma.mma_async.sync.aligned.m64n32k16.f32.bf16.bf16 {%0,%1,%2,%3,%4,%5,%6,%7,%8,%9,%10,%11,%12,%13,%14,%15}, {%16,%17,%18,%19}, %20, p, 1, 1, 0;}"
    : "+f"(d[0]),"+f"(d[1]),"+f"(d[2]),"+f"(d[3]),"+f"(d[4]),"+f"(d[5]),"+f"(d[6]),"+f"(d[7]),"+f"(d[8]),"+f"(d[9]),"+f"(d[10]),"+f"(d[11]),"+f"(d[12]),"+f"(d[13]),"+f"(d[14]),"+f"(d[15])
    : "r"(a0), "r"(a1), "r"(a2), "r"(a3), "l"(db), "r"(sc));
}
__device__ __forceinline__ void wgmma_ss_n32_a1b0(float (&d)[16], uint64_t da, uint64_t db, int sc) {
  asm volatile("{.reg .pred p; setp.ne.b32 p, %18, 0; wgmma.mma_async.sync.aligned.m64n32k16.f32.bf16.bf16 {%0,%1,%2,%3,%4,%5,%6,%7,%8,%9,%10,%11,%12,%13,%14,%15}, %16, %17, p, 1, 1, 1, 0;}"
    : "+f"(d[0]),"+f"(d[1]),"+f"(d[2]),"+f"(d[3]),"+f"(d[4]),"+f"(d[5]),"+f"(d[6]),"+f"(d[7]),"+f"(d[8]),"+f"(d[9]),"+f"(d[10]),"+f"(d[11]),"+f"(d[12]),"+f"(d[13]),"+f"(d[14]),"+f"(d[15])
    : "l"(da), "l"(db), "r"(sc));
}
__device__ __forceinline__ void wgmma_ss_n40_a1b0(float (&d)[20], uint64_t da, uint64_t db, int sc) {
  asm volatile("{.reg .pred p; setp.ne.b32 p, %22, 0; wgmma.mma_async.sync.aligned.m64n40k16.f32.bf16.bf16 {%0,%1,%2,%3,%4,%5,%6,%7,%8,%9,%10,%11,%12,%13,%14,%15,%16,%17,%18,%19}, %20, %21, p, 1, 1, 1, 0;}"
    : "+f"(d[0]),"+f"(d[1]),"+f"(d[2]),"+f"(d[3]),"+f"(d[4]),"+f"(d[5]),"+f"(d[6]),"+f"(d[7]),"+f"(d[8]),"+f"(d[9]),"+f"(d[10]),"+f"(d[11]),"+f"(d[12]),"+f"(d[13]),"+f"(d[14]),"+f"(d[15]),"+f"(d[16]),"+f"(d[17]),"+f"(d[18]),"+f"(d[19])
    : "l"(da), "l"(db), "r"(sc));
}
__device__ __forceinline__ void wgmma_ss_n40_a1b1(float (&d)[20], uint64_t da, uint64_t db, int sc) {
  asm volatile("{.reg .pred p; setp.ne.b32 p, %22, 0; wgmma.mma_async.sync.aligned.m64n40k16.f32.bf16.bf16 {%0,%1,%2,%3,%4,%5,%6,%7,%8,%9,%10,%11,%12,%13,%14,%15,%16,%17,%18,%19}, %20, %21, p, 1, 1, 1, 1;}"
    : "+f"(d[0]),"+f"(d[1]),"+f"(d[2]),"+f"(d[3]),"+f"(d[4]),"+f"(d[5]),"+f"(d[6]),"+f"(d[7]),"+f"(d[8]),"+f"(d[9]),"+f"(d[10]),"+f"(d[11]),"+f"(d[12]),"+f"(d[13]),"+f"(d[14]),"+f"(d[15]),"+f"(d[16]),"+f"(d[17]),"+f"(d[18]),"+f"(d[19])
    : "l"(da), "l"(db), "r"(sc));
}
__device__ __forceinline__ void wgmma_rs_n40_b0(float (&d)[20], uint32_t a0, uint32_t a1, uint32_t a2, uint32_t a3, uint64_t db, int sc) {
  asm volatile("{.reg .pred p; setp.ne.b32 p, %25, 0; wgmma.mma_async.sync.aligned.m64n40k16.f32.bf16.bf16 {%0,%1,%2,%3,%4,%5,%6,%7,%8,%9,%10,%11,%12,%13,%14,%15,%16,%17,%18,%19}, {%20,%21,%22,%23}, %24, p, 1, 1, 0;}"
    : "+f"(d[0]),"+f"(d[1]),"+f"(d[2]),"+f"(d[3]),"+f"(d[4]),"+f"(d[5]),"+f"(d[6]),"+f"(d[7]),"+f"(d[8]),"+f"(d[9]),"+f"(d[10]),"+f"(d[11]),"+f"(d[12]),"+f"(d[13]),"+f"(d[14]),"+f"(d[15]),"+f"(d[16]),"+f"(d[17]),"+f"(d[18]),"+f"(d[19])
    : "r"(a0), "r"(a1), "r"(a2), "r"(a3), "l"(db), "r"(sc));
}
__device__ __forceinline__ void wgmma_ssz_n256_a0b1(float (&d)[128], uint64_t da, uint64_t db) {
  asm volatile("{.reg .pred p; setp.ne.b32 p, 0, 0; wgmma.mma_async.sync.aligned.m64n256k16.f32.bf16.bf16 {%0,%1,%2,%3,%4,%5,%6,%7,%8,%9,%10,%11,%12,%13,%14,%15,%16,%17,%18,%19,%20,%21,%22,%23,%24,%25,%26,%27,%28,%29,%30,%31,%32,%33,%34,%35,%36,%37,%38,%39,%40,%41,%42,%43,%44,%45,%46,%47,%48,%49,%50,%51,%52,%53,%54,%55,%56,%57,%58,%59,%60,%61,%62,%63,%64,%65,%66,%67,%68,%69,%70,%71,%72,%73,%74,%75,%76,%77,%78,%79,%80,%81,%82,%83,%84,%85,%86,%87,%88,%89,%90,%91,%92,%93,%94,%95,%96,%97,%98,%99,%100,%101,%102,%103,%104,%105,%106,%107,%108,%109,%110,%111,%112,%113,%114,%115,%116,%117,%118,%119,%120,%121,%122,%123,%124,%125,%126,%127}, %128, %129, p, 1, 1, 0, 1;}"
    : "=f"(d[0]),"=f"(d[1]),"=f"(d[2]),"=f"(d[3]),"=f"(d[4]),"=f"(d[5]),"=f"(d[6]),"=f"(d[7]),"=f"(d[8]),"=f"(d[9]),"=f"(d[10]),"=f"(d[11]),"=f"(d[12]),"=f"(d[13]),"=f"(d[14]),"=f"(d[15]),"=f"(d[16]),"=f"(d[17]),"=f"(d[18]),"=f"(d[19]),"=f"(d[20]),"=f"(d[21]),"=f"(d[22]),"=f"(d[23]),"=f"(d[24]),"=f"(d[25]),"=f"(d[26]),"=f"(d[27]),"=f"(d[28]),"=f"(d[29]),"=f"(d[30]),"=f"(d[31]),"=f"(d[32]),"=f"(d[33]),"=f"(d[34]),"=f"(d[35]),"=f"(d[36]),"=f"(d[37]),"=f"(d[38]),"=f"(d[39]),"=f"(d[40]),"=f"(d[41]),"=f"(d[42]),"=f"(d[43]),"=f"(d[44]),"=f"(d[45]),"=f"(d[46]),"=f"(d[47]),"=f"(d[48]),"=f"(d[49]),"=f"(d[50]),"=f"(d[51]),"=f"(d[52]),"=f"(d[53]),"=f"(d[54]),"=f"(d[55]),"=f"(d[56]),"=f"(d[57]),"=f"(d[58]),"=f"(d[59]),"=f"(d[60]),"=f"(d[61]),"=f"(d[62]),"=f"(d[63]),"=f"(d[64]),"=f"(d[65]),"=f"(d[66]),"=f"(d[67]),"=f"(d[68]),"=f"(d[69]),"=f"(d[70]),"=f"(d[71]),"=f"(d[72]),"=f"(d[73]),"=f"(d[74]),"=f"(d[75]),"=f"(d[76]),"=f"(d[77]),"=f"(d[78]),"=f"(d[79]),"=f"(d[80]),"=f"(d[81]),"=f"(d[82]),"=f"(d[83]),"=f"(d[84]),"=f"(d[85]),"=f"(d[86]),"=f"(d[87]),"=f"(d[88]),"=f"(d[89]),"=f"(d[90]),"=f"(d[91]),"=f"(d[92]),"=f"(d[93]),"=f"(d[94]),"=f"(d[95]),"=f"(d[96]),"=f"(d[97]),"=f"(d[98]),"=f"(d[99]),"=f"(d[100]),"=f"(d[101]),"=f"(d[102]),"=f"(d[103]),"=f"(d[104]),"=f"(d[105]),"=f"(d[106]),"=f"(d[107]),"=f"(d[108]),"=f"(d[109]),"=f"(d[110]),"=f"(d[111]),"=f"(d[112]),"=f"(d[113]),"=f"(d[114]),"=f"(d[115]),"=f"(d[116]),"=f"(d[117]),"=f"(d[118]),"=f"(d[119]),"=f"(d[120]),"=f"(d[121]),"=f"(d[122]),"=f"(d[123]),"=f"(d[124]),"=f"(d[125]),"=f"(d[126]),"=f"(d[127])
    : "l"(da), "l"(db));
}
__device__ __forceinline__ void wgmma_ssz_n128_a0b1(float (&d)[64], uint64_t da, uint64_t db) {
  asm volatile("{.reg .pred p; setp.ne.b32 p, 0, 0; wgmma.mma_async.sync.aligned.m64n128k16.f32.bf16.bf16 {%0,%1,%2,%3,%4,%5,%6,%7,%8,%9,%10,%11,%12,%13,%14,%15,%16,%17,%18,%19,%20,%21,%22,%23,%24,%25,%26,%27,%28,%29,%30,%31,%32,%33,%34,%35,%36,%37,%38,%39,%40,%41,%42,%43,%44,%45,%46,%47,%48,%49,%50,%51,%52,%53,%54,%55,%56,%57,%58,%59,%60,%61,%62,%63}, %64, %65, p, 1, 1, 0, 1;}"
    : "=f"(d[0]),"=f"(d[1]),"=f"(d[2]),"=f"(d[3]),"=f"(d[4]),"=f"(d[5]),"=f"(d[6]),"=f"(d[7]),"=f"(d[8]),"=f"(d[9]),"=f"(d[10]),"=f"(d[11]),"=f"(d[12]),"=f"(d[13]),"=f"(d[14]),"=f"(d[15]),"=f"(d[16]),"=f"(d[17]),"=f"(d[18]),"=f"(d[19]),"=f"(d[20]),"=f"(d[21]),"=f"(d[22]),"=f"(d[23]),"=f"(d[24]),"=f"(d[25]),"=f"(d[26]),"=f"(d[27]),"=f"(d[28]),"=f"(d[29]),"=f"(d[30]),"=f"(d[31]),"=f"(d[32]),"=f"(d[33]),"=f"(d[34]),"=f"(d[35]),"=f"(d[36]),"=f"(d[37]),"=f"(d[38]),"=f"(d[39]),"=f"(d[40]),"=f"(d[41]),"=f"(d[42]),"=f"(d[43]),"=f"(d[44]),"=f"(d[45]),"=f"(d[46]),"=f"(d[47]),"=f"(d[48]),"=f"(d[49]),"=f"(d[50]),"=f"(d[51]),"=f"(d[52]),"=f"(d[53]),"=f"(d[54]),"=f"(d[55]),"=f"(d[56]),"=f"(d[57]),"=f"(d[58]),"=f"(d[59]),"=f"(d[60]),"=f"(d[61]),"=f"(d[62]),"=f"(d[63])
    : "l"(da), "l"(db));
}


__device__ __forceinline__ void wg_fence() { asm volatile("wgmma.fence.sync.aligned;" ::: "memory"); }
__device__ __forceinline__ void wg_commit() { asm volatile("wgmma.commit_group.sync.aligned;" ::: "memory"); }
template <int N> __device__ __forceinline__ void wg_wait() { asm volatile("wgmma.wait_group.sync.aligned %0;" ::"n"(N) : "memory"); }
template <int N> __device__ __forceinline__ void fence_regs(float (&d)[N]) {
#pragma unroll
  for (int i = 0; i < N; i++) asm volatile("" : "+f"(d[i])::"memory");
}
template <int N> __device__ __forceinline__ void fence_regs(uint32_t (&d)[N]) {
#pragma unroll
  for (int i = 0; i < N; i++) asm volatile("" : "+r"(d[i])::"memory");
}
__device__ __forceinline__ uint64_t mk_desc(uint32_t lo, uint32_t hi) {
  uint64_t d;
  asm("mov.b64 %0, {%1,%2};" : "=l"(d) : "r"(lo), "r"(hi));
  return d;
}
constexpr uint32_t DHI_SW128 = (1024u >> 4) | (1u << 30);
__device__ __forceinline__ uint32_t desc_lo(uint32_t addr, uint32_t lbo) { return ((addr & 0x3FFFF) >> 4) | ((lbo >> 4) << 16); }

__device__ __forceinline__ void mbar_init(uint32_t bar, uint32_t cnt) { asm volatile("mbarrier.init.shared::cta.b64 [%0], %1;" ::"r"(bar), "r"(cnt) : "memory"); }
__device__ __forceinline__ uint32_t mbar_try(uint32_t bar, uint32_t par) {
  uint32_t ok;
  asm volatile("{.reg .pred p; mbarrier.try_wait.parity.shared::cta.b64 p, [%1], %2; selp.u32 %0, 1, 0, p;}" : "=r"(ok) : "r"(bar), "r"(par) : "memory");
  return ok;
}
__device__ __noinline__ void mbar_wait_slow(uint32_t bar, uint32_t par) {
  for (int i = 0; i < (1 << 22); i++)
    if (mbar_try(bar, par)) return;
  __trap();
}
__device__ __forceinline__ void mbar_wait(uint32_t bar, uint32_t par) {
  asm volatile(
      "{\n.reg .pred p;\n.reg .u32 c;\n"
      "mbarrier.try_wait.parity.shared::cta.b64 p, [%0], %1;\n"
      "@p bra DONE;\n"
      "mov.u32 c, 0;\n"
      "LOOP:\n"
      "mbarrier.try_wait.parity.shared::cta.b64 p, [%0], %1;\n"
      "@p bra DONE;\n"
      "add.u32 c, c, 1;\n"
      "setp.lt.u32 p, c, 4000000;\n"
      "@p bra LOOP;\n"
      "trap;\n"
      "DONE:\n}" ::"r"(bar), "r"(par) : "memory");
}
__device__ __forceinline__ void mbar_wait2(uint32_t b0, uint32_t p0, uint32_t b1, uint32_t p1) {
  asm volatile(
      "{\n.reg .pred p, q;\n.reg .u32 c;\n"
      "mov.u32 c, 0;\n"
      "LOOP:\n"
      "mbarrier.try_wait.parity.shared::cta.b64 p, [%0], %1;\n"
      "mbarrier.try_wait.parity.shared::cta.b64 q, [%2], %3;\n"
      "and.pred p, p, q;\n"
      "@p bra DONE;\n"
      "add.u32 c, c, 1;\n"
      "setp.lt.u32 p, c, 4000000;\n"
      "@p bra LOOP;\n"
      "trap;\n"
      "DONE:\n}" ::"r"(b0), "r"(p0), "r"(b1), "r"(p1) : "memory");
}
__device__ __forceinline__ void mbar_wait_cl(uint32_t bar, uint32_t par) {
  asm volatile(
      "{\n.reg .pred p;\n.reg .u32 c;\n"
      "mbarrier.try_wait.parity.acquire.cluster.shared::cta.b64 p, [%0], %1;\n"
      "@p bra DONE;\n"
      "mov.u32 c, 0;\n"
      "LOOP:\n"
      "mbarrier.try_wait.parity.acquire.cluster.shared::cta.b64 p, [%0], %1;\n"
      "@p bra DONE;\n"
      "add.u32 c, c, 1;\n"
      "setp.lt.u32 p, c, 4000000;\n"
      "@p bra LOOP;\n"
      "trap;\n"
      "DONE:\n}" ::"r"(bar), "r"(par) : "memory");
}
__device__ __forceinline__ void mbar_arrive(uint32_t bar) { asm volatile("mbarrier.arrive.shared::cta.b64 _, [%0];" ::"r"(bar) : "memory"); }
__device__ __forceinline__ void mbar_arrive_cl(uint32_t bar) { asm volatile("mbarrier.arrive.shared::cluster.b64 _, [%0];" ::"r"(bar) : "memory"); }
__device__ __forceinline__ void mbar_expect(uint32_t bar, uint32_t bytes) { asm volatile("mbarrier.arrive.expect_tx.shared::cta.b64 _, [%0], %1;" ::"r"(bar), "r"(bytes) : "memory"); }
__device__ __forceinline__ void mbar_expect_cl(uint32_t bar, uint32_t bytes) { asm volatile("mbarrier.arrive.expect_tx.shared::cluster.b64 _, [%0], %1;" ::"r"(bar), "r"(bytes) : "memory"); }
__device__ __forceinline__ uint32_t mapa(uint32_t addr, uint32_t rank) {
  uint32_t r;
  asm("mapa.shared::cluster.u32 %0, %1, %2;" : "=r"(r) : "r"(addr), "r"(rank));
  return r;
}
__device__ __forceinline__ void st_async32(uint32_t addr, uint32_t v, uint32_t bar) {
  asm volatile("st.async.shared::cluster.mbarrier::complete_tx::bytes.b32 [%0], %1, [%2];" ::"r"(addr), "r"(v), "r"(bar) : "memory");
}
__device__ __forceinline__ void st_async64(uint32_t addr, uint32_t a, uint32_t b, uint32_t bar) {
  asm volatile("st.async.shared::cluster.mbarrier::complete_tx::bytes.v2.b32 [%0], {%1,%2}, [%3];" ::"r"(addr), "r"(a), "r"(b), "r"(bar) : "memory");
}
__device__ __forceinline__ void st_async128(uint32_t addr, uint32_t a, uint32_t b, uint32_t c, uint32_t d, uint32_t bar) {
  asm volatile("st.async.shared::cluster.mbarrier::complete_tx::bytes.v4.b32 [%0], {%1,%2,%3,%4}, [%5];" ::"r"(addr), "r"(a), "r"(b), "r"(c), "r"(d), "r"(bar) : "memory");
}
__device__ __forceinline__ void bar_sync(int id, int n) { asm volatile("bar.sync %0, %1;" ::"r"(id), "r"(n) : "memory"); }
__device__ __forceinline__ void bar_arrive(int id, int n) { asm volatile("bar.arrive %0, %1;" ::"r"(id), "r"(n) : "memory"); }
__device__ __forceinline__ void cluster_sync() { asm volatile("barrier.cluster.arrive.aligned;\nbarrier.cluster.wait.aligned;" ::: "memory"); }
__device__ __forceinline__ bool elect() {
  uint32_t p;
  asm volatile("{.reg .pred q; elect.sync _|q, 0xffffffff; selp.u32 %0, 1, 0, q;}" : "=r"(p));
  return p != 0;
}
__device__ __forceinline__ void fence_async_smem() { asm volatile("fence.proxy.async.shared::cta;" ::: "memory"); }
__device__ __forceinline__ void fence_async_all() { asm volatile("fence.proxy.async;" ::: "memory"); }
__device__ __forceinline__ void tma2d(uint32_t dst, const CUtensorMap* m, int c0, int c1, uint32_t bar) {
  asm volatile("cp.async.bulk.tensor.2d.shared::cluster.global.mbarrier::complete_tx::bytes [%0], [%1, {%2,%3}], [%4];" ::"r"(dst), "l"(m), "r"(c0), "r"(c1), "r"(bar) : "memory");
}
__device__ __forceinline__ void tma2d_mc(uint32_t dst, const CUtensorMap* m, int c0, int c1, uint32_t bar, uint16_t mask) {
  asm volatile("cp.async.bulk.tensor.2d.shared::cluster.global.mbarrier::complete_tx::bytes.multicast::cluster [%0], [%1, {%2,%3}], [%4], %5;" ::"r"(dst), "l"(m), "r"(c0), "r"(c1), "r"(bar), "h"(mask) : "memory");
}
__device__ __forceinline__ void tma3d(uint32_t dst, const CUtensorMap* m, int c0, int c1, int c2, uint32_t bar) {
  asm volatile("cp.async.bulk.tensor.3d.shared::cluster.global.mbarrier::complete_tx::bytes [%0], [%1, {%2,%3,%4}], [%5];" ::"r"(dst), "l"(m), "r"(c0), "r"(c1), "r"(c2), "r"(bar) : "memory");
}
__device__ __forceinline__ void tma3d_mc(uint32_t dst, const CUtensorMap* m, int c0, int c1, int c2, uint32_t bar, uint16_t mask) {
  asm volatile("cp.async.bulk.tensor.3d.shared::cluster.global.mbarrier::complete_tx::bytes.multicast::cluster [%0], [%1, {%2,%3,%4}], [%5], %6;" ::"r"(dst), "l"(m), "r"(c0), "r"(c1), "r"(c2), "r"(bar), "h"(mask) : "memory");
}
__device__ __forceinline__ uint32_t ld_acquire(const unsigned* p) {
  uint32_t v;
  asm volatile("ld.acquire.gpu.global.u32 %0, [%1];" : "=r"(v) : "l"(p) : "memory");
  return v;
}
__device__ __forceinline__ uint32_t pack_bf16(float lo, float hi) {
  uint32_t r;
  asm("cvt.rn.bf16x2.f32 %0, %1, %2;" : "=r"(r) : "f"(hi), "f"(lo));
  return r;
}
__device__ __forceinline__ float ex2(float x) {
  float y;
  asm("ex2.approx.ftz.f32 %0, %1;" : "=f"(y) : "f"(x));
  return y;
}
__device__ __forceinline__ float rcp(float x) {
  float y;
  asm("rcp.approx.ftz.f32 %0, %1;" : "=f"(y) : "f"(x));
  return y;
}
__device__ __forceinline__ void stg128(void* p, uint32_t a, uint32_t b, uint32_t c, uint32_t d) {
  asm volatile("st.global.v4.b32 [%0], {%1,%2,%3,%4};" ::"l"(p), "r"(a), "r"(b), "r"(c), "r"(d) : "memory");
}
__device__ __forceinline__ void sts128(uint32_t a, uint32_t x, uint32_t y, uint32_t z, uint32_t w) {
  asm volatile("st.shared.v4.b32 [%0], {%1,%2,%3,%4};" ::"r"(a), "r"(x), "r"(y), "r"(z), "r"(w) : "memory");
}
__device__ __forceinline__ void stsm4(uint32_t a, uint32_t r0, uint32_t r1, uint32_t r2, uint32_t r3) {
  asm volatile("stmatrix.sync.aligned.m8n8.x4.shared.b16 [%0], {%1,%2,%3,%4};" ::"r"(a), "r"(r0), "r"(r1), "r"(r2), "r"(r3) : "memory");
}
__device__ __forceinline__ void arrive_elect(uint32_t bar) {
  asm volatile("{.reg .pred q; elect.sync _|q, 0xffffffff; @q mbarrier.arrive.shared::cta.b64 _, [%0];}" ::"r"(bar) : "memory");
}
__device__ __forceinline__ void sched_fence(uint32_t v) { asm volatile("{.reg .pred p; setp.eq.u32 p, %0, 0; @p trap;}" ::"r"(v) : "memory"); }
template <int V> struct IC { static constexpr int value = V; };
template <int A, int B, class F> __device__ __forceinline__ void static_for(F&& f) {
  if constexpr (A < B) {
    f(IC<A>());
    static_for<A + 1, B>(f);
  }
}
__device__ __forceinline__ uint32_t lds32(uint32_t a) {
  uint32_t v;
  asm volatile("ld.shared.b32 %0, [%1];" : "=r"(v) : "r"(a) : "memory");
  return v;
}

constexpr int MAXTASK = 256 + 256 + 200;
constexpr int T_KV = 0, T_FA = 1, T_OA = 2, T_OB = 3, T_SA = 4, T_SB = 5, T_XB = 7;
constexpr uint32_t TASK_END = 0xFFFF, T_NOP = 6;
#ifndef NCL
#define NCL 34
#endif
constexpr int NEARLY = 34;
struct MainParams {
  CUtensorMap ckv, wuk, wuv, ax, wq, scr, woa, wob, scr_st, out_st, woa1, wob1, scr2, scr64;
  uint32_t ntask;
  uint16_t tasks[MAXTASK];
};

constexpr int M_GR = 16384, M_NG = 12;
constexpr int M_STG = M_GR * M_NG;
constexpr int M_BAR = M_STG + 32768;
constexpr int M_FULL = M_BAR, M_EMPTY = M_BAR + 64, M_TFULL = M_BAR + 128, M_TEMPTY = M_BAR + 160, M_EPI = M_BAR + 192, M_SFREE = M_BAR + 224, M_GO = M_BAR + 240,
              M_XR = M_BAR + 248, M_TSLOT = M_BAR + 256;
constexpr int M_SMEM = M_BAR + 512 + 1024;
constexpr int OX_TARGET = 64;

#ifndef PF_ON
#define PF_ON 0
#endif
#ifndef ST_ROWS
#define ST_ROWS 16
#endif
#ifndef ST_DEPTH
#define ST_DEPTH 1
#endif
#ifndef KV_SKEW
#define KV_SKEW 7
#endif
#ifndef FM_NJ
#define FM_NJ 2
#endif
#ifndef Q_SKEW
#define Q_SKEW 6
#endif
struct Ring {
  uint32_t e, g;
  __device__ __forceinline__ uint32_t take(int z) {
    if (g + z > M_NG) g = 0;
    const uint32_t r = g;
    g += z;
    return r;
  }
  __device__ __forceinline__ uint32_t bar() const { return (e & 7) * 8; }
  __device__ __forceinline__ uint32_t par() const { return (e >> 3) & 1; }
};
__device__ __forceinline__ int task_entries(int type, int p) { return type == T_NOP ? 0 : type == T_KV ? 9 : type == T_FA ? 9 + 2 * (2 * p + 2) : type == T_XB ? 17 : type >= T_SA ? 33 : 65; }
__device__ __forceinline__ int entry_size(int type, int it) { return type == T_FA || (type == T_KV && it == 8) ? 2 : 3; }

__device__ __forceinline__ void need_flag(uint32_t& v, int bit, const unsigned* flag, unsigned target) {
  for (int it = 0; !((__ballot_sync(0xffffffffu, v >= target) >> bit) & 1); it++) {
    if (it > (1 << 21)) __trap();
    if (it) __nanosleep(40);
    v = ld_acquire(flag);
  }
}

constexpr float SM_C = 0.08838834764831845f * 1.4426950408889634f;
template <int NJ> __device__ __forceinline__ void softmax_max(const float (&s)[64], float& m0, float& m1, float& a0, float& a1, float& c0, float& c1) {
  float x0 = fmaxf(s[0], s[4]), y0 = fmaxf(s[1], s[5]), x1 = fmaxf(s[2], s[6]), y1 = fmaxf(s[3], s[7]);
#pragma unroll
  for (int j = 2; j < NJ; j++) {
    x0 = fmaxf(x0, s[4 * j]);
    y0 = fmaxf(y0, s[4 * j + 1]);
    x1 = fmaxf(x1, s[4 * j + 2]);
    y1 = fmaxf(y1, s[4 * j + 3]);
  }
  x0 = fmaxf(x0, y0);
  x1 = fmaxf(x1, y1);
  x0 = fmaxf(x0, __shfl_xor_sync(0xffffffffu, x0, 1));
  x1 = fmaxf(x1, __shfl_xor_sync(0xffffffffu, x1, 1));
  x0 = fmaxf(x0, __shfl_xor_sync(0xffffffffu, x0, 2));
  x1 = fmaxf(x1, __shfl_xor_sync(0xffffffffu, x1, 2));
  const float n0 = fmaxf(m0, x0), n1 = fmaxf(m1, x1);
  a0 = ex2((m0 - n0) * SM_C);
  a1 = ex2((m1 - n1) * SM_C);
  m0 = n0;
  m1 = n1;
  c0 = -n0 * SM_C;
  c1 = -n1 * SM_C;
}
template <int J0, int J1> __device__ __forceinline__ void softmax_exp(const float (&s)[64], uint32_t (&p)[32], float c0, float c1, float (&t)[4]) {
#pragma unroll
  for (int j = J0; j < J1; j++) {
    const float e0 = ex2(fmaf(s[4 * j], SM_C, c0)), e1 = ex2(fmaf(s[4 * j + 1], SM_C, c0));
    const float e2 = ex2(fmaf(s[4 * j + 2], SM_C, c1)), e3 = ex2(fmaf(s[4 * j + 3], SM_C, c1));
    p[2 * j] = pack_bf16(e0, e1);
    p[2 * j + 1] = pack_bf16(e2, e3);
    if (j == 0) { t[0] = e0; t[1] = e1; t[2] = e2; t[3] = e3; }
    else { t[0] += e0; t[1] += e1; t[2] += e2; t[3] += e3; }
  }
}
template <int I0, int I1> __device__ __forceinline__ void fence_part(uint32_t (&d)[32]) {
#pragma unroll
  for (int i = I0; i < I1; i++) asm volatile("" : "+r"(d[i])::"memory");
}
template <int J0, int J1, int N> __device__ __forceinline__ void stage_tile(const float (&d)[N], uint32_t a, float f0, float f1) {
#pragma unroll
  for (int j = J0; j < J1; j += 2)
    stsm4((a ^ (((j - J0) & 7) << 4)) + ((j - J0) >> 3) * 8192, pack_bf16(d[4 * j] * f0, d[4 * j + 1] * f0), pack_bf16(d[4 * j + 2] * f1, d[4 * j + 3] * f1),
          pack_bf16(d[4 * j + 4] * f0, d[4 * j + 5] * f0), pack_bf16(d[4 * j + 6] * f1, d[4 * j + 7] * f1));
}
template <int J0, int J1> __device__ __forceinline__ void causal_mask(float (&s)[64], int lim0) {
#pragma unroll
  for (int j = J0; j < J1; j++) {
    if (8 * j > lim0) s[4 * j] = -INFINITY;
    if (8 * j + 1 > lim0) s[4 * j + 1] = -INFINITY;
    if (8 * j > lim0 + 8) s[4 * j + 2] = -INFINITY;
    if (8 * j + 1 > lim0 + 8) s[4 * j + 3] = -INFINITY;
  }
}

__global__ void __cluster_dims__(2, 1, 1) __launch_bounds__(384, 1) main_kernel(const __grid_constant__ MainParams P) {
  extern __shared__ uint8_t smem_raw[];
  const uint32_t sb = ((uint32_t)__cvta_generic_to_shared(smem_raw) + 1023u) & ~1023u;
  const int warp = __shfl_sync(0xffffffffu, threadIdx.x >> 5, 0), lane = threadIdx.x & 31;
  uint32_t rank;
  asm("mov.u32 %0, %%cluster_ctarank;" : "=r"(rank));
  rank = __shfl_sync(0xffffffffu, rank, 0);
#ifdef DEV_TRACE
  if (threadIdx.x == 0) { long long c; asm volatile("mov.u64 %0, %%globaltimer;" : "=l"(c)); g_trace[blockIdx.x * 4096 + 4090] = c; }
#endif
  const uint32_t cluster = blockIdx.x >> 1;
  static_assert(M_EMPTY == M_FULL + 64 && M_TFULL == M_FULL + 128 && M_TEMPTY == M_FULL + 160 && M_EPI == M_FULL + 192 && M_SFREE == M_FULL + 224 && M_XR == M_FULL + 248, "barriers");
  if (warp >= 1 && warp <= 8 && elect()) {
    const uint32_t b = sb + M_FULL + 32 * (warp & 7), cnt = (warp & 14) == 2 ? 16 : warp == 5 ? 22 : warp == 6 ? 4 : 1;
#pragma unroll
    for (int i = 0; i < 4; i++) mbar_init(b + 8 * i, cnt);
    asm volatile("fence.mbarrier_init.release.cluster;" ::: "memory");
    if (warp == 8 && cluster < NEARLY) {
#pragma unroll 1
      for (int i = 0; i < 4; i++) {
        const uint32_t st = sb + i * 3 * M_GR, fb = sb + M_FULL + 8 * i;
        mbar_expect(fb, 49152);
        tma2d(st, &P.ckv, i * 64, (cluster & 7) * 256 + rank * 128, fb);
        tma3d(st + 16384, &P.wuk, 0, i * 64, (cluster >> 3) * 2, fb);
        tma3d(st + 32768, &P.wuv, 0, i * 64, (cluster >> 3) * 2, fb);
      }
    }
  }
  __syncwarp();
  if (warp == 8) TRM(5);
  asm volatile("barrier.cluster.arrive.relaxed.aligned;" ::: "memory");
  const uint32_t task0 = cluster < NEARLY ? cluster : (uint32_t)P.tasks[cluster];
  auto started = [&]() { asm volatile("barrier.cluster.wait.aligned;" ::: "memory"); };
  const uint32_t tempty0 = mapa(sb + M_TEMPTY, 0);
  auto read_task = [&](int ti) -> uint32_t {
    if (ti == 0) return task0;
    mbar_wait(sb + M_TFULL + 8 * ((ti - 1) & 3), ((ti - 1) >> 2) & 1);
    return __shfl_sync(0xffffffffu, lds32(sb + M_TSLOT + 4 * ((ti - 1) & 3)), 0);
  };
  auto free_task = [&](int ti) {
    if (ti > 0 && lane == 0) mbar_arrive_cl(tempty0 + 8 * ((ti - 1) & 3));
  };

  if (warp >= 8) {
    asm volatile("setmaxnreg.dec.sync.aligned.u32 40;");
    if (warp == 8) {
      if (lane >= 3 && lane < 14) asm volatile("prefetch.tensormap [%0];" ::"l"(&P.ckv + lane) : "memory");
      __syncwarp();
      started();
      TRM(4);
      Ring r{0, 0};
      uint32_t lin = 0;
      uint32_t mypos = 0, mypar = 2;
      const uint32_t myempty = sb + M_EMPTY + 8 * (lane & 7);
      auto alloc = [&](int z, uint32_t& fb) -> uint32_t {
        if (r.g + z > M_NG) lin += M_NG - r.g;
        const uint32_t st = sb + r.take(z) * M_GR;
        const uint32_t need = mypar < 2 && lin + z - mypos > M_NG;
        for (int it = 0;; it++) {
          uint32_t ok;
          asm volatile("{.reg .pred p, q; setp.eq.u32 q, %3, 0; mov.pred p, q; @!q mbarrier.try_wait.parity.shared::cta.b64 p, [%1], %2; selp.u32 %0, 1, 0, p;}"
                       : "=r"(ok) : "r"(myempty), "r"(mypar), "r"(need) : "memory");
          if (__all_sync(0xffffffffu, ok)) break;
          if (it > 4000000) __trap();
        }
        mypar = need ? 2 : mypar;
        if (lane == (r.e & 7)) { mypos = lin; mypar = r.par(); }
        lin += z;
        fb = sb + M_FULL + r.bar();
        r.e++;
        return st;
      };
      auto go = [&]() { if (rank == 0) arrive_elect(sb + M_GO); };
      for (int ti = 0;; ti++) {
        const uint32_t task = read_task(ti);
        free_task(ti);
        if (task == TASK_END) break;
        const int type = task >> 12, nn = (task >> 8) & 15, h = (task >> 3) & 31, p = task & 7;
        uint32_t fb, fv = 0;
        if (type == T_NOP) {
          go();
        } else if (type == T_KV) {
          const CUtensorMap* w = rank ? &P.wuv : &P.wuk;
          const int row = p * 256 + rank * 128;
#pragma unroll 1
          for (int k = 0; k < 512; k += 64) {
            const uint32_t st = alloc(3, fb);
            if ((ti > 0 || k >= 256 || cluster >= NEARLY) && elect()) {
              mbar_expect(fb, 49152);
              tma2d(st, &P.ckv, k, row, fb);
              tma3d_mc(st + 16384 + rank * 16384, w, 0, k, h * 2, fb, 3);
            }
            if (k == 384) go();
            if (PF_ON && ti == 0 && h < 4 && k == 192 && elect()) {
              asm volatile("cp.async.bulk.prefetch.tensor.3d.L2.global [%0, {0,%1,%2}];" ::"l"(w), "r"(p * 64), "r"((h + 4) * 2) : "memory");
              if (h == 0) asm volatile("cp.async.bulk.prefetch.tensor.3d.L2.global [%0, {0,%1,%2}];" ::"l"(w), "r"(p * 64), "r"(16) : "memory");
            }
            if (PF_ON && ti == 1 && h < 8 && k >= 192 && elect()) {
              const int c = (k - 192) / 32 + rank;
              if (c < 9) asm volatile("cp.async.bulk.prefetch.tensor.2d.L2.global [%0, {%1,%2}];" ::"l"(&P.ax), "r"(c * 64), "r"(p * 256 + (h & 3) * 64) : "memory");
              if (k == 192) asm volatile("cp.async.bulk.prefetch.tensor.2d.L2.global [%0, {%1,%2}];" ::"l"(&P.wq), "r"((h & 3) * 128 + rank * 64), "r"(p * 64) : "memory");
            }
            __syncwarp();
          }
          alloc(2, fb);
          arrive_elect(fb);
        } else if (type == T_FA) {
          const unsigned* flag = g_sync + SY_KV + h * 8 + (lane & 7);
          asm volatile("ld.relaxed.gpu.global.u32 %0, [%1];" : "=r"(fv) : "l"(flag) : "memory");
          const int r0 = p * 256 + rank * 64, r1 = p * 256 + 192 - rank * 64, col = h * 128 + rank * 64;
#pragma unroll 1
          for (int k = 0; k < 576; k += 64) {
            const uint32_t st = alloc(2, fb);
            if (elect()) {
              mbar_expect(fb, 32768);
              tma2d(st, &P.ax, k, r0, fb);
              tma2d(st + 8192, &P.ax, k, r1, fb);
              tma2d_mc(st + 16384 + rank * 8192, &P.wq, col, k, fb, 3);
            }
          }
          auto kv = [&](int row) {
            const uint32_t st = alloc(2, fb);
            if (elect()) {
              mbar_expect(fb, 32768);
              tma2d_mc(st + rank * 16384, &P.scr, col, row, fb, 3);
            }
          };
          need_flag(fv, p, flag, 4);
          kv((2 * p + 1) * 128);
#pragma unroll 1
          for (int j = 2 * p; j >= 0; j--) {
            need_flag(fv, j >> 1, flag, 4);
            if (j == 0) go();
            kv(j * 128);
            kv(SEQ + (j + 1) * 128);
          }
          kv(SEQ);
        } else {
          const int part = type & 1;
          const unsigned* flag = g_sync + (part ? SY_OX + 2 * p + (type == T_XB ? h : 1) : SY_CTX + p * 32 + lane);
          const unsigned target = part ? OX_TARGET : 4;
          const int row = (2 + part) * SEQ + p * 256 + rank * 128;
          if (type == T_XB) {
            need_flag(fv, 0, flag, target);
#pragma unroll 1
            for (int i = 0; i < 16; i++) {
              const int k = rank * 2048 + i * 128;
              const uint32_t st = alloc(3, fb);
              if (elect()) {
                mbar_expect(fb, h ? 32768 : 49152);
                if (h) {
                  tma2d(st, &P.scr64, k, 3 * SEQ + p * 256 + 128, fb);
                  tma2d(st + 16384, &P.scr64, k + 64, 3 * SEQ + p * 256 + 128, fb);
                } else {
                  tma3d(st, &P.scr2, 0, 3 * SEQ + p * 256, k >> 6, fb);
                }
                tma2d(st + 32768, &P.wob1, nn * 64, k, fb);
                tma2d(st + 40960, &P.wob1, nn * 64, k + 64, fb);
              }
              if (i == 13) go();
            }
          } else if (type >= T_SA) {
            const CUtensorMap* w = part ? &P.wob1 : &P.woa1;
#pragma unroll 1
            for (int k = 0; k < HDALL; k += 128) {
              need_flag(fv, k >> 7, flag, target);
              const uint32_t st = alloc(3, fb);
              if (elect()) {
                mbar_expect(fb, 49152);
                tma3d(st, &P.scr2, 0, row, k >> 6, fb);
                tma2d_mc(st + 32768 + rank * 8192, w, nn * 64, k + rank * 64, fb, 3);
              }
              if (k == HDALL - 384) go();
            }
          } else {
            const CUtensorMap* w = part ? &P.wob : &P.woa;
#pragma unroll 1
            for (int k = 0; k < HDALL; k += 64) {
              need_flag(fv, k >> 7, flag, target);
              const uint32_t st = alloc(3, fb);
              if (elect()) {
                mbar_expect(fb, 40960);
                tma2d(st, &P.scr, k, row, fb);
                tma3d_mc(st + 16384 + rank * 12288, w, 0, k + rank * 32, nn * 3, fb, 3);
              }
              if (k == HDALL - 192) go();
            }
          }
          alloc(3, fb);
          arrive_elect(fb);
        }
      }
    } else if (warp == 9) {
      started();
      TRM(0);
      if (rank == 0) {
        for (int ti = 0;; ti++) {
          uint32_t q = 0;
          mbar_wait(sb + M_GO, ti & 1);
          if (lane == 0) q = NCL + atomicAdd(&g_sync[SY_Q], 1u);
          q = __shfl_sync(0xffffffffu, q, 0);
          if (ti == 0 && q < 100000) TRM(1);
          const uint32_t t = q < P.ntask ? (uint32_t)P.tasks[q] : TASK_END;
          if (ti == 0 && t < 100000) TRM(2);
          mbar_wait(sb + M_TEMPTY + 8 * (ti & 3), ((ti >> 2) & 1) ^ 1);
          if (lane < 2) {
            const uint32_t b = mapa(sb + M_TFULL + 8 * (ti & 3), lane);
            mbar_expect_cl(b, 4);
            st_async32(mapa(sb + M_TSLOT + 4 * (ti & 3), lane), t, b);
          }
          __syncwarp();
          if (t == TASK_END) break;
        }
      }
    } else {
      const int wg = warp - 10;
      const uint32_t emptyx = mapa(sb + M_EMPTY, lane & 1);
      Ring r{0, 0};
      int lead = wg;
      started();
      for (int ti = 0;; ti++) {
        const int sl = ti & 1;
        const uint32_t task = read_task(ti);
        const int type = task >> 12, nn = (task >> 8) & 15, h = (task >> 3) & 31, p = task & 7;
        if (task != TASK_END) {
          const int nit = task_entries(type, p);
          uint32_t st = 0;
          for (int it = 0; it < nit; it++) st = r.take(entry_size(type, it));
          r.e += nit - 1;
          int row = p * 256 + rank * 128 + wg * 64;
          if (type == T_FA) {
            row = 2 * SEQ + p * 256 + (lead ? 3 - (int)rank : (int)rank) * 64;
            lead ^= 1;
          }
          mbar_wait(sb + M_EPI + 8 * (sl * 2 + wg), (ti >> 1) & 1);
          auto store = [&](const CUtensorMap* m, uint32_t src, int r0, int c0, int nch, bool fast = true) {
            if (lane == 0) {
#pragma unroll 1
              for (int i = 0; i < nch * (64 / ST_ROWS); i++) {
                asm volatile("cp.async.bulk.tensor.2d.global.shared::cta.bulk_group [%0, {%1,%2}], [%3];" ::"l"(m), "r"((c0 + i / (64 / ST_ROWS)) * 64), "r"(r0 + i % (64 / ST_ROWS) * ST_ROWS), "r"(src + i * ST_ROWS * 128) : "memory");
                asm volatile("cp.async.bulk.commit_group;" ::: "memory");
                if (fast) asm volatile("cp.async.bulk.wait_group.read %0;" ::"n"(ST_DEPTH) : "memory");
                else asm volatile("cp.async.bulk.wait_group.read 0;" ::: "memory");
              }
              asm volatile("cp.async.bulk.wait_group.read 0;" ::: "memory");
            }
            __syncwarp();
          };
          if (type != T_FA && type != T_NOP) {
            if (type == T_KV) store(&P.scr_st, sb + st * M_GR + wg * 16384, SEQ + row, h * 2, 2);
            else if (type == T_XB) store(&P.out_st, sb + st * M_GR + wg * 8192, p * 256 + h * 128 + wg * 64, 9 + nn, wg == rank && !(h & wg));
            else if (type >= T_SA) store(&P.out_st, sb + st * M_GR + wg * 8192, row, (type & 1) * 9 + nn, 1);
            else store(&P.out_st, sb + st * M_GR + wg * 24576, row, (type & 1) * 9 + nn * 3, 3);
            if (lane < 2) asm volatile("mbarrier.arrive.shared::cluster.b64 _, [%0], 4;" ::"r"(emptyx + r.bar()) : "memory");
          }
          r.e++;
          if (type <= T_FA) store(&P.scr_st, sb + M_STG + wg * 16384, row, h * 2, 2, false);
          if (lane == 0) mbar_arrive(sb + M_SFREE + 8 * wg);
          if (lane == 0) {
            asm volatile("cp.async.bulk.wait_group 0;" ::: "memory");
            if (type <= T_FA) {
              __threadfence();
              atomicAdd(type == T_KV ? &g_sync[SY_KV + h * 8 + p] : &g_sync[SY_CTX + p * 32 + h], 1u);
            }
          }
        }
        __syncwarp();
        free_task(ti);
        if (task == TASK_END) break;
      }
    }
    __syncwarp();
    cluster_sync();
    if (warp == 9) {
      uint32_t old = 0;
      if (lane == 0) {
        __threadfence();
        old = atomicAdd(&g_sync[SY_EXIT], 1u);
        __threadfence();
      }
      if (__shfl_sync(0xffffffffu, old, 0) == gridDim.x - 1) {
        for (int i = lane; i < SY_N; i += 32) g_sync[i] = 0;
        asm volatile("griddepcontrol.wait;" ::: "memory");
      }
    }
  } else {
    asm volatile("setmaxnreg.inc.sync.aligned.u32 232;");
    if (warp == 0) TRM(3);
    const int wg = warp >> 2, w4 = warp & 3, g = lane >> 2, t4 = lane & 3;
    const uint32_t emptyx = mapa(sb + M_EMPTY, lane & 1);
    Ring r{0, 0};
    int lead = wg;
    uint32_t xph = 0;
    auto release = [&](uint32_t bar) {
      if (lane < 2) mbar_arrive_cl(emptyx + bar);
    };
    auto acquire = [&](int z, uint32_t& bar) -> uint32_t {
      bar = r.bar();
      mbar_wait(sb + M_FULL + bar, r.par());
      r.e++;
      return sb + r.take(z) * M_GR;
    };
    const uint32_t sa = (w4 * 16 + ((lane >> 3) & 1) * 8 + (lane & 7)) * 128 + (((lane >> 4) ^ (lane & 7)) << 4);
    uint32_t ntask = task0;
    started();
    for (int ti = 0;; ti++) {
      const int sl = ti & 1;
      const uint32_t task = ntask;
      if (task == TASK_END) break;
      auto next_task = [&]() { ntask = read_task(ti + 1); free_task(ti + 1); };
      const int type = task >> 12, p = task & 7;
#ifdef DEV_TRACE
      if (w4 == 0 && lane == 0 && ti < 250) { long long c; asm volatile("mov.u64 %0, %%globaltimer;" : "=l"(c)); g_trace[blockIdx.x * 4096 + ti * 8 + wg * 4] = c; g_trace[blockIdx.x * 4096 + ti * 8 + wg * 4 + 2] = task; g_trace[blockIdx.x * 4096 + ti * 8 + wg * 4 + 3] = clock64(); }
#endif
      if (type == T_KV) {
        float acc[128];
        uint32_t prev;
        {
          const uint32_t st = acquire(3, prev);
          if (ti == 0 && warp == 0) TRM(6);
          const uint32_t a = desc_lo(st + wg * 8192, 16), b = desc_lo(st + 16384, 8192);
          wg_fence();
          wgmma_ssz_n256_a0b1(acc, mk_desc(a, DHI_SW128), mk_desc(b, DHI_SW128));
#pragma unroll
          for (int kk = 1; kk < 4; kk++) wgmma_ss_n256_a0b1(acc, mk_desc(a + kk * 2, DHI_SW128), mk_desc(b + kk * 128, DHI_SW128), 1);
          wg_commit();
        }
#pragma unroll 1
        for (int kb = 1; kb < 8; kb++) {
          uint32_t bar;
          const uint32_t st = acquire(3, bar);
          const uint32_t a = desc_lo(st + wg * 8192, 16), b = desc_lo(st + 16384, 8192);
          if (KV_SKEW < 8 && kb == KV_SKEW && !lead) {
            wg_wait<0>();
            release(prev);
            bar_sync(5, 256);
          }
          wg_fence();
#pragma unroll
          for (int kk = 0; kk < 4; kk++) wgmma_ss_n256_a0b1(acc, mk_desc(a + kk * 2, DHI_SW128), mk_desc(b + kk * 128, DHI_SW128), 1);
          wg_commit();
          if (KV_SKEW < 8 && kb == 7 && lead) bar_arrive(5, 256);
          if (KV_SKEW < 8 && kb == KV_SKEW && !lead) { prev = bar; continue; }
          wg_wait<1>();
          release(prev);
          prev = bar;
        }
        if (ti == 0 && warp == 0) TRM(7);
        next_task();
        uint32_t bar;
        const uint32_t st = acquire(2, bar);
        mbar_wait(sb + M_SFREE + 8 * wg, (ti & 1) ^ 1);
        wg_wait<0>();
        release(prev);
        fence_regs(acc);
        stage_tile<16, 32>(acc, st + wg * 16384 + sa, 1.f, 1.f);
        stage_tile<0, 16>(acc, sb + M_STG + wg * 16384 + sa, 1.f, 1.f);
        fence_async_smem();
        __syncwarp();
        arrive_elect(sb + M_EPI + 8 * (sl * 2 + wg));
      } else if (type == T_FA) {
        const int lng = lead;
        lead ^= 1;
        const int grp = lng ? 3 - (int)rank : (int)rank;
        const int n = 2 * p + 1 + lng;
        float s[64], o[64];
        uint32_t pr[32], q[32];
        TRF(0);
        {
          uint32_t prev;
          {
            const uint32_t st = acquire(2, prev);
            const uint32_t a = desc_lo(st + lng * 8192, 16), b = desc_lo(st + 16384, 8192);
            wg_fence();
            wgmma_ssz_n128_a0b1(s, mk_desc(a, DHI_SW128), mk_desc(b, DHI_SW128));
#pragma unroll
            for (int kk = 1; kk < 4; kk++) wgmma_ss_n128_a0b1(s, mk_desc(a + kk * 2, DHI_SW128), mk_desc(b + kk * 128, DHI_SW128), 1);
            wg_commit();
          }
#pragma unroll 1
          for (int kb = 1; kb < 9; kb++) {
            uint32_t bar;
            if (kb == 1) TRF(8);
            if (kb == 5) TRF(9);
            const uint32_t st = acquire(2, bar);
            const uint32_t a = desc_lo(st + lng * 8192, 16), b = desc_lo(st + 16384, 8192);
            const bool hold = kb == Q_SKEW && !lng;
            if (hold) {
              wg_wait<0>();
              release(prev);
              bar_sync(5, 256);
            }
            wg_fence();
#pragma unroll
            for (int kk = 0; kk < 4; kk++) wgmma_ss_n128_a0b1(s, mk_desc(a + kk * 2, DHI_SW128), mk_desc(b + kk * 128, DHI_SW128), 1);
            wg_commit();
            if (Q_SKEW < 9 && kb == 8 && lng) bar_arrive(5, 256);
            if (hold) { prev = bar; continue; }
            wg_wait<1>();
            release(prev);
            prev = bar;
          }
#pragma unroll
          for (int i = 0; i < 64; i++) o[i] = 0.f;
          wg_wait<0>();
          release(prev);
          fence_regs(s);
#pragma unroll
          for (int i = 0; i < 32; i++) q[i] = pack_bf16(s[2 * i], s[2 * i + 1]);
        }
        TRF(1);
        const int lim0 = (grp & 1) * 64 + w4 * 16 + g - 2 * t4;
        float m0 = -INFINITY, m1 = -INFINITY, l0 = 0.f, l1 = 0.f;
        auto issue_s = [&](uint32_t st) {
          const uint32_t b = desc_lo(st, 16);
#pragma unroll
          for (int kk = 0; kk < 8; kk++) wgmma_rs_n128_b0(s, q[4 * kk], q[4 * kk + 1], q[4 * kk + 2], q[4 * kk + 3], mk_desc(b + (kk >> 2) * 1024 + (kk & 3) * 2, DHI_SW128), kk);
          wg_commit();
        };
        auto issue_pv = [&](uint32_t st) {
          const uint32_t b = desc_lo(st, 16384);
#pragma unroll
          for (int kk = 0; kk < 8; kk++) {
            wgmma_rs_n128_b1(o, pr[4 * kk], pr[4 * kk + 1], pr[4 * kk + 2], pr[4 * kk + 3], mk_desc(b + kk * 128, DHI_SW128), 1);
            if (kk == 1 || kk == 3 || kk == 7) wg_commit();
          }
        };
        auto skip = [&]() {
          uint32_t bar;
          acquire(2, bar);
          release(bar);
        };
        const bool half = !(grp & 1);
        float t[4];
        auto first = [&]() {
          float a0, a1, c0, c1;
          uint32_t kb;
          const uint32_t kst = acquire(2, kb);
          if (!lng) bar_sync(1 + wg, 256);
          fence_regs(q);
          fence_regs(s);
          if (half) {
            const uint32_t b = desc_lo(kst, 16);
            wg_fence();
#pragma unroll
            for (int kk = 0; kk < 8; kk++) wgmma_rs_n64_b0(reinterpret_cast<float(&)[32]>(s), q[4 * kk], q[4 * kk + 1], q[4 * kk + 2], q[4 * kk + 3], mk_desc(b + (kk >> 2) * 1024 + (kk & 3) * 2, DHI_SW128), kk);
            wg_commit();
            bar_arrive(2 - wg, 256);
            wg_wait<0>();
            fence_regs(s);
            causal_mask<0, 8>(s, lim0);
          } else {
            wg_fence();
            issue_s(kst);
            bar_arrive(2 - wg, 256);
            wg_wait<0>();
            fence_regs(s);
            causal_mask<8, 16>(s, lim0);
          }
          release(kb);
          TRF(2);
          softmax_max<FM_NJ>(s, m0, m1, a0, a1, c0, c1);
          softmax_exp<0, 8>(s, pr, c0, c1, t);
          if (half) {
#pragma unroll
            for (int i = 16; i < 32; i++) pr[i] = 0;
          } else {
            softmax_exp<8, 16>(s, pr, c0, c1, t);
          }
        };
        auto block = [&]() {
          const uint32_t kb = r.bar(), kp = r.par(), kst = sb + r.take(2) * M_GR;
          r.e++;
          const uint32_t vb = r.bar(), vp = r.par(), vst = sb + r.take(2) * M_GR;
          r.e++;
          mbar_wait2(sb + M_FULL + kb, kp, sb + M_FULL + vb, vp);
          fence_regs(o);
          fence_regs(pr);
          fence_regs(s);
          bar_sync(1 + wg, 256);
          wg_fence();
          issue_s(kst);
          issue_pv(vst);
          bar_arrive(2 - wg, 256);
          wg_wait<3>();
          release(kb);
          fence_regs(s);
          const float d0 = -m0 * SM_C, d1 = -m1 * SM_C;
          wg_wait<2>();
          fence_part<0, 8>(pr);
          softmax_exp<0, 4>(s, pr, d0, d1, t);
          fence_part<0, 8>(pr);
          sched_fence(kst);
          wg_wait<1>();
          fence_part<8, 16>(pr);
          softmax_exp<4, 8>(s, pr, d0, d1, t);
          fence_part<8, 16>(pr);
          sched_fence(vst);
          wg_wait<0>();
          release(vb);
          fence_regs(o);
          fence_part<16, 32>(pr);
          softmax_exp<8, 16>(s, pr, d0, d1, t);
        };
        auto check = [&](bool hlf) {
          if (__builtin_expect(__any_sync(0xffffffffu, !((t[0] + t[1]) + (t[2] + t[3]) < 1.8446744e19f)), 0)) {
            float a0, a1, c0, c1;
            if (hlf) {
#pragma unroll
              for (int i = 32; i < 64; i++) s[i] = -INFINITY;
            }
            softmax_max<16>(s, m0, m1, a0, a1, c0, c1);
            l0 *= a0;
            l1 *= a1;
#pragma unroll
            for (int i = 0; i < 16; i++) { o[4 * i] *= a0; o[4 * i + 1] *= a0; o[4 * i + 2] *= a1; o[4 * i + 3] *= a1; }
            softmax_exp<0, 16>(s, pr, c0, c1, t);
          }
          l0 += t[0] + t[1];
          l1 += t[2] + t[3];
        };
        if (!lng) skip();
        first();
        check(half);
        if (!lng) skip();
        TRF(3);
#pragma unroll 1
        for (int j = 1; j < n; j++) {
          if (j == n - 1) TRF(4);
          block();
          check(false);
        }
        TRF(5);
        uint32_t vb;
        const uint32_t vst = acquire(2, vb);
        fence_regs(o);
        fence_regs(pr);
        if (!lng) bar_sync(1 + wg, 256);
        wg_fence();
        issue_pv(vst);
        l0 += __shfl_xor_sync(0xffffffffu, l0, 1);
        l1 += __shfl_xor_sync(0xffffffffu, l1, 1);
        l0 += __shfl_xor_sync(0xffffffffu, l0, 2);
        l1 += __shfl_xor_sync(0xffffffffu, l1, 2);
        const float i0 = rcp(l0), i1 = rcp(l1);
        next_task();
        mbar_wait(sb + M_SFREE + 8 * wg, (ti & 1) ^ 1);
        wg_wait<0>();
        release(vb);
        fence_regs(o);
        fence_regs(pr);
        TRF(6);
        stage_tile<0, 16>(o, sb + M_STG + wg * 16384 + sa, i0, i1);
        fence_async_smem();
        __syncwarp();
        arrive_elect(sb + M_EPI + 8 * (sl * 2 + wg));
        TRF(7);
      } else if (type == T_NOP) {
        next_task();
        arrive_elect(sb + M_EPI + 8 * (sl * 2 + wg));
      } else if (type >= T_SA) {
        float acc[32];
#pragma unroll
        for (int i = 0; i < 32; i++) acc[i] = 0.f;
        uint32_t prev = 0;
        for (int kb = 0; kb < (type == T_XB ? 16 : 32); kb++) {
          uint32_t bar;
          const uint32_t st = acquire(3, bar);
          const uint32_t a = desc_lo(st + wg * 8192, 16), b = desc_lo(st + 32768, 4096);
          wg_fence();
#pragma unroll
          for (int kk = 0; kk < 8; kk++) wgmma_ss_n64_a0b1(acc, mk_desc(a + (kk >> 2) * 1024 + (kk & 3) * 2, DHI_SW128), mk_desc(b + kk * 128, DHI_SW128), kk | kb);
          wg_commit();
          if (kb > 0) { wg_wait<1>(); release(prev); }
          prev = bar;
        }
        next_task();
        uint32_t bar;
        const uint32_t st = acquire(3, bar);
        mbar_wait(sb + M_SFREE + 8 * wg, (ti & 1) ^ 1);
        wg_wait<0>();
        release(prev);
        fence_regs(acc);
        if (type == T_XB) {
          const uint32_t xa = st + 16384 + (threadIdx.x & 127) * 16;
          if (wg != rank) {
            const uint32_t ra = mapa(xa, wg), rb = mapa(sb + M_XR, wg);
#pragma unroll
            for (int i = 0; i < 8; i++) st_async128(ra + i * 2048, __float_as_uint(acc[4 * i]), __float_as_uint(acc[4 * i + 1]), __float_as_uint(acc[4 * i + 2]), __float_as_uint(acc[4 * i + 3]), rb);
          } else {
            if (w4 == 0 && elect()) mbar_expect(sb + M_XR, 16384);
            __syncwarp();
            mbar_wait(sb + M_XR, xph);
#pragma unroll
            for (int i = 0; i < 8; i++) {
              float4 v;
              asm volatile("ld.shared.v4.f32 {%0,%1,%2,%3}, [%4];" : "=f"(v.x), "=f"(v.y), "=f"(v.z), "=f"(v.w) : "r"(xa + i * 2048) : "memory");
              acc[4 * i] += v.x; acc[4 * i + 1] += v.y; acc[4 * i + 2] += v.z; acc[4 * i + 3] += v.w;
            }
          }
          xph ^= 1;
        }
        stage_tile<0, 8>(acc, st + wg * 8192 + sa, 1.f, 1.f);
        fence_async_smem();
        __syncwarp();
        arrive_elect(sb + M_EPI + 8 * (sl * 2 + wg));
      } else {
        float acc[96];
#pragma unroll
        for (int i = 0; i < 96; i++) acc[i] = 0.f;
        uint32_t prev = 0;
        for (int kb = 0; kb < 64; kb++) {
          uint32_t bar;
          const uint32_t st = acquire(3, bar);
          const uint32_t a = desc_lo(st + wg * 8192, 16), b = desc_lo(st + 16384, 4096);
          wg_fence();
#pragma unroll
          for (int kk = 0; kk < 4; kk++) wgmma_ss_n192_a0b1(acc, mk_desc(a + kk * 2, DHI_SW128), mk_desc(b + (kk >> 1) * 768 + (kk & 1) * 128, DHI_SW128), kk | kb);
          wg_commit();
          if (kb > 0) { wg_wait<1>(); release(prev); }
          prev = bar;
        }
        next_task();
        uint32_t bar;
        const uint32_t st = acquire(3, bar);
        mbar_wait(sb + M_SFREE + 8 * wg, (ti & 1) ^ 1);
        wg_wait<0>();
        release(prev);
        fence_regs(acc);
        stage_tile<0, 24>(acc, st + wg * 24576 + sa, 1.f, 1.f);
        fence_async_smem();
        __syncwarp();
        arrive_elect(sb + M_EPI + 8 * (sl * 2 + wg));
      }
#ifdef DEV_TRACE
      if (w4 == 0 && lane == 0 && ti < 250) { long long c; asm volatile("mov.u64 %0, %%globaltimer;" : "=l"(c)); g_trace[blockIdx.x * 4096 + ti * 8 + wg * 4 + 1] = c; }
#endif
    }
    cluster_sync();
  }
}

typedef CUresult (*EncodeFn)(CUtensorMap*, CUtensorMapDataType, cuuint32_t, void*, const cuuint64_t*, const cuuint64_t*, const cuuint32_t*,
                             const cuuint32_t*, CUtensorMapInterleave, CUtensorMapSwizzle, CUtensorMapL2promotion, CUtensorMapFloatOOBfill);

void map2d(EncodeFn enc, CUtensorMap* m, const void* p, int rows, int cols, int boxr) {
  cuuint64_t gd[2] = {(cuuint64_t)cols, (cuuint64_t)rows}, gs[1] = {(cuuint64_t)cols * 2};
  cuuint32_t bx[2] = {64, (cuuint32_t)boxr}, es[2] = {1, 1};
  enc(m, CU_TENSOR_MAP_DATA_TYPE_BFLOAT16, 2, (void*)p, gd, gs, bx, es, CU_TENSOR_MAP_INTERLEAVE_NONE, CU_TENSOR_MAP_SWIZZLE_128B,
      CU_TENSOR_MAP_L2_PROMOTION_L2_256B, CU_TENSOR_MAP_FLOAT_OOB_FILL_NONE);
}
void map3d(EncodeFn enc, CUtensorMap* m, const void* p, int rows, int cols, int boxr, int nch) {
  cuuint64_t gd[3] = {64, (cuuint64_t)rows, (cuuint64_t)cols / 64}, gs[2] = {(cuuint64_t)cols * 2, 128};
  cuuint32_t bx[3] = {64, (cuuint32_t)boxr, (cuuint32_t)nch}, es[3] = {1, 1, 1};
  enc(m, CU_TENSOR_MAP_DATA_TYPE_BFLOAT16, 3, (void*)p, gd, gs, bx, es, CU_TENSOR_MAP_INTERLEAVE_NONE, CU_TENSOR_MAP_SWIZZLE_128B,
      CU_TENSOR_MAP_L2_PROMOTION_L2_256B, CU_TENSOR_MAP_FLOAT_OOB_FILL_NONE);
}

#ifndef R_KR
#define R_KR 24
#endif
#ifndef R_VR
#define R_VR 9
#endif
constexpr int R_NS = 36 - R_KR;
constexpr int R_WQ = 0, R_WK = R_WQ + R_NS * 2048, R_WV = R_WK + R_NS * 2048;
constexpr int R_OS = 102 * 1024;
constexpr int R_RS = 103 * 1024;
static_assert(R_WV + (36 - R_VR) * 2048 <= R_OS, "weights");
constexpr int R_HC = 9216, R_H = 114 * 1024, R_HM = R_H + 4096;
__host__ __device__ constexpr int hoff(int c) { return (c < 8 ? 1 + (c >> 1) + 4 * (c & 1) : 0) * R_HC; }
constexpr int R_PS = R_H + 9 * R_HC;
constexpr int R_GS = 1056, R_HS = 12288, R_QS = 201 * 1024;
static_assert(R_PS + 5120 <= R_QS, "layout");
constexpr int R_BAR = R_QS + 2 * R_HS;
static_assert(3 * 73728 <= R_BAR, "prologue staging");
constexpr int RB_MEM = R_BAR  , RB_RS = R_BAR + 40, RB_QK = R_BAR + 48, RB_XF = R_BAR + 88  , RB_QXL = R_BAR + 104, RB_W = R_BAR + 112  ;
constexpr int R_SMEM = R_BAR + 128;
static_assert(R_SMEM <= 232448, "smem");
constexpr int QK_TX = 2048 + 8 * R_GS;
constexpr int NB_P1 = 1, NB_P3 = 2, NB_PM = 3, NB_O = 4, NB_PX = 5, NB_RD = 6, NB_S = 7, NB_O2 = 8;
static_assert(R_NS >= 9 && R_NS <= 18, "R_KR");
__host__ __device__ constexpr int nsm(int c) { return c < R_NS - 9 ? 2 : 1; }
__host__ __device__ constexpr int sm0(int c) { return c < R_NS - 9 ? 2 * c : c + R_NS - 9; }
__host__ __device__ constexpr bool qk_in_reg(int k) { return (k & 3) >= nsm(k >> 2); }
__host__ __device__ constexpr int qk_slot(int k) { return qk_in_reg(k) ? k - sm0((k >> 2) + 1) : sm0(k >> 2) + (k & 3); }
__host__ __device__ constexpr int qk_step(int slot, bool reg) {
  for (int k = 0; k < 36; k++)
    if (qk_in_reg(k) == reg && qk_slot(k) == slot) return k;
  return -1;
}
#ifndef B_SEQ
#define B_SEQ "qkqkqkqkQkqkKqkq|QKQKQKqkQkqKqkQkqKqkQkqKqkQkqKqkQkqKqkQkqKqkQkqKqkQkqKqk"
#endif
__host__ __device__ constexpr int seq_count(char c, int n) {
  int r = 0;
  for (int i = 0; i < n; i++) r += B_SEQ[i] == c;
  return r;
}
static_assert(sizeof(B_SEQ) == 74 && seq_count('q', 73) == R_KR && seq_count('k', 73) == R_KR && seq_count('Q', 73) == R_NS && seq_count('K', 73) == R_NS, "B_SEQ");
#ifndef V_N1
#define V_N1 10
#endif
#ifndef V_PER
#define V_PER 3
#endif
#ifndef V_K0
#define V_K0 11
#endif
#ifndef QX_AFTER
#define QX_AFTER 2
#endif
#ifndef P1_PRE
#define P1_PRE 2
#endif
#ifndef B_DELAY
#define B_DELAY 0
#endif
#ifndef PUB_REL
#define PUB_REL 0
#endif
#ifndef PF_MAIN
#define PF_MAIN 2
#endif
#ifndef PRE_EARLY
#define PRE_EARLY 1
#endif
#ifndef P3_EARLY
#define P3_EARLY 0
#endif
#ifndef POLL_STAG
#define POLL_STAG 80
#endif
#ifndef POLL_DELAY
#define POLL_DELAY 240
#endif
__host__ __device__ constexpr bool v_in_reg(int k) { return k >= V_K0 && (k - V_K0) % V_PER == 0 && (k - V_K0) / V_PER < R_VR; }
__host__ __device__ constexpr int v_nreg_before(int k) { return k <= V_K0 ? 0 : ((k - V_K0 + V_PER - 1) / V_PER < R_VR ? (k - V_K0 + V_PER - 1) / V_PER : R_VR); }
__host__ __device__ constexpr int v_slot(int k) { return v_in_reg(k) ? (k - V_K0) / V_PER : k - v_nreg_before(k); }
static_assert(V_K0 + (R_VR - 1) * V_PER < 36, "Wv split");

struct RmtParams {
  CUtensorMap wq, wk, wv, wo, x, mem, ox;
  const __nv_bfloat16 *ckv, *wuk, *wuv;
  uint32_t* out;
};
constexpr int XCH_CL = 16 * 288, XCH_SLOT = 4 * XCH_CL;
__device__ uint32_t g_xch[2 * XCH_SLOT];
__device__ uint32_t g_xch2[8 * XCH_SLOT];
constexpr int R_T = 0, R_TN = 65536;
#ifdef DEV_TRACE
__device__ long long g_trace_b[64 * 4096];
#ifndef TR_S0
#define TR_S0 24
#endif
#ifndef TR_MASK
#define TR_MASK 0xffffffffu
#endif
#define TRW(slot, w) do { if (((TR_MASK >> (slot)) & 1) && w4 == (w) && s >= TR_S0 && s < TR_S0 + 16) { uint32_t c_; asm volatile("mov.u32 %0, %%clock;" : "=r"(c_)::"memory"); sts32(sb + R_QS + R_GS + ((s >> 3) & 1) * R_HS + (s & 7) * 128 + (slot) * 4, c_); } } while (0)
#else
#define TRW(slot, w)
#endif
#define TRB(slot) TRW(slot, 0)
#ifdef DEV_TRACE
#ifndef TRG_MASK
#define TRG_MASK 0x41
#endif
#define TRG(slot) do { if (((slot) >= 16 || ((TRG_MASK >> (slot)) & 1)) && (threadIdx.x & 127) == 0) { long long c_; asm volatile("mov.u64 %0, %%globaltimer;" : "=l"(c_)); g_trace_b[bid * 4096 + 2048 + (slot)] = c_; if ((slot) < 8) g_trace_b[bid * 4096 + 2056 + (slot)] = clock64(); } } while (0)
#else
#define TRG(slot)
#endif

__device__ __forceinline__ void ldsm4(uint32_t (&r)[4], uint32_t a) {
  asm volatile("ldmatrix.sync.aligned.m8n8.x4.shared.b16 {%0,%1,%2,%3}, [%4];" : "=r"(r[0]), "=r"(r[1]), "=r"(r[2]), "=r"(r[3]) : "r"(a) : "memory");
}
__device__ __forceinline__ void ldsm4t(uint32_t (&r)[4], uint32_t a) {
  asm volatile("ldmatrix.sync.aligned.m8n8.x4.trans.shared.b16 {%0,%1,%2,%3}, [%4];" : "=r"(r[0]), "=r"(r[1]), "=r"(r[2]), "=r"(r[3]) : "r"(a) : "memory");
}
__device__ __forceinline__ void stsm4t(uint32_t a, uint32_t r0, uint32_t r1, uint32_t r2, uint32_t r3) {
  asm volatile("stmatrix.sync.aligned.m8n8.x4.trans.shared.b16 [%0], {%1,%2,%3,%4};" ::"r"(a), "r"(r0), "r"(r1), "r"(r2), "r"(r3) : "memory");
}
__device__ __forceinline__ void stsm2t(uint32_t a, uint32_t r0, uint32_t r1) {
  asm volatile("stmatrix.sync.aligned.m8n8.x2.trans.shared.b16 [%0], {%1,%2};" ::"r"(a), "r"(r0), "r"(r1) : "memory");
}
__device__ __forceinline__ void mma16816(float (&c)[4], const uint32_t (&a)[4], uint32_t b0, uint32_t b1) {
  asm volatile("mma.sync.aligned.m16n8k16.row.col.f32.bf16.bf16.f32 {%0,%1,%2,%3}, {%4,%5,%6,%7}, {%8,%9}, {%0,%1,%2,%3};"
               : "+f"(c[0]), "+f"(c[1]), "+f"(c[2]), "+f"(c[3])
               : "r"(a[0]), "r"(a[1]), "r"(a[2]), "r"(a[3]), "r"(b0), "r"(b1));
}
__device__ __forceinline__ void sts32(uint32_t a, uint32_t v) { asm volatile("st.shared.b32 [%0], %1;" ::"r"(a), "r"(v) : "memory"); }
__device__ __forceinline__ uint2 lds64(uint32_t a) {
  uint2 v;
  asm volatile("ld.shared.v2.b32 {%0,%1}, [%2];" : "=r"(v.x), "=r"(v.y) : "r"(a) : "memory");
  return v;
}
__device__ __forceinline__ float4 lds128f(uint32_t a) {
  float4 v;
  asm volatile("ld.shared.v4.f32 {%0,%1,%2,%3}, [%4];" : "=f"(v.x), "=f"(v.y), "=f"(v.z), "=f"(v.w) : "r"(a) : "memory");
  return v;
}
__device__ __forceinline__ uint4 ld_relaxed128(const uint32_t* p) {
  uint4 v;
  asm volatile("ld.relaxed.gpu.global.v4.u32 {%0,%1,%2,%3}, [%4];" : "=r"(v.x), "=r"(v.y), "=r"(v.z), "=r"(v.w) : "l"(p) : "memory");
  return v;
}
__device__ __forceinline__ void st_relaxed32(uint32_t* p, uint32_t v) { asm volatile("st.relaxed.gpu.global.u32 [%0], %1;" ::"l"(p), "r"(v) : "memory"); }

__device__ __forceinline__ void mma1688(float (&c)[4], uint32_t a0, uint32_t a1, uint32_t b0) {
  asm volatile("mma.sync.aligned.m16n8k8.row.col.f32.bf16.bf16.f32 {%0,%1,%2,%3}, {%4,%5}, {%6}, {%0,%1,%2,%3};"
               : "+f"(c[0]), "+f"(c[1]), "+f"(c[2]), "+f"(c[3])
               : "r"(a0), "r"(a1), "r"(b0));
}
__device__ __forceinline__ uint2 ld_relaxed64(const uint32_t* p) {
  uint2 v;
  asm volatile("{.reg .b64 t; ld.relaxed.gpu.global.b64 t, [%2]; mov.b64 {%0,%1}, t;}" : "=r"(v.x), "=r"(v.y) : "l"(p) : "memory");
  return v;
}
__device__ __forceinline__ void st_relaxed64(uint32_t* p, uint32_t a, uint32_t b) { asm volatile("{.reg .b64 t; mov.b64 t, {%1,%2}; st.relaxed.gpu.global.b64 [%0], t;}" ::"l"(p), "r"(a), "r"(b) : "memory"); }

__device__ __forceinline__ void mma16816z(float (&c)[4], const uint32_t (&a)[4], uint32_t b0, uint32_t b1) {
  asm volatile("mma.sync.aligned.m16n8k16.row.col.f32.bf16.bf16.f32 {%0,%1,%2,%3}, {%4,%5,%6,%7}, {%8,%9}, {0f00000000,0f00000000,0f00000000,0f00000000};"
               : "=f"(c[0]), "=f"(c[1]), "=f"(c[2]), "=f"(c[3])
               : "r"(a[0]), "r"(a[1]), "r"(a[2]), "r"(a[3]), "r"(b0), "r"(b1));
}
template <int NB> __device__ __forceinline__ uint2 xch_add(uint32_t a, int key, uint32_t tag) {
  uint32_t m[NB][4];
  float c[2][4];
#pragma unroll
  for (int j = 0; j < NB; j++) ldsm4t(m[j], a ^ (j << 5));
#pragma unroll
  for (int j = 0; j < NB; j++) {
    const uint32_t one = key == j ? 0x3f803f80u : 0u;
    if (j < 2) mma16816z(c[j], m[j], one, one);
    else mma16816(c[j & 1], m[j], one, one);
  }
  return make_uint2((__float_as_uint(c[0][0] + c[1][0]) & ~1u) | tag, __float_as_uint(c[0][2] + c[1][2]));
}
template <int NB> __device__ __forceinline__ uint2 xch_reduce(uint32_t a, int key, uint32_t* dst, uint32_t tag) {
  const uint2 o = xch_add<NB>(a, key, tag);
  st_relaxed64(dst, o.x, o.y);
  return o;
}
__device__ __forceinline__ uint32_t xch_sum(const uint2 (&v)[4]) {
  return pack_bf16((__uint_as_float(v[0].x) + __uint_as_float(v[1].x)) + (__uint_as_float(v[2].x) + __uint_as_float(v[3].x)),
                   (__uint_as_float(v[0].y) + __uint_as_float(v[1].y)) + (__uint_as_float(v[2].y) + __uint_as_float(v[3].y)));
}
__device__ __forceinline__ void xch_probe(uint2 (&v)[4], const uint32_t* x, int cl) {
#pragma unroll
  for (int c = 0; c < 4; c++)
    asm volatile("{.reg .pred p; .reg .b64 t; setp.ne.s32 p, %3, %4; mov.b64 t, {%0,%1}; @p ld.relaxed.gpu.global.b64 t, [%2]; mov.b64 {%0,%1}, t;}"
                 : "+r"(v[c].x), "+r"(v[c].y) : "l"(x + c * XCH_CL), "r"(cl), "r"(c) : "memory");
}
__device__ __forceinline__ uint32_t xch_bad(const uint2 (&v)[4]) {
  uint32_t bad;
  asm("{.reg .b32 t; lop3.b32 t, %1, %2, %3, 0x7e; lop3.b32 %0, t, %4, %3, 0xf6;}" : "=r"(bad) : "r"(v[0].x), "r"(v[1].x), "r"(v[2].x), "r"(v[3].x));
  return bad;
}
template <bool TWO> __device__ __forceinline__ uint32_t xch_poll(const uint32_t* x, int cl, uint2 o, const uint32_t* x2, uint2 o2, uint32_t& r2) {
  uint2 v[4] = {o, o, o, o}, w[4] = {o2, o2, o2, o2};
  uint32_t r;
#pragma unroll 1
  for (int it = 0;; it++) {
    xch_probe(v, x, cl);
    if (TWO) xch_probe(w, x2, cl);
    if (it > (1 << 20)) __trap();
    uint32_t bad = xch_bad(v);
    if (TWO) { bad |= xch_bad(w); r2 = xch_sum(w); }
    r = xch_sum(v);
    if (!__any_sync(0xffffffffu, bad & 1)) break;
  }
  return r;
}
constexpr uint32_t CTA1 = 1u << 24;
template <int NSEND, int NPRE> struct XSend {
  uint32_t d[NPRE], b[NPRE];
  static __device__ constexpr uint32_t off(int i) { return ((2 * i + 2 * i / NSEND) & (NSEND - 1)) * CTA1; }
  __device__ __forceinline__ XSend(uint32_t dst, uint32_t bar) {
#pragma unroll
    for (int i = 0; i < NPRE; i++) { d[i] = dst ^ off(i); b[i] = bar ^ off(i); }
    fence_regs(d);
    fence_regs(b);
  }
  __device__ __forceinline__ void send(uint32_t v) {
    asm volatile("" : "+r"(d[0]), "+r"(b[0]));
#pragma unroll
    for (int i = 0; i < NSEND; i++) st_async32(i < NPRE ? d[i] : d[0] ^ off(i), v, i < NPRE ? b[i] : b[0] ^ off(i));
  }
};
__device__ __forceinline__ uint32_t mbar_try_addr(uint32_t bar, uint32_t par, uint32_t good) {
  uint32_t r;
  asm volatile("{.reg .pred p; .reg .b32 t; mbarrier.try_wait.parity.shared::cta.b64 p, [%1], %2; xor.b32 t, %3, 16; selp.b32 %0, %3, t, p;}" : "=r"(r) : "r"(bar), "r"(par), "r"(good) : "memory");
  return r;
}

#ifdef DEV_TRACE
__device__ __noinline__ void trace_sync() {
  if (threadIdx.x == 0) {
    uint32_t g0, g1, c_;
    asm volatile("mov.u32 %0, %%globaltimer_lo;" : "=r"(g0));
    do { asm volatile("mov.u32 %0, %%globaltimer_lo;" : "=r"(g1)); asm volatile("mov.u32 %0, %%clock;" : "=r"(c_)); } while ((g1 >> 10) == (g0 >> 10));
    g_trace_b[(int)blockIdx.x * 4096 + 2160] = g1; g_trace_b[(int)blockIdx.x * 4096 + 2161] = c_;
  }
}
#endif
template <bool MASK>
__device__ __forceinline__ void rmt_softmax_row(const float (&d)[20], int u, int lim, uint32_t pax, uint32_t pam) {
  constexpr float C = 0.08838834764831845f * 1.4426950408889634f;
  float v[10];
#pragma unroll
  for (int j = 0; j < 5; j++) {
    v[2 * j] = (!MASK || j == 4 || 2 * j <= lim) ? d[4 * j + 2 * u] : -INFINITY;
    v[2 * j + 1] = (!MASK || j == 4 || 2 * j + 1 <= lim) ? d[4 * j + 2 * u + 1] : -INFINITY;
  }
  float m = fmaxf(fmaxf(fmaxf(v[0], v[1]), fmaxf(v[2], v[3])), fmaxf(fmaxf(fmaxf(v[4], v[5]), fmaxf(v[6], v[7])), fmaxf(v[8], v[9])));
  m = fmaxf(m, __shfl_xor_sync(0xffffffffu, m, 1));
  m = fmaxf(m, __shfl_xor_sync(0xffffffffu, m, 2));
  const float mc = -m * C;
#pragma unroll
  for (int i = 0; i < 10; i++) v[i] = ex2(fmaf(v[i], C, mc));
  float l = ((v[0] + v[1]) + (v[2] + v[3])) + (((v[4] + v[5]) + (v[6] + v[7])) + (v[8] + v[9]));
  l += __shfl_xor_sync(0xffffffffu, l, 1);
  l += __shfl_xor_sync(0xffffffffu, l, 2);
  const float inv = rcp(l);
  sts128(pax, pack_bf16(v[0] * inv, v[1] * inv), pack_bf16(v[2] * inv, v[3] * inv), pack_bf16(v[4] * inv, v[5] * inv), pack_bf16(v[6] * inv, v[7] * inv));
  sts32(pam, pack_bf16(v[8] * inv, v[9] * inv));
}

__global__ void __launch_bounds__(256, 1) rmt_kernel(const __grid_constant__ RmtParams P) {
  extern __shared__ __align__(1024) uint8_t smem_rmt[];
  const uint32_t sb = (uint32_t)__cvta_generic_to_shared(smem_rmt);
  const int warp = __shfl_sync(0xffffffffu, threadIdx.x >> 5, 0);
  const int lane = __shfl_sync(0xffffffffu, threadIdx.x & 31, threadIdx.x & 31);
  const int w4 = warp & 3, g = lane >> 2, t4 = lane & 3, rho = lane & 7, li = lane >> 3;
  uint32_t rank;
  asm("mov.u32 %0, %%cluster_ctarank;" : "=r"(rank));
  constexpr int ST_O = R_WV, ST_Q = ST_O + 73728, ST_K = ST_Q + R_KR * 2048, ST_V0 = R_OS, ST_V1 = ST_K + R_KR * 2048 - 6 * 2048;
  static_assert(ST_V0 + 6 * 2048 <= R_H && ST_V0 + 6 * 2048 <= ST_Q && ST_V1 + R_VR * 2048 <= R_BAR, "staging");

#ifdef DEV_SYNC
  trace_sync();
#endif
  if (threadIdx.x == 0) {
    if ((sb & 1023) || mapa(sb, 15) != (mapa(sb, 0) ^ (15 * CTA1))) __trap();
    for (int i = 0; i < 6; i++) mbar_init(sb + RB_MEM + 8 * i, 1);
    mbar_init(sb + RB_QK, 5); mbar_init(sb + RB_XF, 1); mbar_init(sb + RB_XF + 8, 1); mbar_init(sb + RB_QXL, 4); mbar_init(sb + RB_W, 1); mbar_init(sb + RB_W + 8, 1);
    asm volatile("fence.mbarrier_init.release.cluster;" ::: "memory");
    mbar_expect(sb + RB_W, 2 * 73728);
    mbar_expect(sb + RB_W + 8, 73728);
  }
  asm volatile("griddepcontrol.launch_dependents;");
  const int cl = blockIdx.x >> 4;
  __syncthreads();
  const int bid = cl * 16 + rank, c0 = bid * 64;
  if (warp == 0) TRG(0);
  auto prefetch_main = [&]() {
    asm volatile("cp.async.bulk.prefetch.L2.global [%0], 4096;" ::"l"(P.ckv + (bid * 8 + warp) * 2048) : "memory");
    asm volatile("cp.async.bulk.prefetch.L2.global [%0], 1280;" ::"l"(P.wuk + (bid * 8 + warp) * HDALL) : "memory");
    asm volatile("cp.async.bulk.prefetch.L2.global [%0], 1280;" ::"l"(P.wuv + (bid * 8 + warp) * HDALL) : "memory");
  };
  if (PF_MAIN == 1 && elect()) prefetch_main();
  __syncwarp();
  if (B_DELAY > 0) __nanosleep(B_DELAY);
  if (elect()) {
    for (int i = warp; i < 9; i += 8) tma2d(sb + ST_O + i * 8192, &P.wo, i * 64, c0, sb + RB_W + 8);
    if (warp == 1 && bid < 27) asm volatile("cp.async.bulk.prefetch.tensor.2d.L2.global [%0, {%1,%2}];" ::"l"(bid < 18 ? &P.x : &P.mem), "r"(bid % 9 * 64), "r"(bid / 9 % 2 * 32) : "memory");
    for (int k = warp; k < 36; k += 8) {
      const int o = qk_slot(k) * 2048;
      tma2d(sb + (qk_in_reg(k) ? ST_Q : R_WQ) + o, &P.wq, c0, k * 16, sb + RB_W);
      tma2d(sb + (qk_in_reg(k) ? ST_K : R_WK) + o, &P.wk, c0, k * 16, sb + RB_W);
    }
    for (int i = warp; i < 36; i += 8) asm volatile("cp.async.bulk.prefetch.tensor.2d.L2.global [%0, {%1,%2}];" ::"l"(&P.wv), "r"(c0), "r"(i * 16) : "memory");
    if (PF_MAIN == 2) prefetch_main();
  }
  __syncwarp();
  uint32_t wa = sb + ((li >> 1) * 8 + rho) * 128 + (((2 * w4 + (li & 1)) ^ rho) << 4);
  uint32_t la = sb + rho * 128 + ((li ^ rho) << 4);
  int ln = lane;
  if (warp == 0) TRG(1);
  mbar_wait(sb + RB_W + 8 * (warp >> 2), 0);
  if (warp == 0) TRG(2);

  if (warp < 4) {
    uint32_t wq[R_KR][4], wk[R_KR][4];
#pragma unroll
    for (int k = 0; k < R_KR; k++) { ldsm4t(wq[k], wa + ST_Q + k * 2048); ldsm4t(wk[k], wa + ST_K + k * 2048); }
    fence_async_smem();
    bar_sync(NB_P3, 256);
    asm volatile("barrier.cluster.arrive.relaxed.aligned;" ::: "memory");
    if (w4 < 2 && elect()) {
      mbar_expect(sb + RB_XF + 8 * w4, 9 * 4096);
      for (int i = 0; i < 9; i++) tma2d(sb + R_H + hoff(i) + w4 * 5120, &P.x, i * 64, w4 * 32, sb + RB_XF + 8 * w4);
    }
    if (w4 == 3 && elect()) {
      mbar_expect(sb + RB_QK, QK_TX);
      for (int i = 0; i < 5; i++) mbar_expect(sb + RB_MEM + 8 * i, i < 4 ? 2048 : 1024);
      for (int i = 0; i < 9; i++) tma2d(sb + R_HM + hoff(i), &P.mem, i * 64, 0, sb + RB_MEM + 8 * (i >> 1));
    }
    if (w4 == 2) sts128(sb + R_PS + (8 + lane) * 128 + ((5 ^ rho) << 4), 0u, 0u, 0u, 0u);
    __syncwarp();
    uint32_t qm = __shfl_sync(0xffffffffu, sb + R_QS + (rank & 1) * R_HS + (w4 * 16 + g) * 16 + t4 * 4, lane);
    const uint32_t peer = mapa(sb, rank ^ 1) - sb;

    uint32_t aq[P1_PRE][4], ak[P1_PRE][4];
    auto preload = [&]() {
#pragma unroll
      for (int i = 0; i < P1_PRE; i++) { ldsm4t(aq[i], wa + R_WQ + i * 2048); ldsm4t(ak[i], wa + R_WK + i * 2048); }
    };
    auto chain = [&](int s) {
      const bool LAST = s == 63;
      float cq[2][4], ck[2][4];
      for (;;) {
        uint32_t b[3][4];
        if (!PRE_EARLY) preload();
        mbar_wait(sb + RB_MEM, s & 1);
        TRB(0);
        uint32_t lb = la, bad = 0;
        ldsm4(b[0], lb + R_HM + hoff(0));
        ldsm4(b[1], (lb ^ 64) + R_HM + hoff(0));
#pragma unroll
        for (int hc = 0; hc < 18; hc++) {
          if (hc + 2 < 18) {
            if ((hc & 3) == 2) { lb = mbar_try_addr(sb + RB_MEM + 8 * ((hc + 2) >> 2), s & 1, la); bad |= lb ^ la; }
            ldsm4(b[(hc + 2) % 3], ((hc & 1) ? (lb ^ 64) : lb) + R_HM + hoff((hc + 2) >> 1));
          }
#pragma unroll
          for (int j = 0; j < 2; j++) {
            const int k = 2 * hc + j, sl = qk_slot(k);
            if (qk_in_reg(k)) {
              mma16816(cq[j], wq[sl], b[hc % 3][2 * j], b[hc % 3][2 * j + 1]);
              mma16816(ck[j], wk[sl], b[hc % 3][2 * j], b[hc % 3][2 * j + 1]);
            } else {
              static_assert(nsm(0) == 2, "first two steps come from shared memory");
              if (hc == 0) {
                mma16816z(cq[j], aq[j], b[0][2 * j], b[0][2 * j + 1]);
                mma16816z(ck[j], ak[j], b[0][2 * j], b[0][2 * j + 1]);
              } else {
                mma16816(cq[j], aq[sl % P1_PRE], b[hc % 3][2 * j], b[hc % 3][2 * j + 1]);
                mma16816(ck[j], ak[sl % P1_PRE], b[hc % 3][2 * j], b[hc % 3][2 * j + 1]);
              }
              if (sl + P1_PRE < R_NS) { ldsm4t(aq[sl % P1_PRE], wa + R_WQ + (sl + P1_PRE) * 2048); ldsm4t(ak[sl % P1_PRE], wa + R_WK + (sl + P1_PRE) * 2048); }
            }
          }
        }
        if (!__any_sync(0xffffffffu, bad)) break;
#pragma unroll 1
        for (int i = 1; i < 5; i++) mbar_wait(sb + RB_MEM + 8 * i, s & 1);
        if (PRE_EARLY) preload();
      }
      const uint32_t q0 = pack_bf16(cq[0][0] + cq[1][0], cq[0][1] + cq[1][1]), q1 = pack_bf16(cq[0][2] + cq[1][2], cq[0][3] + cq[1][3]);
      const uint32_t k0 = pack_bf16(ck[0][0] + ck[1][0], ck[0][1] + ck[1][1]), k1 = pack_bf16(ck[0][2] + ck[1][2], ck[0][3] + ck[1][3]);
      const uint32_t qp = qm + peer, bp = sb + RB_QK + peer;
      st_async32(qp, q0, bp);
      st_async32(qp + 128, q1, bp);
      st_async32(qp + 10 * R_GS, k0, bp);
      st_async32(qp + 10 * R_GS + 128, k1, bp);
      sts32(qm, q0);
      sts32(qm + 128, q1);
      sts32(qm + 10 * R_GS, k0);
      sts32(qm + 10 * R_GS + 128, k1);
      bar_arrive(NB_P1, 256);
      fence_async_smem();
      __syncwarp();
      arrive_elect(sb + RB_QK);
      TRB(1);
      float d[20];
#pragma unroll
      for (int i = 0; i < 20; i++) d[i] = 0.f;
      constexpr uint32_t HI = R_GS >> 4;
      const uint32_t qd = desc_lo(sb + R_QS, 128);
      mbar_wait(sb + RB_QK, s & 1);
      TRB(16);
      wg_fence();
#pragma unroll
      for (int k = 0; k < 8; k++) wgmma_ss_n40_a1b1(d, mk_desc(qd + (k >> 2) * (R_HS >> 4) + (k & 3) * 16, HI), mk_desc(qd + (k >> 2) * (R_HS >> 4) + (k & 3) * 16 + 6 * HI, HI), k != 0);
      wg_commit();
      bar_arrive(NB_S, 256);
      const int ln = (qm >> 2) & 31, tt = ln & 3;
      if (w4 == 0) {
        const int gg = ln >> 2;
        const uint32_t pa = sb + R_PS + gg * 128;
        const uint32_t pax = pa + ((tt ^ gg) << 4), pam = pa + ((4 ^ gg) << 4) + tt * 4;
        wg_wait<0>();
        fence_regs(d);
        TRB(17);
        rmt_softmax_row<false>(d, 0, 0, pax, pam);
        bar_arrive(NB_PM, 160);
        TRB(18);
      } else if (w4 < 3) {
        const int tq = (ln & 24) + 4 * (w4 - 1) + ((ln >> 2) & 1), r7 = tq & 7;
        const uint32_t pa = sb + R_PS + (8 + tq) * 128;
        wg_wait<0>();
        fence_regs(d);
        rmt_softmax_row<true>(d, 0, tq - 8 * tt, pa + ((tt ^ r7) << 4), pa + ((4 ^ r7) << 4) + tt * 4);
        rmt_softmax_row<true>(d, 1, tq + 2 - 8 * tt, pa + 256 + ((tt ^ r7 ^ 2) << 4), pa + 256 + ((6 ^ r7) << 4) + tt * 4);
        fence_async_smem();
        bar_arrive(NB_PX, 192);
        TRW(15, 1);
      } else {
        if (!LAST) {
          if (ln < 7) mbar_expect(sb + RB_MEM + 8 * ln, ln == 6 ? QK_TX : ln == 5 ? 9216 : ln == 4 ? 1024 : 2048);
          if (ln == 11 && s < 62) mbar_expect(sb + RB_XF + 8 * (s & 1), 9 * 4096);
        } else if (ln < 5) {
          mbar_expect(sb + RB_MEM + 8 * ln, ln == 4 ? 8192 : 16384);
        }
        __syncwarp();
        wg_wait<0>();
        fence_regs(d);
      }
    };
    auto bulk = [&](int s) {
      const bool FIRST = s < 0;
      float dq[16], dk[16];
#pragma unroll
      for (int i = 0; i < 16; i++) dq[i] = dk[i] = 0.f;
      mbar_wait(sb + RB_XF + 8 * ((s + 1) & 1), ((s + 1) >> 1) & 1);
      const uint32_t hd = desc_lo(sb + R_H + ((s + 1) & 1) * 5120, 16), wd = desc_lo(sb + R_WQ, 16);
      auto bdesc = [&](int k) { return mk_desc(hd + (hoff(k >> 2) >> 4) + (k & 3) * 2, DHI_SW128); };
      const uint32_t qx = qm + 2 * R_GS + (qm & 12) * (R_GS / 4 - 1);
      if (s == 56) {
        const int ln = (qm >> 2) & 31;
        uint32_t* z = g_xch2 + 2 * cl * XCH_SLOT + rank * 288 + w4 * 64 + ln * 2;
#pragma unroll
        for (int i = 0; i < 8; i++) {
          st_relaxed64(z + i * XCH_CL, 0u, 0u);
          if (w4 == 3) st_relaxed32(z + i * XCH_CL + 64 - ln, 0u);
        }
      }
      if (!FIRST) bar_sync(NB_P3, 256);
      TRB(2);
      wg_fence();
      static_for<0, 73>([&](auto i_) {
        constexpr int i = decltype(i_)::value;
        constexpr char c = B_SEQ[i];
        constexpr int r = seq_count(c, i), nq = seq_count('q', i) + seq_count('Q', i), nk = seq_count('k', i) + seq_count('K', i);
        if constexpr (c == 'q') wgmma_rs_n32_b0(dq, wq[r][0], wq[r][1], wq[r][2], wq[r][3], bdesc(qk_step(r, true)), nq != 0);
        if constexpr (c == 'k') wgmma_rs_n32_b0(dk, wk[r][0], wk[r][1], wk[r][2], wk[r][3], bdesc(qk_step(r, true)), nk != 0);
        if constexpr (c == 'Q') wgmma_ss_n32_a1b0(dq, mk_desc(wd + r * 128, DHI_SW128), bdesc(qk_step(r, false)), nq != 0);
        if constexpr (c == 'K') wgmma_ss_n32_a1b0(dk, mk_desc(wd + (R_NS + r) * 128, DHI_SW128), bdesc(qk_step(r, false)), nk != 0);
        if constexpr (c == '|') {
          if (!FIRST) bar_sync(NB_RD, 256);
          TRB(6);
        }
      });
      wg_commit();
      if (FIRST) asm volatile("barrier.cluster.wait.aligned;" ::: "memory");
      if (PRE_EARLY) preload();
      wg_wait<0>();
      fence_regs(dq);
      fence_regs(dk);
      TRB(3);
#pragma unroll
      for (int r = 0; r < 2; r++) {
        sts128(qx + r * 128, pack_bf16(dq[2 * r], dq[2 * r + 1]), pack_bf16(dq[4 + 2 * r], dq[5 + 2 * r]), pack_bf16(dq[8 + 2 * r], dq[9 + 2 * r]), pack_bf16(dq[12 + 2 * r], dq[13 + 2 * r]));
        sts128(qx + 4 * R_GS + r * 128, pack_bf16(dk[2 * r], dk[2 * r + 1]), pack_bf16(dk[4 + 2 * r], dk[5 + 2 * r]), pack_bf16(dk[8 + 2 * r], dk[9 + 2 * r]), pack_bf16(dk[12 + 2 * r], dk[13 + 2 * r]));
      }
      __syncwarp();
      arrive_elect(sb + RB_QXL);
      TRB(4);
    };
    TRG(3);
#pragma unroll 1
    for (int s = -1; s < 63;) {
      asm volatile("" : "+r"(wa), "+r"(la), "+r"(qm));
      bulk(s);
      s++;
#ifdef DEV_TRS
      TRG(16 + s);
#endif
      chain(s);
    }
    cluster_sync();
    {
      const int ln = (qm >> 2) & 31, g = ln >> 2, t4 = ln & 3, src = (ln & 7) + (ln >> 4) * 8, hf = (ln >> 3) & 1;
      uint32_t* x = g_xch2 + rank * 288 + w4 * 64 + ln * 2;
      uint32_t* out = P.out + (62 * 32 + 16 * cl + (rank & 7)) * DM + DM / 2 + (rank >> 3) * 16;
      auto finish = [&](auto nb_, uint32_t a, int stride, int key, uint32_t* x, int col) {
        uint2 o[8];
#pragma unroll
        for (int i = 0; i < 8; i++) {
          const int j = (2 * cl + 2 + i) & 7;
          o[i] = xch_add<decltype(nb_)::value>(a + j * stride, key, 1u);
          if (i < 6) st_relaxed64(x + j * XCH_SLOT + cl * XCH_CL, o[i].x, o[i].y);
        }
        return [=]() {
          uint32_t r1;
          const uint32_t r0 = xch_poll<true>(x + 2 * cl * XCH_SLOT, cl, o[6], x + (2 * cl + 1) * XCH_SLOT, o[7], r1);
          out[col] = r0;
          out[col + 8 * DM] = r1;
        };
      };
      const int cp = 16 * (t4 >> 1) + 8 * ((g >> 1) & 1) + 4 * (t4 & 1) + 2 * (g >> 2) + (g & 1), cn = 8 * (ln & 1) + (ln >> 2);
      if (w4 == 3) {
        mbar_wait(sb + RB_MEM + 32, 0);
        finish(IC<2>(), sb + R_TN + src * 64 + ((hf ^ ((ln >> 1) & 3)) << 4), 1024, hf, x + 64 + 2 * (cn - ln), 256 + cn)();
      }
      mbar_wait(sb + RB_MEM + 8 * w4, 0);
      auto last = finish(IC<4>(), sb + R_T + w4 * 16384 + src * 128 + ((hf ^ (ln & 7)) << 4), 2048, ln >> 3, x, 32 * (2 * w4 + (cp >> 4)) + (cp & 15));
      asm volatile("barrier.cluster.arrive.relaxed.aligned;" ::: "memory");
      last();
      TRG(6);
      asm volatile("barrier.cluster.wait.aligned;" ::: "memory");
    }
#ifdef DEV_TRACE
    for (int i = threadIdx.x; i < 16 * 32; i += 128) g_trace_b[bid * 4096 + i] = lds32(sb + R_QS + R_GS + ((i >> 8) ^ 1) * R_HS + (i & 255) * 4);
#endif
  } else {
    uint32_t wo[9][4][4], wv[R_VR][4];
#pragma unroll
    for (int i = 0; i < 9; i++) {
      const int T = i < 8 ? 8 * (i >> 1) + 2 * w4 + (i & 1) : 32 + 2 * (w4 & 1) + (w4 >> 1);
      const int quad = i < 8 ? (g >> 2) * 2 + (g & 1) : g & 3, odd = i < 8 ? (g >> 1) & 1 : g >> 2;
      const uint32_t a = sb + ST_O + (T >> 2) * 8192 + t4 * 256 + (quad & 1) * 8;
      const uint32_t ch = (T & 3) * 2 + (quad >> 1), sel = odd ? 0x7632 : 0x5410;
      const uint32_t a0 = a + ((ch ^ (2 * t4)) << 4), a1 = a + 128 + ((ch ^ (2 * t4 + 1)) << 4);
#pragma unroll
      for (int k = 0; k < 8; k++) {
        const uint2 x = lds64(a0 + k * 1024), y = lds64(a1 + k * 1024);
        wo[i][k >> 1][(k & 1) * 2] = __byte_perm(x.x, y.x, sel);
        wo[i][k >> 1][(k & 1) * 2 + 1] = __byte_perm(x.y, y.y, sel);
      }
    }
    fence_async_smem();
    bar_arrive(NB_P3, 256);
    bar_sync(NB_O, 128);
    if (w4 == 0 && elect()) mbar_expect(sb + RB_W + 8, 73728);
    if (elect())
      for (int k = w4; k < 36; k += 4) {
        const int sl = v_slot(k);
        tma2d(sb + (v_in_reg(k) ? (sl < 6 ? ST_V0 : ST_V1) : R_WV) + sl * 2048, &P.wv, c0, k * 16, sb + RB_W + 8);
      }
    __syncwarp();
    mbar_wait(sb + RB_W + 8, 1);
#pragma unroll
    for (int r = 0; r < R_VR; r++) ldsm4t(wv[r], wa + (r < 6 ? ST_V0 : ST_V1) + r * 2048);
    fence_async_smem();
    asm volatile("barrier.cluster.arrive.relaxed.aligned;" ::: "memory");
    const uint32_t sb0 = mapa(sb, 0), tok = rank & 7;
    uint32_t rsb = mapa(sb + RB_RS, (w4 & 1) * 8 + 2 * t4);
    const uint32_t rrow = rank ^ ((t4 & 1) << 3) ^ (t4 & 2), nrow = rank ^ ((t4 & 1) << 2);
    uint32_t rsA = rsb + (R_RS - RB_RS) + rrow * 128 + (((w4 >> 1) * 64 + g * 8) ^ ((rrow & 7) << 4));
    uint32_t rsN = rsb + (R_RS + 8192 - RB_RS) + nrow * 64 + (((w4 >> 1) * 32 + g * 4) ^ (((nrow >> 1) & 3) << 4));
    const uint32_t cp = 16 * (t4 >> 1) + 8 * ((g >> 1) & 1) + 4 * (t4 & 1) + 2 * (g >> 2) + (g & 1);
    uint32_t agd = sb0 + R_HM + tok * 128 + hoff(2 * w4 + (cp >> 4)) + ((((rank >> 3) * 4 + ((cp & 15) >> 2)) ^ tok) << 4) + (cp & 3) * 4;
    uint32_t* xb = g_xch + rank * 288 + w4 * 64 + lane * 2;
    uint32_t vx[8];
#pragma unroll
    for (int i = 0; i < 8; i++) vx[i] = 0;

    auto step = [&](int s) {
      const bool FIRST = s < 0, LAST = s == 63, MID = !FIRST && !LAST;
      const int par = (s + 1) & 1;
      float d[20];
#pragma unroll
      for (int i = 0; i < 20; i++) d[i] = 0.f;
      if (!LAST) mbar_wait(sb + RB_XF + 8 * par, ((s + 1) >> 1) & 1);
      const uint32_t hd = desc_lo(sb + R_H + par * 4096, 16), vd = desc_lo(sb + R_WV, 16);
      if (!FIRST) {
        if (w4 == 0) {
          mbar_wait(sb + RB_QXL, s & 1);
          mbar_wait(sb + RB_MEM + QX_AFTER * 8, s & 1);
          fence_async_smem();
          if (elect()) {
            const uint32_t src = sb + R_QS + (rank & 1) * R_HS + 2 * R_GS, dst = mapa(src, rank ^ 1), bar = mapa(sb + RB_QK, rank ^ 1), cut = 256 + rank * 512;
            asm volatile("cp.async.bulk.shared::cluster.shared::cta.mbarrier::complete_tx::bytes [%0], [%1], %2, [%3];" ::"r"(dst + cut), "r"(src + cut), "r"(8 * R_GS - cut), "r"(bar) : "memory");
            asm volatile("cp.async.bulk.shared::cluster.shared::cta.mbarrier::complete_tx::bytes [%0], [%1], %2, [%3];" ::"r"(dst), "r"(src), "r"(cut), "r"(bar) : "memory");
          }
          __syncwarp();
          TRW(7, 0);
        }
#pragma unroll
        for (int i = 0; i < 5; i++) { mbar_wait(sb + RB_MEM + 8 * i, s & 1); if (i == 4) TRW(30, 2); }
        fence_async_smem();
        bar_sync(NB_P1, 256);
      }
      wg_fence();
#pragma unroll
      for (int k = 0; k < 36; k++) {
        if (k == V_N1 && !FIRST) bar_sync(NB_S, 256);
        const uint64_t db = mk_desc(hd + (hoff(k >> 2) >> 4) + (k & 3) * 2, DHI_SW128);
        if (v_in_reg(k)) wgmma_rs_n40_b0(d, wv[v_slot(k)][0], wv[v_slot(k)][1], wv[v_slot(k)][2], wv[v_slot(k)][3], db, 1);
        else wgmma_ss_n40_a1b0(d, mk_desc(vd + v_slot(k) * 128, DHI_SW128), db, k != 0);
      }
      wg_commit();
      TRB(8);
      uint32_t vm0, vm1, vn[8];
      auto pack_v = [&]() {
#pragma unroll
        for (int i = 0; i < 8; i++) vn[i] = par ? pack_bf16(d[2 * i + 4], d[2 * i + 5]) : pack_bf16(d[2 * i], d[2 * i + 1]);
      };
      if (MID) {
        float o[4] = {0.f, 0.f, 0.f, 0.f};
        uint32_t b0[4], b1[4];
        bar_sync(NB_PM, 160);
        ldsm4(b0, la + R_PS);
        ldsm4(b1, (la ^ 64) + R_PS);
        {
          const uint32_t x0[4] = {vx[0], vx[1], vx[2], vx[3]}, x1[4] = {vx[4], vx[5], vx[6], vx[7]};
          float o2[4] = {0.f, 0.f, 0.f, 0.f};
          wg_wait<0>();
          fence_regs(d);
          TRB(9);
          mma16816(o, x0, b0[0], b0[1]);
          mma16816(o2, x1, b0[2], b0[3]);
          vm0 = par ? pack_bf16(d[0], d[1]) : pack_bf16(d[16], d[17]);
          vm1 = par ? pack_bf16(d[2], d[3]) : pack_bf16(d[18], d[19]);
          float o3[4] = {0.f, 0.f, 0.f, 0.f};
          mma1688(o3, vm0, vm1, b1[0]);
          stsm2t(wa + R_OS, pack_bf16(o[0] + o2[0] + o3[0], o[1] + o2[1] + o3[1]), pack_bf16(o[2] + o2[2] + o3[2], o[3] + o2[3] + o3[3]));
        }
        bar_sync(NB_O, 128);
        TRB(11);
        ldsm4(b0, la + R_OS);
        ldsm4(b1, (la ^ 64) + R_OS);
        auto send = [&](int j, const float (&c0_)[4], const float (&c1_)[4]) {
          st_async64(rsA + j * 2048, pack_bf16(c0_[0], c0_[2]), pack_bf16(c1_[0], c1_[2]), rsb);
          st_async64(rsA + j * 2048 + CTA1, pack_bf16(c0_[1], c0_[3]), pack_bf16(c1_[1], c1_[3]), rsb + CTA1);
        };
        auto tile = [&](float (&c)[4], int i, int k) {
          if (k == 0) mma16816z(c, wo[i][0], b0[0], b0[1]);
          else mma16816(c, wo[i][k], k < 2 ? b0[2 * k] : b1[2 * k - 4], k < 2 ? b0[2 * k + 1] : b1[2 * k - 3]);
        };
        {
          float c[4][4];
          mma16816z(c[0], wo[0][0], b0[0], b0[1]);
          mma16816z(c[1], wo[1][0], b0[0], b0[1]);
          mma16816z(c[2], wo[0][2], b1[0], b1[1]);
          mma16816z(c[3], wo[1][2], b1[0], b1[1]);
          mma16816(c[0], wo[0][1], b0[2], b0[3]);
          mma16816(c[1], wo[1][1], b0[2], b0[3]);
          mma16816(c[2], wo[0][3], b1[2], b1[3]);
          mma16816(c[3], wo[1][3], b1[2], b1[3]);
          pack_v();
#pragma unroll
          for (int i = 0; i < 4; i++) { c[0][i] += c[2][i]; c[1][i] += c[3][i]; }
          send(0, c[0], c[1]);
          fence_regs(vn);
        }
        sched_fence(rsb);
        TRB(13);
        {
          float c[3][4];
#pragma unroll
          for (int k = 0; k < 4; k++) { tile(c[0], 8, k); tile(c[1], 2, k); tile(c[2], 3, k); }
          st_async32(rsN, pack_bf16(c[0][0], c[0][2]), rsb);
          st_async32(rsN + CTA1, pack_bf16(c[0][1], c[0][3]), rsb + CTA1);
          send(1, c[1], c[2]);
        }
        sched_fence(la);
        {
          float c[4][4];
#pragma unroll
          for (int k = 0; k < 4; k++)
#pragma unroll
            for (int i = 0; i < 4; i++) tile(c[i], 4 + i, k);
          if (P3_EARLY == 1) { sched_fence(rsA); bar_arrive(NB_P3, 256); }
          send(2, c[0], c[1]);
          send(3, c[2], c[3]);
          if (P3_EARLY == 2) bar_arrive(NB_P3, 256);
        }
        TRB(12);
      } else {
        if (LAST) bar_sync(NB_PM, 160);
        wg_wait<0>();
        fence_regs(d);
        if (LAST) asm volatile("barrier.cluster.arrive.relaxed.aligned;" ::: "memory");
        vm0 = pack_bf16(d[16], d[17]);
        vm1 = pack_bf16(d[18], d[19]);
        pack_v();
      }
      if (FIRST) {
        asm volatile("barrier.cluster.wait.aligned;" ::: "memory");
        TRG(7);
      } else {
        float e[16];
#pragma unroll
        for (int i = 0; i < 16; i++) e[i] = 0.f;
        uint32_t z0 = 0, z1 = 0;
        asm volatile("" : "+r"(z0), "+r"(z1), "+r"(vm0), "+r"(vm1));
        const uint32_t pd = desc_lo(sb + R_PS + 1024, 16);
        fence_regs(vx);
        bar_sync(NB_PX, 192);
        wg_fence();
        wgmma_rs_n32_b0(e, vx[0], vx[1], vx[2], vx[3], mk_desc(pd, DHI_SW128), 0);
        wgmma_rs_n32_b0(e, vx[4], vx[5], vx[6], vx[7], mk_desc(pd + 2, DHI_SW128), 1);
        wgmma_rs_n32_b0(e, vm0, vm1, z0, z1, mk_desc(pd + 4, DHI_SW128), 1);
        wg_commit();
        if (!P3_EARLY && !LAST) bar_arrive(NB_P3, 256);
        wg_wait<0>();
        fence_regs(e);
        fence_regs(vx);
        const uint32_t oa = wa + (s < 62 ? R_PS + 1024 : R_H + (s - 62) * 4096);
        bar_sync(NB_O, 128);
        stsm4t(oa, pack_bf16(e[0], e[1]), pack_bf16(e[2], e[3]), pack_bf16(e[4], e[5]), pack_bf16(e[6], e[7]));
        stsm4t(oa + 2048, pack_bf16(e[8], e[9]), pack_bf16(e[10], e[11]), pack_bf16(e[12], e[13]), pack_bf16(e[14], e[15]));
        TRB(14);
      }
      auto store_x = [&]() {
        fence_async_smem();
        if (w4 == 2) bar_sync(NB_O2, 128); else bar_arrive(NB_O2, 128);
        if (w4 == 2 && s < 62 && elect()) {
          asm volatile("cp.async.bulk.tensor.2d.global.shared::cta.bulk_group [%0, {%1,%2}], [%3];" ::"l"(&P.ox), "r"(c0), "r"(3 * SEQ + s * 32), "r"(sb + R_PS + 1024) : "memory");
          asm volatile("cp.async.bulk.commit_group;" ::: "memory");
        }
        __syncwarp();
      };
      if (MID) {
        const uint32_t tag = ((s >> 1) & 1) ^ 1;
        uint32_t* x = xb + (s & 1) * XCH_SLOT;
        uint32_t* xw = x + cl * XCH_CL;
        const int src = (ln & 7) + (ln >> 4) * 8, hf = (ln >> 3) & 1;
        const uint32_t ra = sb + R_RS + w4 * 2048 + src * 128 + ((hf ^ (ln & 7)) << 4);
        auto delay = [&](uint32_t t0) {
          while ((uint32_t)clock() - t0 < POLL_DELAY + w4 * POLL_STAG) {}
        };
        uint32_t rn;
        const uint32_t agb = sb0 + RB_MEM + 8 * w4 + (uint32_t)(ln >> 5);
        if (w4 == 3) {
          const int cn = 8 * (ln & 1) + (ln >> 2), no = 64 + 2 * (cn - ln);
          const uint32_t rb = sb + R_RS + 8192 + src * 64 + ((hf ^ ((ln >> 1) & 3)) << 4);
          mbar_wait(sb + RB_RS, s & 1);
          const uint2 o = xch_reduce<4>(ra, ln >> 3, xw, tag);
          const uint2 on = xch_reduce<2>(rb, hf, xw + no, tag);
          const uint32_t t0 = clock();
          bar_arrive(NB_RD, 256);
          TRW(27, 3);
          store_x();
          const uint32_t off = (ln & 2) * 4 * CTA1;
          const uint32_t agn = sb0 + R_HM + tok * 128 + hoff(8) + ((((rank >> 3) * 4 + (cn >> 2)) ^ tok) << 4) + (cn & 3) * 4;
          XSend<16, 6> xs(agd, agb);
          delay(t0);
          const uint32_t r = xch_poll<true>(x, cl, o, x + no, on, rn);
          TRW(28, 3);
          xs.send(r);
          XSend<8, 1>(agn ^ off, (agb + 8) ^ off).send(rn);
          TRW(22, 3);
        } else {
          mbar_wait(sb + RB_RS, s & 1);
          TRB(19);
          const uint2 o = xch_reduce<4>(ra, ln >> 3, xw, tag);
          const uint32_t t0 = clock();
          bar_arrive(NB_RD, 256);
          TRB(25);
          store_x();
          if (w4 == 1 && rank < 9 && s < 62 && elect()) {
            tma2d_mc(sb + R_H + hoff(rank) + (s & 1) * 5120, &P.x, rank * 64, (s + 2) * 32, sb + RB_XF + 8 * (s & 1), 0xffff);
            asm volatile("cp.async.bulk.prefetch.tensor.2d.L2.global [%0, {%1,%2}];" ::"l"(&P.x), "r"(rank * 64), "r"(min(s + 3 + cl, 63) * 32) : "memory");
          }
          __syncwarp();
          XSend<16, 12> xs(agd, agb);
          delay(t0);
          asm volatile("cp.async.bulk.wait_group.read 0;" ::: "memory");
          const uint32_t r = xch_poll<false>(x, cl, o, x, o, rn);
          TRB(26); TRW(10, 1); TRW(20, 2);
          xs.send(r);
          TRB(21); TRW(23, 1); TRW(24, 2);
          if (w4 == 2 && ((s & 3) == 3 || s == 61)) {
            asm volatile("cp.async.bulk.wait_group 0;" ::: "memory");
#if PUB_REL
            asm volatile("{.reg .pred q; elect.sync _|q, 0xffffffff; @q red.release.gpu.global.add.u32 [%0], 1;}" ::"l"(&g_sync[SY_OX + (s >> 2)]) : "memory");
#else
            asm volatile("{.reg .pred q; elect.sync _|q, 0xffffffff; @q red.relaxed.gpu.global.add.u32 [%0], 1;}" ::"l"(&g_sync[SY_OX + (s >> 2)]) : "memory");
#endif
          }
        }
      }
#pragma unroll
      for (int i = 0; i < 8; i++) vx[i] = vn[i];
    };
    TRG(5);
#pragma unroll 1
    for (int s = -1; s < 64; s++) {
      asm volatile("" : "+r"(wa), "+r"(la), "+r"(rsb), "+r"(rsA), "+r"(rsN), "+r"(agd), "+r"(ln), "+l"(xb));
      step(s);
    }
    fence_async_smem();
    bar_sync(NB_O2, 128);
    {
      float a0[32], a1[32];
      uint32_t u[32];
#pragma unroll
      for (int i = 0; i < 32; i++) a0[i] = a1[i] = 0.f;
      const uint32_t od = desc_lo(sb + R_H, 16), tb = rsb - (RB_RS - RB_MEM), ta = rsA - (R_RS - R_T), tn = rsN - (R_RS + 8192 - R_TN);
      auto issue = [&](float (&a)[32], int i) {
#pragma unroll
        for (int k = 0; k < 4; k++) wgmma_rs_n64_b0(a, wo[i][k][0], wo[i][k][1], wo[i][k][2], wo[i][k][3], mk_desc(od + 2 * k, DHI_SW128), k);
      };
      wg_fence();
      issue(a0, 8);
      wg_commit();
      if (w4 != 2) {
        uint32_t* z = g_xch + XCH_SLOT + cl * XCH_CL + rank * 288 + (w4 == 3 ? 64 : w4 * 32) + ln;
        st_relaxed32(z, 0u); st_relaxed32(z + 96, 0u); st_relaxed32(z + 192, 0u);
      }
      wg_wait<0>();
      fence_regs(a0);
#pragma unroll
      for (int j = 0; j < 16; j++) u[j] = pack_bf16(a0[4 * (j >> 1) + (j & 1)], a0[4 * (j >> 1) + (j & 1) + 2]);
      wg_fence();
      issue(a0, 0);
      issue(a1, 1);
      wg_commit();
      asm volatile("barrier.cluster.wait.aligned;" ::: "memory");
#pragma unroll
      for (int j = 0; j < 16; j++) st_async32(tn + (j >> 1) * 1024 + (j & 1) * CTA1, u[j], tb + 32 + (j & 1) * CTA1);
#pragma unroll
      for (int b = 0; b < 4; b++) {
        wg_wait<0>();
        fence_regs(a0);
        fence_regs(a1);
#pragma unroll
        for (int j = 0; j < 16; j++) {
          u[2 * j] = pack_bf16(a0[4 * (j >> 1) + (j & 1)], a0[4 * (j >> 1) + (j & 1) + 2]);
          u[2 * j + 1] = pack_bf16(a1[4 * (j >> 1) + (j & 1)], a1[4 * (j >> 1) + (j & 1) + 2]);
        }
        fence_regs(u);
        if (b < 3) {
          wg_fence();
          issue(a0, 2 * b + 2);
          issue(a1, 2 * b + 3);
          wg_commit();
        }
#pragma unroll
        for (int j = 0; j < 16; j++) st_async64(ta + (b * 8 + (j >> 1)) * 2048 + (j & 1) * CTA1, u[2 * j], u[2 * j + 1], tb + 8 * b + (j & 1) * CTA1);
      }
    }
    cluster_sync();
  }
}

void rmt_setup() {
  cudaFuncSetAttribute(rmt_kernel, cudaFuncAttributeMaxDynamicSharedMemorySize, R_SMEM);
  cudaFuncSetAttribute(rmt_kernel, cudaFuncAttributeNonPortableClusterSizeAllowed, 1);
}
void rmt_launch(EncodeFn enc, void* const* d_in, void* scr, void* out) {
  RmtParams R;
  map2d(enc, &R.wq, d_in[8], DM, HDALL, 16);
  map2d(enc, &R.wk, d_in[9], DM, HDALL, 16);
  map2d(enc, &R.wv, d_in[10], DM, HDALL, 16);
  map2d(enc, &R.wo, d_in[11], HDALL, DM, 64);
  map2d(enc, &R.x, d_in[6], SEQ, DM, 32);
  map2d(enc, &R.mem, d_in[7], 8, DM, 8);
  map2d(enc, &R.ox, scr, 4 * SEQ, HDALL, 32);
  cudaLaunchConfig_t cfg = {};
  R.out = (uint32_t*)out;
  R.ckv = (const __nv_bfloat16*)d_in[1]; R.wuk = (const __nv_bfloat16*)d_in[3]; R.wuv = (const __nv_bfloat16*)d_in[4];
  cfg.gridDim = dim3(64);
  cfg.blockDim = dim3(256);
  cfg.dynamicSmemBytes = R_SMEM;
  cfg.stream = cudaStreamPerThread;
  cudaLaunchAttribute at[1];
  at[0].id = cudaLaunchAttributeClusterDimension;
  at[0].val.clusterDim.x = 16;
  at[0].val.clusterDim.y = 1;
  at[0].val.clusterDim.z = 1;
  cfg.attrs = at;
  cfg.numAttrs = 1;
  cudaLaunchKernelEx(&cfg, rmt_kernel, R);
}


const uint16_t h_order[] = {
    0, 1, 2, 3, 4, 5, 6, 7, 8, 9, 10, 11, 12, 13, 14, 15, 16, 17, 18, 19,
    20, 21, 22, 23, 24, 25, 26, 27, 28, 29, 30, 31, 32, 33, 4096, 4097, 34, 35, 36, 37,
    38, 39, 40, 41, 42, 43, 44, 45, 46, 47, 48, 49, 50, 51, 52, 53, 54, 55, 56, 57,
    58, 59, 60, 61, 62, 63, 64, 65, 66, 67, 68, 69, 70, 71, 72, 73, 74, 75, 76, 77,
    78, 79, 80, 81, 82, 83, 84, 85, 86, 87, 88, 89, 90, 91, 92, 93, 94, 95, 96, 97,
    98, 99, 100, 101, 102, 103, 4103, 4102, 4101, 4100, 4099, 104, 105, 106, 107, 108, 109, 110, 111, 4111,
    4110, 4109, 4108, 4107, 112, 113, 114, 115, 116, 117, 118, 119, 4119, 4118, 4117, 4116, 4115, 120, 121, 122,
    123, 124, 125, 126, 127, 4127, 4126, 4125, 4124, 4123, 128, 129, 130, 131, 132, 133, 134, 135, 4135, 4134,
    4133, 4132, 4131, 136, 137, 138, 139, 140, 12288, 12544, 12800, 141, 142, 143, 4143, 4142, 4141, 4140, 4139, 144,
    145, 146, 147, 148, 149, 150, 151, 4151, 4150, 4149, 4148, 4147, 152, 153, 154, 155, 156, 157, 158, 159,
    4159, 4158, 4157, 4156, 4155, 160, 161, 162, 163, 164, 165, 166, 167, 4167, 4166, 4165, 4164, 4163, 168, 169,
    170, 171, 172, 173, 174, 175, 4175, 4174, 4173, 4172, 4171, 176, 177, 178, 179, 180, 181, 182, 183, 4183,
    4182, 4181, 4180, 4179, 184, 185, 186, 187, 188, 189, 190, 191, 4191, 12289, 12545, 12801, 4190, 4189, 4188, 4187,
    192, 193, 194, 195, 196, 197, 198, 199, 4199, 4198, 4197, 4196, 4195, 200, 201, 202, 203, 204, 205, 206,
    207, 4207, 4206, 4205, 4204, 4203, 208, 209, 210, 211, 212, 213, 214, 215, 4215, 4214, 4213, 4212, 4211, 216,
    217, 12290, 12546, 12802, 218, 219, 220, 221, 222, 223, 4223, 4222, 4221, 4220, 4219, 224, 225, 226, 227, 228,
    229, 230, 231, 4231, 4230, 4229, 4228, 4227, 232, 233, 234, 235, 236, 237, 238, 239, 4239, 4238, 4237, 4236,
    4235, 240, 241, 242, 243, 244, 245, 246, 247, 4247, 4246, 4245, 4244, 4243, 248, 249, 250, 251, 252, 253,
    254, 255, 4255, 4254, 4253, 12291, 12547, 12803, 4252, 4251, 4263, 4262, 4261, 4260, 4259, 4271, 4270, 4269, 4268, 4267,
    4279, 4278, 4277, 4276, 4275, 4287, 4286, 4285, 4284, 4283, 4295, 4294, 4293, 4292, 4291, 4303, 4302, 4301, 4300, 4299,
    4311, 4310, 4309, 4308, 4307, 4319, 4318, 4317, 4316, 4315, 4327, 4326, 4325, 4324, 4323, 4335, 4334, 4333, 4332, 4331,
    8196, 8452, 8708, 4343, 4342, 4341, 4340, 8197, 8453, 8709, 4339, 4351, 4350, 4349, 4348, 4347, 8198, 8454, 8710, 8195,
    8451, 8707, 4098, 4106, 4105, 4104, 4114, 4113, 4112, 4122, 4121, 4120, 4130, 4129, 4128, 4138, 4137, 4136, 4146, 4145,
    4144, 4154, 4153, 4152, 4162, 4161, 4160, 4170, 4169, 4168, 4178, 4177, 4176, 4186, 4185, 4184, 4194, 4193, 4192, 4202,
    4201, 4200, 4210, 4209, 4208, 4218, 4217, 4216, 4226, 4225, 4224, 4234, 12292, 12548, 12804, 4233, 8199, 8455, 8711, 4232,
    4242, 4241, 4240, 4250, 4249, 4248, 4258, 4257, 4256, 4266, 4265, 4264, 4274, 4273, 8193, 8449, 8705, 12293, 12549, 12805,
    4272, 4282, 12294, 12550, 12806, 4281, 4280, 8192, 8448, 8704, 8194, 8450, 8706, 4290, 4289, 4288, 4298, 4297, 4296, 4306,
    4305, 4304, 4314, 4313, 4312, 4322, 4321, 4320, 4330, 4329, 4328, 4338, 4337, 4336, 4346, 4345, 4344, 28679, 28935, 29191,
    29447, 29703, 29959, 30215, 30471, 30727, 28687, 28943, 29199, 29455, 29711, 29967, 30223, 30479, 30735,
};
int build_tasks(uint16_t* t) {
  int n = 0;
#ifdef DEV_ORDER
  if (const char* fn = getenv("ORDER")) {
    FILE* f = fopen(fn, "r");
    int v;
    while (fscanf(f, "%d", &v) == 1) t[n++] = v;
    fclose(f);
    return n;
  }
#endif
  static_assert(sizeof(h_order) / 2 <= MAXTASK, "tasks");
  for (; n < (int)(sizeof(h_order) / 2); n++) t[n] = h_order[n];
  return n;
}

}

extern "C" void kernel_launch(void* const* d_in, const int* in_sizes, int n_in, void* d_out, int out_size) {
  (void)in_sizes; (void)n_in; (void)out_size;
  static EncodeFn enc = nullptr;
  static void* scr = nullptr;
  if (!enc) {
    cudaDriverEntryPointQueryResult q;
    cudaGetDriverEntryPoint("cuTensorMapEncodeTiled", (void**)&enc, cudaEnableDefault, &q);
    cudaGetSymbolAddress(&scr, g_scr);
    cudaFuncSetAttribute(main_kernel, cudaFuncAttributeMaxDynamicSharedMemorySize, M_SMEM);
    rmt_setup();
  }
  rmt_launch(enc, d_in, scr, d_out);

  MainParams P;
  map2d(enc, &P.ckv, d_in[1], SEQ, 512, 128);
  map3d(enc, &P.wuk, d_in[3], 512, HDALL, 64, 2);
  map3d(enc, &P.wuv, d_in[4], 512, HDALL, 64, 2);
  map2d(enc, &P.ax, d_in[0], SEQ, DM, 64);
  map2d(enc, &P.wq, d_in[2], DM, HDALL, 64);
  map2d(enc, &P.scr, scr, 4 * SEQ, HDALL, 128);
  map3d(enc, &P.woa, d_in[5], HDALL, DM, 32, 3);
  map3d(enc, &P.wob, d_in[11], HDALL, DM, 32, 3);
  map2d(enc, &P.scr_st, scr, 4 * SEQ, HDALL, ST_ROWS);
  map2d(enc, &P.out_st, d_out, SEQ, 2 * DM, ST_ROWS);
  map2d(enc, &P.woa1, d_in[5], HDALL, DM, 64);
  map2d(enc, &P.wob1, d_in[11], HDALL, DM, 64);
  map3d(enc, &P.scr2, scr, 4 * SEQ, HDALL, 128, 2);
  map2d(enc, &P.scr64, scr, 4 * SEQ, HDALL, 64);
  P.ntask = build_tasks(P.tasks);

  cudaLaunchConfig_t cfg = {};
  cfg.gridDim = dim3(2 * NCL);
  cfg.blockDim = dim3(384);
  cfg.dynamicSmemBytes = M_SMEM;
  cfg.stream = cudaStreamPerThread;
  cudaLaunchAttribute at[1];
  at[0].id = cudaLaunchAttributeProgrammaticStreamSerialization;
  at[0].val.programmaticStreamSerializationAllowed = 1;
  cfg.attrs = at;
  cfg.numAttrs = 1;
#ifdef DEV_SERIAL
  cfg.numAttrs = 0;
#endif
  cudaLaunchKernelEx(&cfg, main_kernel, P);
}
```

```cpp
#include <cuda_runtime.h>
#include <cuda_bf16.h>
#include <cuda.h>
#include <stdint.h>
#ifdef DEV_ORDER
#include <stdio.h>
#include <stdlib.h>
#endif

namespace {

constexpr int SEQ = 2048, DM = 576, HDALL = 4096;

__device__ __nv_bfloat16 g_scr[4ull * SEQ * HDALL];
constexpr int SY_Q = 0, SY_EXIT = 16, SY_KV = 32, SY_CTX = 32 + 256, SY_OX = 32 + 512, SY_N = 32 + 512 + 32;
__device__ unsigned g_sync[SY_N];

#ifdef DEV_END
__device__ long long g_end[512];
#define TRE(i) do { long long c_; asm volatile("mov.u64 %0, %%globaltimer;" : "=l"(c_)); g_end[i] = c_; } while (0)
#else
#define TRE(i)
#endif
#ifdef DEV_TRACE
__device__ long long g_trace[132 * 4096];
#ifdef DEV_TRF
#define TRF(slot) do { if (w4 == 0 && ti < 60) { uint32_t c_; asm volatile("mov.u32 %0, %%clock;" : "=r"(c_)::"memory"); if (elect()) g_trace[blockIdx.x * 4096 + 2048 + ti * 32 + wg * 16 + (slot)] = c_; __syncwarp(); } } while (0)
#else
#define TRF(slot)
#endif
#define TRM(slot) do { if ((threadIdx.x & 31) == 0) { long long c_; asm volatile("mov.u64 %0, %%globaltimer;" : "=l"(c_)); g_trace[blockIdx.x * 4096 + 4080 + (slot)] = c_; } } while (0)
#else
#define TRM(slot)
#define TRF(slot)
#endif

__device__ __forceinline__ void wgmma_ss_n256_a0b1(float (&d)[128], uint64_t da, uint64_t db, int sc) {
  asm volatile("{.reg .pred p; setp.ne.b32 p, %130, 0; wgmma.mma_async.sync.aligned.m64n256k16.f32.bf16.bf16 {%0,%1,%2,%3,%4,%5,%6,%7,%8,%9,%10,%11,%12,%13,%14,%15,%16,%17,%18,%19,%20,%21,%22,%23,%24,%25,%26,%27,%28,%29,%30,%31,%32,%33,%34,%35,%36,%37,%38,%39,%40,%41,%42,%43,%44,%45,%46,%47,%48,%49,%50,%51,%52,%53,%54,%55,%56,%57,%58,%59,%60,%61,%62,%63,%64,%65,%66,%67,%68,%69,%70,%71,%72,%73,%74,%75,%76,%77,%78,%79,%80,%81,%82,%83,%84,%85,%86,%87,%88,%89,%90,%91,%92,%93,%94,%95,%96,%97,%98,%99,%100,%101,%102,%103,%104,%105,%106,%107,%108,%109,%110,%111,%112,%113,%114,%115,%116,%117,%118,%119,%120,%121,%122,%123,%124,%125,%126,%127}, %128, %129, p, 1, 1, 0, 1;}"
    : "+f"(d[0]),"+f"(d[1]),"+f"(d[2]),"+f"(d[3]),"+f"(d[4]),"+f"(d[5]),"+f"(d[6]),"+f"(d[7]),"+f"(d[8]),"+f"(d[9]),"+f"(d[10]),"+f"(d[11]),"+f"(d[12]),"+f"(d[13]),"+f"(d[14]),"+f"(d[15]),"+f"(d[16]),"+f"(d[17]),"+f"(d[18]),"+f"(d[19]),"+f"(d[20]),"+f"(d[21]),"+f"(d[22]),"+f"(d[23]),"+f"(d[24]),"+f"(d[25]),"+f"(d[26]),"+f"(d[27]),"+f"(d[28]),"+f"(d[29]),"+f"(d[30]),"+f"(d[31]),"+f"(d[32]),"+f"(d[33]),"+f"(d[34]),"+f"(d[35]),"+f"(d[36]),"+f"(d[37]),"+f"(d[38]),"+f"(d[39]),"+f"(d[40]),"+f"(d[41]),"+f"(d[42]),"+f"(d[43]),"+f"(d[44]),"+f"(d[45]),"+f"(d[46]),"+f"(d[47]),"+f"(d[48]),"+f"(d[49]),"+f"(d[50]),"+f"(d[51]),"+f"(d[52]),"+f"(d[53]),"+f"(d[54]),"+f"(d[55]),"+f"(d[56]),"+f"(d[57]),"+f"(d[58]),"+f"(d[59]),"+f"(d[60]),"+f"(d[61]),"+f"(d[62]),"+f"(d[63]),"+f"(d[64]),"+f"(d[65]),"+f"(d[66]),"+f"(d[67]),"+f"(d[68]),"+f"(d[69]),"+f"(d[70]),"+f"(d[71]),"+f"(d[72]),"+f"(d[73]),"+f"(d[74]),"+f"(d[75]),"+f"(d[76]),"+f"(d[77]),"+f"(d[78]),"+f"(d[79]),"+f"(d[80]),"+f"(d[81]),"+f"(d[82]),"+f"(d[83]),"+f"(d[84]),"+f"(d[85]),"+f"(d[86]),"+f"(d[87]),"+f"(d[88]),"+f"(d[89]),"+f"(d[90]),"+f"(d[91]),"+f"(d[92]),"+f"(d[93]),"+f"(d[94]),"+f"(d[95]),"+f"(d[96]),"+f"(d[97]),"+f"(d[98]),"+f"(d[99]),"+f"(d[100]),"+f"(d[101]),"+f"(d[102]),"+f"(d[103]),"+f"(d[104]),"+f"(d[105]),"+f"(d[106]),"+f"(d[107]),"+f"(d[108]),"+f"(d[109]),"+f"(d[110]),"+f"(d[111]),"+f"(d[112]),"+f"(d[113]),"+f"(d[114]),"+f"(d[115]),"+f"(d[116]),"+f"(d[117]),"+f"(d[118]),"+f"(d[119]),"+f"(d[120]),"+f"(d[121]),"+f"(d[122]),"+f"(d[123]),"+f"(d[124]),"+f"(d[125]),"+f"(d[126]),"+f"(d[127])
    : "l"(da), "l"(db), "r"(sc));
}
__device__ __forceinline__ void wgmma_ss_n192_a0b1(float (&d)[96], uint64_t da, uint64_t db, int sc) {
  asm volatile("{.reg .pred p; setp.ne.b32 p, %98, 0; wgmma.mma_async.sync.aligned.m64n192k16.f32.bf16.bf16 {%0,%1,%2,%3,%4,%5,%6,%7,%8,%9,%10,%11,%12,%13,%14,%15,%16,%17,%18,%19,%20,%21,%22,%23,%24,%25,%26,%27,%28,%29,%30,%31,%32,%33,%34,%35,%36,%37,%38,%39,%40,%41,%42,%43,%44,%45,%46,%47,%48,%49,%50,%51,%52,%53,%54,%55,%56,%57,%58,%59,%60,%61,%62,%63,%64,%65,%66,%67,%68,%69,%70,%71,%72,%73,%74,%75,%76,%77,%78,%79,%80,%81,%82,%83,%84,%85,%86,%87,%88,%89,%90,%91,%92,%93,%94,%95}, %96, %97, p, 1, 1, 0, 1;}"
    : "+f"(d[0]),"+f"(d[1]),"+f"(d[2]),"+f"(d[3]),"+f"(d[4]),"+f"(d[5]),"+f"(d[6]),"+f"(d[7]),"+f"(d[8]),"+f"(d[9]),"+f"(d[10]),"+f"(d[11]),"+f"(d[12]),"+f"(d[13]),"+f"(d[14]),"+f"(d[15]),"+f"(d[16]),"+f"(d[17]),"+f"(d[18]),"+f"(d[19]),"+f"(d[20]),"+f"(d[21]),"+f"(d[22]),"+f"(d[23]),"+f"(d[24]),"+f"(d[25]),"+f"(d[26]),"+f"(d[27]),"+f"(d[28]),"+f"(d[29]),"+f"(d[30]),"+f"(d[31]),"+f"(d[32]),"+f"(d[33]),"+f"(d[34]),"+f"(d[35]),"+f"(d[36]),"+f"(d[37]),"+f"(d[38]),"+f"(d[39]),"+f"(d[40]),"+f"(d[41]),"+f"(d[42]),"+f"(d[43]),"+f"(d[44]),"+f"(d[45]),"+f"(d[46]),"+f"(d[47]),"+f"(d[48]),"+f"(d[49]),"+f"(d[50]),"+f"(d[51]),"+f"(d[52]),"+f"(d[53]),"+f"(d[54]),"+f"(d[55]),"+f"(d[56]),"+f"(d[57]),"+f"(d[58]),"+f"(d[59]),"+f"(d[60]),"+f"(d[61]),"+f"(d[62]),"+f"(d[63]),"+f"(d[64]),"+f"(d[65]),"+f"(d[66]),"+f"(d[67]),"+f"(d[68]),"+f"(d[69]),"+f"(d[70]),"+f"(d[71]),"+f"(d[72]),"+f"(d[73]),"+f"(d[74]),"+f"(d[75]),"+f"(d[76]),"+f"(d[77]),"+f"(d[78]),"+f"(d[79]),"+f"(d[80]),"+f"(d[81]),"+f"(d[82]),"+f"(d[83]),"+f"(d[84]),"+f"(d[85]),"+f"(d[86]),"+f"(d[87]),"+f"(d[88]),"+f"(d[89]),"+f"(d[90]),"+f"(d[91]),"+f"(d[92]),"+f"(d[93]),"+f"(d[94]),"+f"(d[95])
    : "l"(da), "l"(db), "r"(sc));
}
__device__ __forceinline__ void wgmma_ss_n32_a0b1(float (&d)[16], uint64_t da, uint64_t db, int sc) {
  asm volatile("{.reg .pred p; setp.ne.b32 p, %18, 0; wgmma.mma_async.sync.aligned.m64n32k16.f32.bf16.bf16 {%0,%1,%2,%3,%4,%5,%6,%7,%8,%9,%10,%11,%12,%13,%14,%15}, %16, %17, p, 1, 1, 0, 1;}"
    : "+f"(d[0]),"+f"(d[1]),"+f"(d[2]),"+f"(d[3]),"+f"(d[4]),"+f"(d[5]),"+f"(d[6]),"+f"(d[7]),"+f"(d[8]),"+f"(d[9]),"+f"(d[10]),"+f"(d[11]),"+f"(d[12]),"+f"(d[13]),"+f"(d[14]),"+f"(d[15])
    : "l"(da), "l"(db), "r"(sc));
}
__device__ __forceinline__ void wgmma_rs_n64_b0(float (&d)[32], uint32_t a0, uint32_t a1, uint32_t a2, uint32_t a3, uint64_t db, int sc) {
  asm volatile("{.reg .pred p; setp.ne.b32 p, %37, 0; wgmma.mma_async.sync.aligned.m64n64k16.f32.bf16.bf16 {%0,%1,%2,%3,%4,%5,%6,%7,%8,%9,%10,%11,%12,%13,%14,%15,%16,%17,%18,%19,%20,%21,%22,%23,%24,%25,%26,%27,%28,%29,%30,%31}, {%32,%33,%34,%35}, %36, p, 1, 1, 0;}"
    : "+f"(d[0]),"+f"(d[1]),"+f"(d[2]),"+f"(d[3]),"+f"(d[4]),"+f"(d[5]),"+f"(d[6]),"+f"(d[7]),"+f"(d[8]),"+f"(d[9]),"+f"(d[10]),"+f"(d[11]),"+f"(d[12]),"+f"(d[13]),"+f"(d[14]),"+f"(d[15]),"+f"(d[16]),"+f"(d[17]),"+f"(d[18]),"+f"(d[19]),"+f"(d[20]),"+f"(d[21]),"+f"(d[22]),"+f"(d[23]),"+f"(d[24]),"+f"(d[25]),"+f"(d[26]),"+f"(d[27]),"+f"(d[28]),"+f"(d[29]),"+f"(d[30]),"+f"(d[31])
    : "r"(a0), "r"(a1), "r"(a2), "r"(a3), "l"(db), "r"(sc));
}
__device__ __forceinline__ void wgmma_ss_n128_a0b1(float (&d)[64], uint64_t da, uint64_t db, int sc) {
  asm volatile("{.reg .pred p; setp.ne.b32 p, %66, 0; wgmma.mma_async.sync.aligned.m64n128k16.f32.bf16.bf16 {%0,%1,%2,%3,%4,%5,%6,%7,%8,%9,%10,%11,%12,%13,%14,%15,%16,%17,%18,%19,%20,%21,%22,%23,%24,%25,%26,%27,%28,%29,%30,%31,%32,%33,%34,%35,%36,%37,%38,%39,%40,%41,%42,%43,%44,%45,%46,%47,%48,%49,%50,%51,%52,%53,%54,%55,%56,%57,%58,%59,%60,%61,%62,%63}, %64, %65, p, 1, 1, 0, 1;}"
    : "+f"(d[0]),"+f"(d[1]),"+f"(d[2]),"+f"(d[3]),"+f"(d[4]),"+f"(d[5]),"+f"(d[6]),"+f"(d[7]),"+f"(d[8]),"+f"(d[9]),"+f"(d[10]),"+f"(d[11]),"+f"(d[12]),"+f"(d[13]),"+f"(d[14]),"+f"(d[15]),"+f"(d[16]),"+f"(d[17]),"+f"(d[18]),"+f"(d[19]),"+f"(d[20]),"+f"(d[21]),"+f"(d[22]),"+f"(d[23]),"+f"(d[24]),"+f"(d[25]),"+f"(d[26]),"+f"(d[27]),"+f"(d[28]),"+f"(d[29]),"+f"(d[30]),"+f"(d[31]),"+f"(d[32]),"+f"(d[33]),"+f"(d[34]),"+f"(d[35]),"+f"(d[36]),"+f"(d[37]),"+f"(d[38]),"+f"(d[39]),"+f"(d[40]),"+f"(d[41]),"+f"(d[42]),"+f"(d[43]),"+f"(d[44]),"+f"(d[45]),"+f"(d[46]),"+f"(d[47]),"+f"(d[48]),"+f"(d[49]),"+f"(d[50]),"+f"(d[51]),"+f"(d[52]),"+f"(d[53]),"+f"(d[54]),"+f"(d[55]),"+f"(d[56]),"+f"(d[57]),"+f"(d[58]),"+f"(d[59]),"+f"(d[60]),"+f"(d[61]),"+f"(d[62]),"+f"(d[63])
    : "l"(da), "l"(db), "r"(sc));
}
__device__ __forceinline__ void wgmma_rs_n128_b0(float (&d)[64], uint32_t a0, uint32_t a1, uint32_t a2, uint32_t a3, uint64_t db, int sc) {
  asm volatile("{.reg .pred p; setp.ne.b32 p, %69, 0; wgmma.mma_async.sync.aligned.m64n128k16.f32.bf16.bf16 {%0,%1,%2,%3,%4,%5,%6,%7,%8,%9,%10,%11,%12,%13,%14,%15,%16,%17,%18,%19,%20,%21,%22,%23,%24,%25,%26,%27,%28,%29,%30,%31,%32,%33,%34,%35,%36,%37,%38,%39,%40,%41,%42,%43,%44,%45,%46,%47,%48,%49,%50,%51,%52,%53,%54,%55,%56,%57,%58,%59,%60,%61,%62,%63}, {%64,%65,%66,%67}, %68, p, 1, 1, 0;}"
    : "+f"(d[0]),"+f"(d[1]),"+f"(d[2]),"+f"(d[3]),"+f"(d[4]),"+f"(d[5]),"+f"(d[6]),"+f"(d[7]),"+f"(d[8]),"+f"(d[9]),"+f"(d[10]),"+f"(d[11]),"+f"(d[12]),"+f"(d[13]),"+f"(d[14]),"+f"(d[15]),"+f"(d[16]),"+f"(d[17]),"+f"(d[18]),"+f"(d[19]),"+f"(d[20]),"+f"(d[21]),"+f"(d[22]),"+f"(d[23]),"+f"(d[24]),"+f"(d[25]),"+f"(d[26]),"+f"(d[27]),"+f"(d[28]),"+f"(d[29]),"+f"(d[30]),"+f"(d[31]),"+f"(d[32]),"+f"(d[33]),"+f"(d[34]),"+f"(d[35]),"+f"(d[36]),"+f"(d[37]),"+f"(d[38]),"+f"(d[39]),"+f"(d[40]),"+f"(d[41]),"+f"(d[42]),"+f"(d[43]),"+f"(d[44]),"+f"(d[45]),"+f"(d[46]),"+f"(d[47]),"+f"(d[48]),"+f"(d[49]),"+f"(d[50]),"+f"(d[51]),"+f"(d[52]),"+f"(d[53]),"+f"(d[54]),"+f"(d[55]),"+f"(d[56]),"+f"(d[57]),"+f"(d[58]),"+f"(d[59]),"+f"(d[60]),"+f"(d[61]),"+f"(d[62]),"+f"(d[63])
    : "r"(a0), "r"(a1), "r"(a2), "r"(a3), "l"(db), "r"(sc));
}
__device__ __forceinline__ void wgmma_rs_n128_b1(float (&d)[64], uint32_t a0, uint32_t a1, uint32_t a2, uint32_t a3, uint64_t db, int sc) {
  asm volatile("{.reg .pred p; setp.ne.b32 p, %69, 0; wgmma.mma_async.sync.aligned.m64n128k16.f32.bf16.bf16 {%0,%1,%2,%3,%4,%5,%6,%7,%8,%9,%10,%11,%12,%13,%14,%15,%16,%17,%18,%19,%20,%21,%22,%23,%24,%25,%26,%27,%28,%29,%30,%31,%32,%33,%34,%35,%36,%37,%38,%39,%40,%41,%42,%43,%44,%45,%46,%47,%48,%49,%50,%51,%52,%53,%54,%55,%56,%57,%58,%59,%60,%61,%62,%63}, {%64,%65,%66,%67}, %68, p, 1, 1, 1;}"
    : "+f"(d[0]),"+f"(d[1]),"+f"(d[2]),"+f"(d[3]),"+f"(d[4]),"+f"(d[5]),"+f"(d[6]),"+f"(d[7]),"+f"(d[8]),"+f"(d[9]),"+f"(d[10]),"+f"(d[11]),"+f"(d[12]),"+f"(d[13]),"+f"(d[14]),"+f"(d[15]),"+f"(d[16]),"+f"(d[17]),"+f"(d[18]),"+f"(d[19]),"+f"(d[20]),"+f"(d[21]),"+f"(d[22]),"+f"(d[23]),"+f"(d[24]),"+f"(d[25]),"+f"(d[26]),"+f"(d[27]),"+f"(d[28]),"+f"(d[29]),"+f"(d[30]),"+f"(d[31]),"+f"(d[32]),"+f"(d[33]),"+f"(d[34]),"+f"(d[35]),"+f"(d[36]),"+f"(d[37]),"+f"(d[38]),"+f"(d[39]),"+f"(d[40]),"+f"(d[41]),"+f"(d[42]),"+f"(d[43]),"+f"(d[44]),"+f"(d[45]),"+f"(d[46]),"+f"(d[47]),"+f"(d[48]),"+f"(d[49]),"+f"(d[50]),"+f"(d[51]),"+f"(d[52]),"+f"(d[53]),"+f"(d[54]),"+f"(d[55]),"+f"(d[56]),"+f"(d[57]),"+f"(d[58]),"+f"(d[59]),"+f"(d[60]),"+f"(d[61]),"+f"(d[62]),"+f"(d[63])
    : "r"(a0), "r"(a1), "r"(a2), "r"(a3), "l"(db), "r"(sc));
}
__device__ __forceinline__ void wgmma_rs_n32_b0(float (&d)[16], uint32_t a0, uint32_t a1, uint32_t a2, uint32_t a3, uint64_t db, int sc) {
  asm volatile("{.reg .pred p; setp.ne.b32 p, %21, 0; wgmma.mma_async.sync.aligned.m64n32k16.f32.bf16.bf16 {%0,%1,%2,%3,%4,%5,%6,%7,%8,%9,%10,%11,%12,%13,%14,%15}, {%16,%17,%18,%19}, %20, p, 1, 1, 0;}"
    : "+f"(d[0]),"+f"(d[1]),"+f"(d[2]),"+f"(d[3]),"+f"(d[4]),"+f"(d[5]),"+f"(d[6]),"+f"(d[7]),"+f"(d[8]),"+f"(d[9]),"+f"(d[10]),"+f"(d[11]),"+f"(d[12]),"+f"(d[13]),"+f"(d[14]),"+f"(d[15])
    : "r"(a0), "r"(a1), "r"(a2), "r"(a3), "l"(db), "r"(sc));
}
__device__ __forceinline__ void wgmma_ss_n32_a1b0(float (&d)[16], uint64_t da, uint64_t db, int sc) {
  asm volatile("{.reg .pred p; setp.ne.b32 p, %18, 0; wgmma.mma_async.sync.aligned.m64n32k16.f32.bf16.bf16 {%0,%1,%2,%3,%4,%5,%6,%7,%8,%9,%10,%11,%12,%13,%14,%15}, %16, %17, p, 1, 1, 1, 0;}"
    : "+f"(d[0]),"+f"(d[1]),"+f"(d[2]),"+f"(d[3]),"+f"(d[4]),"+f"(d[5]),"+f"(d[6]),"+f"(d[7]),"+f"(d[8]),"+f"(d[9]),"+f"(d[10]),"+f"(d[11]),"+f"(d[12]),"+f"(d[13]),"+f"(d[14]),"+f"(d[15])
    : "l"(da), "l"(db), "r"(sc));
}
__device__ __forceinline__ void wgmma_ss_n40_a1b0(float (&d)[20], uint64_t da, uint64_t db, int sc) {
  asm volatile("{.reg .pred p; setp.ne.b32 p, %22, 0; wgmma.mma_async.sync.aligned.m64n40k16.f32.bf16.bf16 {%0,%1,%2,%3,%4,%5,%6,%7,%8,%9,%10,%11,%12,%13,%14,%15,%16,%17,%18,%19}, %20, %21, p, 1, 1, 1, 0;}"
    : "+f"(d[0]),"+f"(d[1]),"+f"(d[2]),"+f"(d[3]),"+f"(d[4]),"+f"(d[5]),"+f"(d[6]),"+f"(d[7]),"+f"(d[8]),"+f"(d[9]),"+f"(d[10]),"+f"(d[11]),"+f"(d[12]),"+f"(d[13]),"+f"(d[14]),"+f"(d[15]),"+f"(d[16]),"+f"(d[17]),"+f"(d[18]),"+f"(d[19])
    : "l"(da), "l"(db), "r"(sc));
}
__device__ __forceinline__ void wgmma_ss_n40_a1b1(float (&d)[20], uint64_t da, uint64_t db, int sc) {
  asm volatile("{.reg .pred p; setp.ne.b32 p, %22, 0; wgmma.mma_async.sync.aligned.m64n40k16.f32.bf16.bf16 {%0,%1,%2,%3,%4,%5,%6,%7,%8,%9,%10,%11,%12,%13,%14,%15,%16,%17,%18,%19}, %20, %21, p, 1, 1, 1, 1;}"
    : "+f"(d[0]),"+f"(d[1]),"+f"(d[2]),"+f"(d[3]),"+f"(d[4]),"+f"(d[5]),"+f"(d[6]),"+f"(d[7]),"+f"(d[8]),"+f"(d[9]),"+f"(d[10]),"+f"(d[11]),"+f"(d[12]),"+f"(d[13]),"+f"(d[14]),"+f"(d[15]),"+f"(d[16]),"+f"(d[17]),"+f"(d[18]),"+f"(d[19])
    : "l"(da), "l"(db), "r"(sc));
}
__device__ __forceinline__ void wgmma_rs_n40_b0(float (&d)[20], uint32_t a0, uint32_t a1, uint32_t a2, uint32_t a3, uint64_t db, int sc) {
  asm volatile("{.reg .pred p; setp.ne.b32 p, %25, 0; wgmma.mma_async.sync.aligned.m64n40k16.f32.bf16.bf16 {%0,%1,%2,%3,%4,%5,%6,%7,%8,%9,%10,%11,%12,%13,%14,%15,%16,%17,%18,%19}, {%20,%21,%22,%23}, %24, p, 1, 1, 0;}"
    : "+f"(d[0]),"+f"(d[1]),"+f"(d[2]),"+f"(d[3]),"+f"(d[4]),"+f"(d[5]),"+f"(d[6]),"+f"(d[7]),"+f"(d[8]),"+f"(d[9]),"+f"(d[10]),"+f"(d[11]),"+f"(d[12]),"+f"(d[13]),"+f"(d[14]),"+f"(d[15]),"+f"(d[16]),"+f"(d[17]),"+f"(d[18]),"+f"(d[19])
    : "r"(a0), "r"(a1), "r"(a2), "r"(a3), "l"(db), "r"(sc));
}
__device__ __forceinline__ void wgmma_ssz_n256_a0b1(float (&d)[128], uint64_t da, uint64_t db) {
  asm volatile("{.reg .pred p; setp.ne.b32 p, 0, 0; wgmma.mma_async.sync.aligned.m64n256k16.f32.bf16.bf16 {%0,%1,%2,%3,%4,%5,%6,%7,%8,%9,%10,%11,%12,%13,%14,%15,%16,%17,%18,%19,%20,%21,%22,%23,%24,%25,%26,%27,%28,%29,%30,%31,%32,%33,%34,%35,%36,%37,%38,%39,%40,%41,%42,%43,%44,%45,%46,%47,%48,%49,%50,%51,%52,%53,%54,%55,%56,%57,%58,%59,%60,%61,%62,%63,%64,%65,%66,%67,%68,%69,%70,%71,%72,%73,%74,%75,%76,%77,%78,%79,%80,%81,%82,%83,%84,%85,%86,%87,%88,%89,%90,%91,%92,%93,%94,%95,%96,%97,%98,%99,%100,%101,%102,%103,%104,%105,%106,%107,%108,%109,%110,%111,%112,%113,%114,%115,%116,%117,%118,%119,%120,%121,%122,%123,%124,%125,%126,%127}, %128, %129, p, 1, 1, 0, 1;}"
    : "=f"(d[0]),"=f"(d[1]),"=f"(d[2]),"=f"(d[3]),"=f"(d[4]),"=f"(d[5]),"=f"(d[6]),"=f"(d[7]),"=f"(d[8]),"=f"(d[9]),"=f"(d[10]),"=f"(d[11]),"=f"(d[12]),"=f"(d[13]),"=f"(d[14]),"=f"(d[15]),"=f"(d[16]),"=f"(d[17]),"=f"(d[18]),"=f"(d[19]),"=f"(d[20]),"=f"(d[21]),"=f"(d[22]),"=f"(d[23]),"=f"(d[24]),"=f"(d[25]),"=f"(d[26]),"=f"(d[27]),"=f"(d[28]),"=f"(d[29]),"=f"(d[30]),"=f"(d[31]),"=f"(d[32]),"=f"(d[33]),"=f"(d[34]),"=f"(d[35]),"=f"(d[36]),"=f"(d[37]),"=f"(d[38]),"=f"(d[39]),"=f"(d[40]),"=f"(d[41]),"=f"(d[42]),"=f"(d[43]),"=f"(d[44]),"=f"(d[45]),"=f"(d[46]),"=f"(d[47]),"=f"(d[48]),"=f"(d[49]),"=f"(d[50]),"=f"(d[51]),"=f"(d[52]),"=f"(d[53]),"=f"(d[54]),"=f"(d[55]),"=f"(d[56]),"=f"(d[57]),"=f"(d[58]),"=f"(d[59]),"=f"(d[60]),"=f"(d[61]),"=f"(d[62]),"=f"(d[63]),"=f"(d[64]),"=f"(d[65]),"=f"(d[66]),"=f"(d[67]),"=f"(d[68]),"=f"(d[69]),"=f"(d[70]),"=f"(d[71]),"=f"(d[72]),"=f"(d[73]),"=f"(d[74]),"=f"(d[75]),"=f"(d[76]),"=f"(d[77]),"=f"(d[78]),"=f"(d[79]),"=f"(d[80]),"=f"(d[81]),"=f"(d[82]),"=f"(d[83]),"=f"(d[84]),"=f"(d[85]),"=f"(d[86]),"=f"(d[87]),"=f"(d[88]),"=f"(d[89]),"=f"(d[90]),"=f"(d[91]),"=f"(d[92]),"=f"(d[93]),"=f"(d[94]),"=f"(d[95]),"=f"(d[96]),"=f"(d[97]),"=f"(d[98]),"=f"(d[99]),"=f"(d[100]),"=f"(d[101]),"=f"(d[102]),"=f"(d[103]),"=f"(d[104]),"=f"(d[105]),"=f"(d[106]),"=f"(d[107]),"=f"(d[108]),"=f"(d[109]),"=f"(d[110]),"=f"(d[111]),"=f"(d[112]),"=f"(d[113]),"=f"(d[114]),"=f"(d[115]),"=f"(d[116]),"=f"(d[117]),"=f"(d[118]),"=f"(d[119]),"=f"(d[120]),"=f"(d[121]),"=f"(d[122]),"=f"(d[123]),"=f"(d[124]),"=f"(d[125]),"=f"(d[126]),"=f"(d[127])
    : "l"(da), "l"(db));
}
__device__ __forceinline__ void wgmma_ssz_n128_a0b1(float (&d)[64], uint64_t da, uint64_t db) {
  asm volatile("{.reg .pred p; setp.ne.b32 p, 0, 0; wgmma.mma_async.sync.aligned.m64n128k16.f32.bf16.bf16 {%0,%1,%2,%3,%4,%5,%6,%7,%8,%9,%10,%11,%12,%13,%14,%15,%16,%17,%18,%19,%20,%21,%22,%23,%24,%25,%26,%27,%28,%29,%30,%31,%32,%33,%34,%35,%36,%37,%38,%39,%40,%41,%42,%43,%44,%45,%46,%47,%48,%49,%50,%51,%52,%53,%54,%55,%56,%57,%58,%59,%60,%61,%62,%63}, %64, %65, p, 1, 1, 0, 1;}"
    : "=f"(d[0]),"=f"(d[1]),"=f"(d[2]),"=f"(d[3]),"=f"(d[4]),"=f"(d[5]),"=f"(d[6]),"=f"(d[7]),"=f"(d[8]),"=f"(d[9]),"=f"(d[10]),"=f"(d[11]),"=f"(d[12]),"=f"(d[13]),"=f"(d[14]),"=f"(d[15]),"=f"(d[16]),"=f"(d[17]),"=f"(d[18]),"=f"(d[19]),"=f"(d[20]),"=f"(d[21]),"=f"(d[22]),"=f"(d[23]),"=f"(d[24]),"=f"(d[25]),"=f"(d[26]),"=f"(d[27]),"=f"(d[28]),"=f"(d[29]),"=f"(d[30]),"=f"(d[31]),"=f"(d[32]),"=f"(d[33]),"=f"(d[34]),"=f"(d[35]),"=f"(d[36]),"=f"(d[37]),"=f"(d[38]),"=f"(d[39]),"=f"(d[40]),"=f"(d[41]),"=f"(d[42]),"=f"(d[43]),"=f"(d[44]),"=f"(d[45]),"=f"(d[46]),"=f"(d[47]),"=f"(d[48]),"=f"(d[49]),"=f"(d[50]),"=f"(d[51]),"=f"(d[52]),"=f"(d[53]),"=f"(d[54]),"=f"(d[55]),"=f"(d[56]),"=f"(d[57]),"=f"(d[58]),"=f"(d[59]),"=f"(d[60]),"=f"(d[61]),"=f"(d[62]),"=f"(d[63])
    : "l"(da), "l"(db));
}


__device__ __forceinline__ void wg_fence() { asm volatile("wgmma.fence.sync.aligned;" ::: "memory"); }
__device__ __forceinline__ void wg_commit() { asm volatile("wgmma.commit_group.sync.aligned;" ::: "memory"); }
template <int N> __device__ __forceinline__ void wg_wait() { asm volatile("wgmma.wait_group.sync.aligned %0;" ::"n"(N) : "memory"); }
template <int N> __device__ __forceinline__ void fence_regs(float (&d)[N]) {
#pragma unroll
  for (int i = 0; i < N; i++) asm volatile("" : "+f"(d[i])::"memory");
}
template <int N> __device__ __forceinline__ void fence_regs(uint32_t (&d)[N]) {
#pragma unroll
  for (int i = 0; i < N; i++) asm volatile("" : "+r"(d[i])::"memory");
}
__device__ __forceinline__ uint64_t mk_desc(uint32_t lo, uint32_t hi) {
  uint64_t d;
  asm("mov.b64 %0, {%1,%2};" : "=l"(d) : "r"(lo), "r"(hi));
  return d;
}
constexpr uint32_t DHI_SW128 = (1024u >> 4) | (1u << 30);
__device__ __forceinline__ uint32_t desc_lo(uint32_t addr, uint32_t lbo) { return ((addr & 0x3FFFF) >> 4) | ((lbo >> 4) << 16); }

__device__ __forceinline__ void mbar_init(uint32_t bar, uint32_t cnt) { asm volatile("mbarrier.init.shared::cta.b64 [%0], %1;" ::"r"(bar), "r"(cnt) : "memory"); }
__device__ __forceinline__ uint32_t mbar_try(uint32_t bar, uint32_t par) {
  uint32_t ok;
  asm volatile("{.reg .pred p; mbarrier.try_wait.parity.shared::cta.b64 p, [%1], %2; selp.u32 %0, 1, 0, p;}" : "=r"(ok) : "r"(bar), "r"(par) : "memory");
  return ok;
}
__device__ __noinline__ void mbar_wait_slow(uint32_t bar, uint32_t par) {
  for (int i = 0; i < (1 << 22); i++)
    if (mbar_try(bar, par)) return;
  __trap();
}
__device__ __forceinline__ void mbar_wait(uint32_t bar, uint32_t par) {
  asm volatile(
      "{\n.reg .pred p;\n.reg .u32 c;\n"
      "mbarrier.try_wait.parity.shared::cta.b64 p, [%0], %1;\n"
      "@p bra DONE;\n"
      "mov.u32 c, 0;\n"
      "LOOP:\n"
      "mbarrier.try_wait.parity.shared::cta.b64 p, [%0], %1;\n"
      "@p bra DONE;\n"
      "add.u32 c, c, 1;\n"
      "setp.lt.u32 p, c, 4000000;\n"
      "@p bra LOOP;\n"
      "trap;\n"
      "DONE:\n}" ::"r"(bar), "r"(par) : "memory");
}
__device__ __forceinline__ void mbar_wait2(uint32_t b0, uint32_t p0, uint32_t b1, uint32_t p1) {
  asm volatile(
      "{\n.reg .pred p, q;\n.reg .u32 c;\n"
      "mov.u32 c, 0;\n"
      "LOOP:\n"
      "mbarrier.try_wait.parity.shared::cta.b64 p, [%0], %1;\n"
      "mbarrier.try_wait.parity.shared::cta.b64 q, [%2], %3;\n"
      "and.pred p, p, q;\n"
      "@p bra DONE;\n"
      "add.u32 c, c, 1;\n"
      "setp.lt.u32 p, c, 4000000;\n"
      "@p bra LOOP;\n"
      "trap;\n"
      "DONE:\n}" ::"r"(b0), "r"(p0), "r"(b1), "r"(p1) : "memory");
}
__device__ __forceinline__ void mbar_wait_cl(uint32_t bar, uint32_t par) {
  asm volatile(
      "{\n.reg .pred p;\n.reg .u32 c;\n"
      "mbarrier.try_wait.parity.acquire.cluster.shared::cta.b64 p, [%0], %1;\n"
      "@p bra DONE;\n"
      "mov.u32 c, 0;\n"
      "LOOP:\n"
      "mbarrier.try_wait.parity.acquire.cluster.shared::cta.b64 p, [%0], %1;\n"
      "@p bra DONE;\n"
      "add.u32 c, c, 1;\n"
      "setp.lt.u32 p, c, 4000000;\n"
      "@p bra LOOP;\n"
      "trap;\n"
      "DONE:\n}" ::"r"(bar), "r"(par) : "memory");
}
__device__ __forceinline__ void mbar_arrive(uint32_t bar) { asm volatile("mbarrier.arrive.shared::cta.b64 _, [%0];" ::"r"(bar) : "memory"); }
__device__ __forceinline__ void mbar_arrive_cl(uint32_t bar) { asm volatile("mbarrier.arrive.shared::cluster.b64 _, [%0];" ::"r"(bar) : "memory"); }
__device__ __forceinline__ void mbar_expect(uint32_t bar, uint32_t bytes) { asm volatile("mbarrier.arrive.expect_tx.shared::cta.b64 _, [%0], %1;" ::"r"(bar), "r"(bytes) : "memory"); }
__device__ __forceinline__ void mbar_expect_cl(uint32_t bar, uint32_t bytes) { asm volatile("mbarrier.arrive.expect_tx.shared::cluster.b64 _, [%0], %1;" ::"r"(bar), "r"(bytes) : "memory"); }
__device__ __forceinline__ uint32_t mapa(uint32_t addr, uint32_t rank) {
  uint32_t r;
  asm("mapa.shared::cluster.u32 %0, %1, %2;" : "=r"(r) : "r"(addr), "r"(rank));
  return r;
}
__device__ __forceinline__ void st_async32(uint32_t addr, uint32_t v, uint32_t bar) {
  asm volatile("st.async.shared::cluster.mbarrier::complete_tx::bytes.b32 [%0], %1, [%2];" ::"r"(addr), "r"(v), "r"(bar) : "memory");
}
__device__ __forceinline__ void st_async64(uint32_t addr, uint32_t a, uint32_t b, uint32_t bar) {
  asm volatile("st.async.shared::cluster.mbarrier::complete_tx::bytes.v2.b32 [%0], {%1,%2}, [%3];" ::"r"(addr), "r"(a), "r"(b), "r"(bar) : "memory");
}
__device__ __forceinline__ void st_async128(uint32_t addr, uint32_t a, uint32_t b, uint32_t c, uint32_t d, uint32_t bar) {
  asm volatile("st.async.shared::cluster.mbarrier::complete_tx::bytes.v4.b32 [%0], {%1,%2,%3,%4}, [%5];" ::"r"(addr), "r"(a), "r"(b), "r"(c), "r"(d), "r"(bar) : "memory");
}
__device__ __forceinline__ void bar_sync(int id, int n) { asm volatile("bar.sync %0, %1;" ::"r"(id), "r"(n) : "memory"); }
__device__ __forceinline__ void bar_arrive(int id, int n) { asm volatile("bar.arrive %0, %1;" ::"r"(id), "r"(n) : "memory"); }
__device__ __forceinline__ void cluster_sync() { asm volatile("barrier.cluster.arrive.aligned;\nbarrier.cluster.wait.aligned;" ::: "memory"); }
__device__ __forceinline__ bool elect() {
  uint32_t p;
  asm volatile("{.reg .pred q; elect.sync _|q, 0xffffffff; selp.u32 %0, 1, 0, q;}" : "=r"(p));
  return p != 0;
}
__device__ __forceinline__ void fence_async_smem() { asm volatile("fence.proxy.async.shared::cta;" ::: "memory"); }
__device__ __forceinline__ void fence_async_all() { asm volatile("fence.proxy.async;" ::: "memory"); }
__device__ __forceinline__ void tma2d(uint32_t dst, const CUtensorMap* m, int c0, int c1, uint32_t bar) {
  asm volatile("cp.async.bulk.tensor.2d.shared::cluster.global.mbarrier::complete_tx::bytes [%0], [%1, {%2,%3}], [%4];" ::"r"(dst), "l"(m), "r"(c0), "r"(c1), "r"(bar) : "memory");
}
__device__ __forceinline__ void tma2d_mc(uint32_t dst, const CUtensorMap* m, int c0, int c1, uint32_t bar, uint16_t mask) {
  asm volatile("cp.async.bulk.tensor.2d.shared::cluster.global.mbarrier::complete_tx::bytes.multicast::cluster [%0], [%1, {%2,%3}], [%4], %5;" ::"r"(dst), "l"(m), "r"(c0), "r"(c1), "r"(bar), "h"(mask) : "memory");
}
__device__ __forceinline__ void tma3d(uint32_t dst, const CUtensorMap* m, int c0, int c1, int c2, uint32_t bar) {
  asm volatile("cp.async.bulk.tensor.3d.shared::cluster.global.mbarrier::complete_tx::bytes [%0], [%1, {%2,%3,%4}], [%5];" ::"r"(dst), "l"(m), "r"(c0), "r"(c1), "r"(c2), "r"(bar) : "memory");
}
__device__ __forceinline__ void tma3d_mc(uint32_t dst, const CUtensorMap* m, int c0, int c1, int c2, uint32_t bar, uint16_t mask) {
  asm volatile("cp.async.bulk.tensor.3d.shared::cluster.global.mbarrier::complete_tx::bytes.multicast::cluster [%0], [%1, {%2,%3,%4}], [%5], %6;" ::"r"(dst), "l"(m), "r"(c0), "r"(c1), "r"(c2), "r"(bar), "h"(mask) : "memory");
}
__device__ __forceinline__ uint32_t ld_acquire(const unsigned* p) {
  uint32_t v;
  asm volatile("ld.acquire.gpu.global.u32 %0, [%1];" : "=r"(v) : "l"(p) : "memory");
  return v;
}
__device__ __forceinline__ uint32_t pack_bf16(float lo, float hi) {
  uint32_t r;
  asm("cvt.rn.bf16x2.f32 %0, %1, %2;" : "=r"(r) : "f"(hi), "f"(lo));
  return r;
}
__device__ __forceinline__ float ex2(float x) {
  float y;
  asm("ex2.approx.ftz.f32 %0, %1;" : "=f"(y) : "f"(x));
  return y;
}
__device__ __forceinline__ float rcp(float x) {
  float y;
  asm("rcp.approx.ftz.f32 %0, %1;" : "=f"(y) : "f"(x));
  return y;
}
__device__ __forceinline__ void stg128(void* p, uint32_t a, uint32_t b, uint32_t c, uint32_t d) {
  asm volatile("st.global.v4.b32 [%0], {%1,%2,%3,%4};" ::"l"(p), "r"(a), "r"(b), "r"(c), "r"(d) : "memory");
}
__device__ __forceinline__ void sts128(uint32_t a, uint32_t x, uint32_t y, uint32_t z, uint32_t w) {
  asm volatile("st.shared.v4.b32 [%0], {%1,%2,%3,%4};" ::"r"(a), "r"(x), "r"(y), "r"(z), "r"(w) : "memory");
}
__device__ __forceinline__ void stsm4(uint32_t a, uint32_t r0, uint32_t r1, uint32_t r2, uint32_t r3) {
  asm volatile("stmatrix.sync.aligned.m8n8.x4.shared.b16 [%0], {%1,%2,%3,%4};" ::"r"(a), "r"(r0), "r"(r1), "r"(r2), "r"(r3) : "memory");
}
__device__ __forceinline__ void arrive_elect(uint32_t bar) {
  asm volatile("{.reg .pred q; elect.sync _|q, 0xffffffff; @q mbarrier.arrive.shared::cta.b64 _, [%0];}" ::"r"(bar) : "memory");
}
__device__ __forceinline__ void sched_fence(uint32_t v) { asm volatile("{.reg .pred p; setp.eq.u32 p, %0, 0; @p trap;}" ::"r"(v) : "memory"); }
template <int V> struct IC { static constexpr int value = V; };
template <int A, int B, class F> __device__ __forceinline__ void static_for(F&& f) {
  if constexpr (A < B) {
    f(IC<A>());
    static_for<A + 1, B>(f);
  }
}
__device__ __forceinline__ uint32_t lds32(uint32_t a) {
  uint32_t v;
  asm volatile("ld.shared.b32 %0, [%1];" : "=r"(v) : "r"(a) : "memory");
  return v;
}

constexpr int MAXTASK = 256 + 256 + 200;
constexpr int T_KV = 0, T_FA = 1, T_OA = 2, T_OB = 3, T_XA = 4, T_XB = 5;
constexpr uint32_t TASK_END = 0xFFFF, T_NOP = 6;
#ifndef NLATE
#define NLATE 0
#endif
constexpr int NEARLY = 34, NCL = NEARLY + NLATE;
struct MainParams {
  CUtensorMap ckv, wuk, wuv, ax, wq, scr, woa, wob, scr_st, out_st, woa1, wob1, scr64;
  uint32_t ntask;
  uint16_t tasks[MAXTASK];
};

constexpr int M_GR = 16384, M_NG = 12;
constexpr int M_STG = M_GR * M_NG;
constexpr int M_BAR = M_STG + 32768;
constexpr int M_FULL = M_BAR, M_EMPTY = M_BAR + 64, M_TFULL = M_BAR + 128, M_TEMPTY = M_BAR + 160, M_EPI = M_BAR + 192, M_SFREE = M_BAR + 224, M_GO = M_BAR + 240,
              M_XR = M_BAR + 248, M_TSLOT = M_BAR + 256;
constexpr int M_SMEM = M_BAR + 512 + 1024;
constexpr int OX_TARGET = 64;

#ifndef PF_ON
#define PF_ON 0
#endif
#ifndef ST_ROWS
#define ST_ROWS 16
#endif
#ifndef ST_DEPTH
#define ST_DEPTH 1
#endif
#ifndef KV_SKEW
#define KV_SKEW 7
#endif
#ifndef FM_NJ
#define FM_NJ 2
#endif
#ifndef Q_SKEW
#define Q_SKEW 6
#endif
struct Ring {
  uint32_t e, g;
  __device__ __forceinline__ uint32_t take(int z) {
    if (g + z > M_NG) g = 0;
    const uint32_t r = g;
    g += z;
    return r;
  }
  __device__ __forceinline__ uint32_t bar() const { return (e & 7) * 8; }
  __device__ __forceinline__ uint32_t par() const { return (e >> 3) & 1; }
};
__device__ __forceinline__ int task_entries(int type, int p) { return type == T_NOP ? 0 : type == T_KV ? 9 : type == T_FA ? 9 + 2 * (2 * p + 2) : type >= T_XA ? 17 : 65; }
__device__ __forceinline__ int entry_size(int type, int it) { return type == T_FA || (type == T_KV && it == 8) || type >= T_XA ? 2 : 3; }

__device__ __forceinline__ void need_flag(uint32_t& v, int bit, const unsigned* flag, unsigned target) {
  for (int it = 0; !((__ballot_sync(0xffffffffu, v >= target) >> bit) & 1); it++) {
    if (it > (1 << 21)) __trap();
    if (it) __nanosleep(40);
    v = ld_acquire(flag);
  }
}

constexpr float SM_C = 0.08838834764831845f * 1.4426950408889634f;
template <int NJ> __device__ __forceinline__ void softmax_max(const float (&s)[64], float& m0, float& m1, float& a0, float& a1, float& c0, float& c1) {
  float x0 = fmaxf(s[0], s[4]), y0 = fmaxf(s[1], s[5]), x1 = fmaxf(s[2], s[6]), y1 = fmaxf(s[3], s[7]);
#pragma unroll
  for (int j = 2; j < NJ; j++) {
    x0 = fmaxf(x0, s[4 * j]);
    y0 = fmaxf(y0, s[4 * j + 1]);
    x1 = fmaxf(x1, s[4 * j + 2]);
    y1 = fmaxf(y1, s[4 * j + 3]);
  }
  x0 = fmaxf(x0, y0);
  x1 = fmaxf(x1, y1);
  x0 = fmaxf(x0, __shfl_xor_sync(0xffffffffu, x0, 1));
  x1 = fmaxf(x1, __shfl_xor_sync(0xffffffffu, x1, 1));
  x0 = fmaxf(x0, __shfl_xor_sync(0xffffffffu, x0, 2));
  x1 = fmaxf(x1, __shfl_xor_sync(0xffffffffu, x1, 2));
  const float n0 = fmaxf(m0, x0), n1 = fmaxf(m1, x1);
  a0 = ex2((m0 - n0) * SM_C);
  a1 = ex2((m1 - n1) * SM_C);
  m0 = n0;
  m1 = n1;
  c0 = -n0 * SM_C;
  c1 = -n1 * SM_C;
}
template <int J0, int J1> __device__ __forceinline__ void softmax_exp(const float (&s)[64], uint32_t (&p)[32], float c0, float c1, float (&t)[4]) {
#pragma unroll
  for (int j = J0; j < J1; j++) {
    const float e0 = ex2(fmaf(s[4 * j], SM_C, c0)), e1 = ex2(fmaf(s[4 * j + 1], SM_C, c0));
    const float e2 = ex2(fmaf(s[4 * j + 2], SM_C, c1)), e3 = ex2(fmaf(s[4 * j + 3], SM_C, c1));
    p[2 * j] = pack_bf16(e0, e1);
    p[2 * j + 1] = pack_bf16(e2, e3);
    if (j == 0) { t[0] = e0; t[1] = e1; t[2] = e2; t[3] = e3; }
    else { t[0] += e0; t[1] += e1; t[2] += e2; t[3] += e3; }
  }
}
template <int I0, int I1> __device__ __forceinline__ void fence_part(uint32_t (&d)[32]) {
#pragma unroll
  for (int i = I0; i < I1; i++) asm volatile("" : "+r"(d[i])::"memory");
}
template <int J0, int J1, int N> __device__ __forceinline__ void stage_tile(const float (&d)[N], uint32_t a, float f0, float f1) {
#pragma unroll
  for (int j = J0; j < J1; j += 2)
    stsm4((a ^ (((j - J0) & 7) << 4)) + ((j - J0) >> 3) * 8192, pack_bf16(d[4 * j] * f0, d[4 * j + 1] * f0), pack_bf16(d[4 * j + 2] * f1, d[4 * j + 3] * f1),
          pack_bf16(d[4 * j + 4] * f0, d[4 * j + 5] * f0), pack_bf16(d[4 * j + 6] * f1, d[4 * j + 7] * f1));
}
template <int J0, int J1> __device__ __forceinline__ void causal_mask(float (&s)[64], int lim0) {
#pragma unroll
  for (int j = J0; j < J1; j++) {
    if (8 * j > lim0) s[4 * j] = -INFINITY;
    if (8 * j + 1 > lim0) s[4 * j + 1] = -INFINITY;
    if (8 * j > lim0 + 8) s[4 * j + 2] = -INFINITY;
    if (8 * j + 1 > lim0 + 8) s[4 * j + 3] = -INFINITY;
  }
}

__global__ void __cluster_dims__(2, 1, 1) __launch_bounds__(384, 1) main_kernel(const __grid_constant__ MainParams P) {
  extern __shared__ uint8_t smem_raw[];
  const uint32_t sb = ((uint32_t)__cvta_generic_to_shared(smem_raw) + 1023u) & ~1023u;
  const int warp = __shfl_sync(0xffffffffu, threadIdx.x >> 5, 0), lane = threadIdx.x & 31;
  uint32_t rank;
  asm("mov.u32 %0, %%cluster_ctarank;" : "=r"(rank));
  rank = __shfl_sync(0xffffffffu, rank, 0);
#ifdef DEV_TRACE
  if (threadIdx.x == 0) { long long c; asm volatile("mov.u64 %0, %%globaltimer;" : "=l"(c)); g_trace[blockIdx.x * 4096 + 4090] = c; }
#endif
  const uint32_t cluster = blockIdx.x >> 1;
  static_assert(M_EMPTY == M_FULL + 64 && M_TFULL == M_FULL + 128 && M_TEMPTY == M_FULL + 160 && M_EPI == M_FULL + 192 && M_SFREE == M_FULL + 224 && M_XR == M_FULL + 248, "barriers");
  if (warp == 8 && cluster < NEARLY && elect()) {
#pragma unroll 1
    for (int i = 0; i < 4; i++) {
      const uint32_t st = sb + i * 3 * M_GR, fb = sb + M_FULL + 8 * i;
      mbar_init(fb, 1);
      mbar_expect(fb, 49152);
      tma2d(st, &P.ckv, i * 64, (cluster & 7) * 256 + rank * 128, fb);
      tma3d(st + 16384, &P.wuk, 0, i * 64, (cluster >> 3) * 2, fb);
      tma3d(st + 32768, &P.wuv, 0, i * 64, (cluster >> 3) * 2, fb);
    }
    asm volatile("fence.mbarrier_init.release.cluster;" ::: "memory");
  }
  const uint32_t jl = cluster - NEARLY, task0 = cluster < NEARLY ? cluster : jl < NLATE ? T_XB << 12 | (jl % 9) << 8 | (3 - jl / 9) << 3 | 7 : T_NOP << 12;
  if (NLATE > 0 && warp == 8 && cluster >= NEARLY && elect()) {
    const int h = (task0 >> 3) & 31, p = 7;
#pragma unroll 1
    for (int i = 0; i < 8; i++) {
      const uint32_t fb = sb + M_FULL + 8 * i;
      mbar_init(fb, 1);
      if (i < 6) {
        mbar_expect(fb, 32768);
        tma2d(sb + (2 * i + 1) * M_GR, &P.wob1, (task0 >> 8 & 15) * 64, rank * 2048 + i * 128, fb);
      }
    }
    asm volatile("fence.mbarrier_init.release.cluster;" ::: "memory");
    for (int it = 0; ld_acquire(g_sync + SY_OX + 2 * p + max(h - 1, 0)) < OX_TARGET; it++)
      if (it > (1 << 21)) __trap();
#pragma unroll 1
    for (int i = 0; i < 6; i++) tma3d(sb + 2 * i * M_GR, &P.scr64, 0, 3 * SEQ + p * 256 + h * 64, rank * 32 + i * 2, sb + M_FULL + 8 * i);
  }
  if (warp >= 1 + (cluster >= NEARLY) && warp < 8 && elect()) {
    const uint32_t b = sb + M_FULL + 32 * warp, cnt = (warp & 14) == 2 ? 16 : warp == 5 ? 22 : warp == 6 ? 4 : 1;
#pragma unroll
    for (int i = 0; i < 4; i++) mbar_init(b + 8 * i, cnt);
    asm volatile("fence.mbarrier_init.release.cluster;" ::: "memory");
  }
  __syncwarp();
  if (warp == 8) TRM(5);
  asm volatile("barrier.cluster.arrive.relaxed.aligned;" ::: "memory");
  auto started = [&]() { asm volatile("barrier.cluster.wait.aligned;" ::: "memory"); };
  const uint32_t tempty0 = mapa(sb + M_TEMPTY, 0);
  auto read_task = [&](int ti) -> uint32_t {
    if (ti == 0) return task0;
    mbar_wait(sb + M_TFULL + 8 * ((ti - 1) & 3), ((ti - 1) >> 2) & 1);
    return __shfl_sync(0xffffffffu, lds32(sb + M_TSLOT + 4 * ((ti - 1) & 3)), 0);
  };
  auto free_task = [&](int ti) {
    if (ti > 0 && lane == 0) mbar_arrive_cl(tempty0 + 8 * ((ti - 1) & 3));
  };

  if (warp >= 8) {
    asm volatile("setmaxnreg.dec.sync.aligned.u32 40;");
    if (warp == 8) {
      if (lane >= 3 && lane < 13) asm volatile("prefetch.tensormap [%0];" ::"l"(&P.ckv + lane) : "memory");
      __syncwarp();
      started();
      TRM(4);
      Ring r{0, 0};
      uint32_t lin = 0;
      uint32_t mypos = 0, mypar = 2;
      const uint32_t myempty = sb + M_EMPTY + 8 * (lane & 7);
      auto alloc = [&](int z, uint32_t& fb) -> uint32_t {
        if (r.g + z > M_NG) lin += M_NG - r.g;
        const uint32_t st = sb + r.take(z) * M_GR;
        const uint32_t need = mypar < 2 && lin + z - mypos > M_NG;
        for (int it = 0;; it++) {
          uint32_t ok;
          asm volatile("{.reg .pred p, q; setp.eq.u32 q, %3, 0; mov.pred p, q; @!q mbarrier.try_wait.parity.shared::cta.b64 p, [%1], %2; selp.u32 %0, 1, 0, p;}"
                       : "=r"(ok) : "r"(myempty), "r"(mypar), "r"(need) : "memory");
          if (__all_sync(0xffffffffu, ok)) break;
          if (it > 4000000) __trap();
        }
        mypar = need ? 2 : mypar;
        if (lane == (r.e & 7)) { mypos = lin; mypar = r.par(); }
        lin += z;
        fb = sb + M_FULL + r.bar();
        r.e++;
        return st;
      };
      auto go = [&]() { if (rank == 0) arrive_elect(sb + M_GO); };
      for (int ti = 0;; ti++) {
        const uint32_t task = read_task(ti);
        free_task(ti);
        if (task == TASK_END) break;
        const int type = task >> 12, nn = (task >> 8) & 15, h = (task >> 3) & 31, p = task & 7;
        uint32_t fb, fv = 0;
        if (type == T_NOP) {
          go();
        } else if (type == T_KV) {
          const CUtensorMap* w = rank ? &P.wuv : &P.wuk;
          const int row = p * 256 + rank * 128;
#pragma unroll 1
          for (int k = 0; k < 512; k += 64) {
            const uint32_t st = alloc(3, fb);
            if ((ti > 0 || k >= 256 || cluster >= NEARLY) && elect()) {
              mbar_expect(fb, 49152);
              tma2d(st, &P.ckv, k, row, fb);
              tma3d_mc(st + 16384 + rank * 16384, w, 0, k, h * 2, fb, 3);
            }
            if (k == 384) go();
            if (PF_ON && ti == 0 && h < 4 && k == 192 && elect()) {
              asm volatile("cp.async.bulk.prefetch.tensor.3d.L2.global [%0, {0,%1,%2}];" ::"l"(w), "r"(p * 64), "r"((h + 4) * 2) : "memory");
              if (h == 0) asm volatile("cp.async.bulk.prefetch.tensor.3d.L2.global [%0, {0,%1,%2}];" ::"l"(w), "r"(p * 64), "r"(16) : "memory");
            }
            if (PF_ON && ti == 1 && h < 8 && k >= 192 && elect()) {
              const int c = (k - 192) / 32 + rank;
              if (c < 9) asm volatile("cp.async.bulk.prefetch.tensor.2d.L2.global [%0, {%1,%2}];" ::"l"(&P.ax), "r"(c * 64), "r"(p * 256 + (h & 3) * 64) : "memory");
              if (k == 192) asm volatile("cp.async.bulk.prefetch.tensor.2d.L2.global [%0, {%1,%2}];" ::"l"(&P.wq), "r"((h & 3) * 128 + rank * 64), "r"(p * 64) : "memory");
            }
            __syncwarp();
          }
          alloc(2, fb);
          arrive_elect(fb);
        } else if (type == T_FA) {
          const unsigned* flag = g_sync + SY_KV + h * 8 + (lane & 7);
          asm volatile("ld.relaxed.gpu.global.u32 %0, [%1];" : "=r"(fv) : "l"(flag) : "memory");
          const int r0 = p * 256 + rank * 64, r1 = p * 256 + 192 - rank * 64, col = h * 128 + rank * 64;
#pragma unroll 1
          for (int k = 0; k < 576; k += 64) {
            const uint32_t st = alloc(2, fb);
            if (elect()) {
              mbar_expect(fb, 32768);
              tma2d(st, &P.ax, k, r0, fb);
              tma2d(st + 8192, &P.ax, k, r1, fb);
              tma2d_mc(st + 16384 + rank * 8192, &P.wq, col, k, fb, 3);
            }
          }
          auto kv = [&](int row) {
            const uint32_t st = alloc(2, fb);
            if (elect()) {
              mbar_expect(fb, 32768);
              tma2d_mc(st + rank * 16384, &P.scr, col, row, fb, 3);
            }
          };
          need_flag(fv, p, flag, 4);
          kv((2 * p + 1) * 128);
#pragma unroll 1
          for (int j = 2 * p; j >= 0; j--) {
            need_flag(fv, j >> 1, flag, 4);
            if (j == 0) go();
            kv(j * 128);
            kv(SEQ + (j + 1) * 128);
          }
          kv(SEQ);
        } else {
          const int part = type & 1;
          const unsigned* flag = g_sync + (part ? SY_OX + 2 * p + (type == T_XB ? max(h - 1, 0) : 1) : SY_CTX + p * 32 + lane);
          const unsigned target = part ? OX_TARGET : 4;
          const int row = (2 + part) * SEQ + p * 256 + rank * 128;
          if (type >= T_XA) {
            const CUtensorMap* w = part ? &P.wob1 : &P.woa1;
#pragma unroll 1
            for (int i = 0; i < 16; i++) {
              const int k = rank * 2048 + i * 128;
              need_flag(fv, k >> 7, flag, target);
              const uint32_t st = alloc(2, fb);
              if ((ti > 0 || i >= 6 || type != T_XB) && elect()) {
                mbar_expect(fb, 32768);
                tma3d(st, &P.scr64, 0, (2 + part) * SEQ + p * 256 + h * 64, k >> 6, fb);
                tma2d(st + M_GR, w, nn * 64, k, fb);
              }
              if (i == 11) go();
            }
          } else {
            const CUtensorMap* w = part ? &P.wob : &P.woa;
#pragma unroll 1
            for (int k = 0; k < HDALL; k += 64) {
              need_flag(fv, k >> 7, flag, target);
              const uint32_t st = alloc(3, fb);
              if (elect()) {
                mbar_expect(fb, 40960);
                tma2d(st, &P.scr, k, row, fb);
                tma3d_mc(st + 16384 + rank * 12288, w, 0, k + rank * 32, nn * 3, fb, 3);
              }
              if (k == HDALL - 192) go();
            }
          }
          alloc(type >= T_XA ? 2 : 3, fb);
          arrive_elect(fb);
        }
      }
    } else if (warp == 9) {
      started();
      TRM(0);
      if (rank == 0) {
        for (int ti = 0;; ti++) {
          uint32_t q = 0;
          mbar_wait(sb + M_GO, ti & 1);
          if (lane == 0) q = atomicAdd(&g_sync[SY_Q], 1u);
          q = __shfl_sync(0xffffffffu, q, 0);
          if (ti == 0 && q < 100000) TRM(1);
          const uint32_t t = q < P.ntask ? (uint32_t)P.tasks[q] : TASK_END;
          if (ti == 0 && t < 100000) TRM(2);
          mbar_wait(sb + M_TEMPTY + 8 * (ti & 3), ((ti >> 2) & 1) ^ 1);
          if (lane < 2) {
            const uint32_t b = mapa(sb + M_TFULL + 8 * (ti & 3), lane);
            mbar_expect_cl(b, 4);
            st_async32(mapa(sb + M_TSLOT + 4 * (ti & 3), lane), t, b);
          }
          __syncwarp();
          if (t == TASK_END) break;
        }
      }
    } else {
      const int wg = warp - 10;
      const uint32_t emptyx = mapa(sb + M_EMPTY, lane & 1);
      Ring r{0, 0};
      int lead = wg;
      started();
      for (int ti = 0;; ti++) {
        const int sl = ti & 1;
        const uint32_t task = read_task(ti);
        const int type = task >> 12, nn = (task >> 8) & 15, h = (task >> 3) & 31, p = task & 7;
        if (task != TASK_END) {
          const int nit = task_entries(type, p);
          uint32_t st = 0;
          for (int it = 0; it < nit; it++) st = r.take(entry_size(type, it));
          r.e += nit - 1;
          int row = p * 256 + rank * 128 + wg * 64;
          if (type == T_FA) {
            row = 2 * SEQ + p * 256 + (lead ? 3 - (int)rank : (int)rank) * 64;
            lead ^= 1;
          }
          mbar_wait(sb + M_EPI + 8 * (sl * 2 + wg), (ti >> 1) & 1);
          auto store = [&](const CUtensorMap* m, uint32_t src, int r0, int c0, int n32, bool fast = true) {
            if (lane == 0) {
#pragma unroll 1
              for (int i = 0; i < n32 * (32 / ST_ROWS); i++) {
                asm volatile("cp.async.bulk.tensor.2d.global.shared::cta.bulk_group [%0, {%1,%2}], [%3];" ::"l"(m), "r"((c0 + i / (64 / ST_ROWS)) * 64), "r"(r0 + i % (64 / ST_ROWS) * ST_ROWS), "r"(src + i * ST_ROWS * 128) : "memory");
                asm volatile("cp.async.bulk.commit_group;" ::: "memory");
                if (fast) asm volatile("cp.async.bulk.wait_group.read %0;" ::"n"(ST_DEPTH) : "memory");
                else asm volatile("cp.async.bulk.wait_group.read 0;" ::: "memory");
              }
              asm volatile("cp.async.bulk.wait_group.read 0;" ::: "memory");
            }
            __syncwarp();
          };
          if (type != T_FA && type != T_NOP) {
            if (type == T_KV) store(&P.scr_st, sb + st * M_GR + wg * 16384, SEQ + row, h * 2, 4);
            else if (type < T_XA) store(&P.out_st, sb + st * M_GR + wg * 24576, row, (type & 1) * 9 + nn * 3, 6);
            else if (wg == 0) {
              mbar_wait(sb + M_EPI + 8 * (sl * 2 + 1), (ti >> 1) & 1);
              store(&P.out_st, sb + st * M_GR + rank * 4096, p * 256 + h * 64 + rank * 32, (type & 1) * 9 + nn, 1);
            }
            if (lane < 2) asm volatile("mbarrier.arrive.shared::cluster.b64 _, [%0], 4;" ::"r"(emptyx + r.bar()) : "memory");
          }
          r.e++;
          if (type <= T_FA) store(&P.scr_st, sb + M_STG + wg * 16384, row, h * 2, 4, false);
          if (lane == 0) mbar_arrive(sb + M_SFREE + 8 * wg);
          if (lane == 0) {
            asm volatile("cp.async.bulk.wait_group 0;" ::: "memory");
            if (type <= T_FA) {
              __threadfence();
              atomicAdd(type == T_KV ? &g_sync[SY_KV + h * 8 + p] : &g_sync[SY_CTX + p * 32 + h], 1u);
            }
          }
        }
        __syncwarp();
        free_task(ti);
        if (task == TASK_END) break;
      }
    }
    __syncwarp();
    cluster_sync();
    if (threadIdx.x == 288) TRE(256 + blockIdx.x);
    if (warp == 9) {
      uint32_t old = 0;
      if (lane == 0) {
        __threadfence();
        old = atomicAdd(&g_sync[SY_EXIT], 1u);
        __threadfence();
      }
      if (__shfl_sync(0xffffffffu, old, 0) == gridDim.x - 1) {
        asm volatile("griddepcontrol.wait;" ::: "memory");
        for (int i = lane; i < SY_N; i += 32) g_sync[i] = 0;
      }
    }
  } else {
    asm volatile("setmaxnreg.inc.sync.aligned.u32 232;");
    if (warp == 0) TRM(3);
    const int wg = warp >> 2, w4 = warp & 3, g = lane >> 2, t4 = lane & 3;
    const uint32_t emptyx = mapa(sb + M_EMPTY, lane & 1);
    Ring r{0, 0};
    int lead = wg;
    uint32_t xph = 0;
    auto release = [&](uint32_t bar) {
      if (lane < 2) mbar_arrive_cl(emptyx + bar);
    };
    auto acquire = [&](int z, uint32_t& bar) -> uint32_t {
      bar = r.bar();
      mbar_wait(sb + M_FULL + bar, r.par());
      r.e++;
      return sb + r.take(z) * M_GR;
    };
    const uint32_t sa = (w4 * 16 + ((lane >> 3) & 1) * 8 + (lane & 7)) * 128 + (((lane >> 4) ^ (lane & 7)) << 4);
    uint32_t ntask = task0;
    started();
    for (int ti = 0;; ti++) {
      const int sl = ti & 1;
      const uint32_t task = ntask;
      if (task == TASK_END) break;
      auto next_task = [&]() { ntask = read_task(ti + 1); free_task(ti + 1); };
      const int type = task >> 12, p = task & 7;
#ifdef DEV_TRACE
      if (w4 == 0 && lane == 0 && ti < 250) { long long c; asm volatile("mov.u64 %0, %%globaltimer;" : "=l"(c)); g_trace[blockIdx.x * 4096 + ti * 8 + wg * 4] = c; g_trace[blockIdx.x * 4096 + ti * 8 + wg * 4 + 2] = task; g_trace[blockIdx.x * 4096 + ti * 8 + wg * 4 + 3] = clock64(); }
#endif
      if (type == T_KV) {
        float acc[128];
        uint32_t prev;
        {
          const uint32_t st = acquire(3, prev);
          if (ti == 0 && warp == 0) TRM(6);
          const uint32_t a = desc_lo(st + wg * 8192, 16), b = desc_lo(st + 16384, 8192);
          wg_fence();
          wgmma_ssz_n256_a0b1(acc, mk_desc(a, DHI_SW128), mk_desc(b, DHI_SW128));
#pragma unroll
          for (int kk = 1; kk < 4; kk++) wgmma_ss_n256_a0b1(acc, mk_desc(a + kk * 2, DHI_SW128), mk_desc(b + kk * 128, DHI_SW128), 1);
          wg_commit();
        }
#pragma unroll 1
        for (int kb = 1; kb < 8; kb++) {
          uint32_t bar;
          const uint32_t st = acquire(3, bar);
          const uint32_t a = desc_lo(st + wg * 8192, 16), b = desc_lo(st + 16384, 8192);
          if (KV_SKEW < 8 && kb == KV_SKEW && !lead) {
            wg_wait<0>();
            release(prev);
            bar_sync(5, 256);
          }
          wg_fence();
#pragma unroll
          for (int kk = 0; kk < 4; kk++) wgmma_ss_n256_a0b1(acc, mk_desc(a + kk * 2, DHI_SW128), mk_desc(b + kk * 128, DHI_SW128), 1);
          wg_commit();
          if (KV_SKEW < 8 && kb == 7 && lead) bar_arrive(5, 256);
          if (KV_SKEW < 8 && kb == KV_SKEW && !lead) { prev = bar; continue; }
          wg_wait<1>();
          release(prev);
          prev = bar;
        }
        if (ti == 0 && warp == 0) TRM(7);
        next_task();
        uint32_t bar;
        const uint32_t st = acquire(2, bar);
        mbar_wait(sb + M_SFREE + 8 * wg, (ti & 1) ^ 1);
        wg_wait<0>();
        release(prev);
        fence_regs(acc);
        stage_tile<16, 32>(acc, st + wg * 16384 + sa, 1.f, 1.f);
        stage_tile<0, 16>(acc, sb + M_STG + wg * 16384 + sa, 1.f, 1.f);
        fence_async_smem();
        __syncwarp();
        arrive_elect(sb + M_EPI + 8 * (sl * 2 + wg));
      } else if (type == T_FA) {
        const int lng = lead;
        lead ^= 1;
        const int grp = lng ? 3 - (int)rank : (int)rank;
        const int n = 2 * p + 1 + lng;
        float s[64], o[64];
        uint32_t pr[32], q[32];
        TRF(0);
        {
          uint32_t prev;
          {
            const uint32_t st = acquire(2, prev);
            const uint32_t a = desc_lo(st + lng * 8192, 16), b = desc_lo(st + 16384, 8192);
            wg_fence();
            wgmma_ssz_n128_a0b1(s, mk_desc(a, DHI_SW128), mk_desc(b, DHI_SW128));
#pragma unroll
            for (int kk = 1; kk < 4; kk++) wgmma_ss_n128_a0b1(s, mk_desc(a + kk * 2, DHI_SW128), mk_desc(b + kk * 128, DHI_SW128), 1);
            wg_commit();
          }
#pragma unroll 1
          for (int kb = 1; kb < 9; kb++) {
            uint32_t bar;
            if (kb == 1) TRF(8);
            if (kb == 5) TRF(9);
            const uint32_t st = acquire(2, bar);
            const uint32_t a = desc_lo(st + lng * 8192, 16), b = desc_lo(st + 16384, 8192);
            const bool hold = kb == Q_SKEW && !lng;
            if (hold) {
              wg_wait<0>();
              release(prev);
              bar_sync(5, 256);
            }
            wg_fence();
#pragma unroll
            for (int kk = 0; kk < 4; kk++) wgmma_ss_n128_a0b1(s, mk_desc(a + kk * 2, DHI_SW128), mk_desc(b + kk * 128, DHI_SW128), 1);
            wg_commit();
            if (Q_SKEW < 9 && kb == 8 && lng) bar_arrive(5, 256);
            if (hold) { prev = bar; continue; }
            wg_wait<1>();
            release(prev);
            prev = bar;
          }
#pragma unroll
          for (int i = 0; i < 64; i++) o[i] = 0.f;
          wg_wait<0>();
          release(prev);
          fence_regs(s);
#pragma unroll
          for (int i = 0; i < 32; i++) q[i] = pack_bf16(s[2 * i], s[2 * i + 1]);
        }
        TRF(1);
        const int lim0 = (grp & 1) * 64 + w4 * 16 + g - 2 * t4;
        float m0 = -INFINITY, m1 = -INFINITY, l0 = 0.f, l1 = 0.f;
        auto issue_s = [&](uint32_t st) {
          const uint32_t b = desc_lo(st, 16);
#pragma unroll
          for (int kk = 0; kk < 8; kk++) wgmma_rs_n128_b0(s, q[4 * kk], q[4 * kk + 1], q[4 * kk + 2], q[4 * kk + 3], mk_desc(b + (kk >> 2) * 1024 + (kk & 3) * 2, DHI_SW128), kk);
          wg_commit();
        };
        auto issue_pv = [&](uint32_t st) {
          const uint32_t b = desc_lo(st, 16384);
#pragma unroll
          for (int kk = 0; kk < 8; kk++) {
            wgmma_rs_n128_b1(o, pr[4 * kk], pr[4 * kk + 1], pr[4 * kk + 2], pr[4 * kk + 3], mk_desc(b + kk * 128, DHI_SW128), 1);
            if (kk == 1 || kk == 3 || kk == 7) wg_commit();
          }
        };
        auto skip = [&]() {
          uint32_t bar;
          acquire(2, bar);
          release(bar);
        };
        const bool half = !(grp & 1);
        float t[4];
        auto first = [&]() {
          float a0, a1, c0, c1;
          uint32_t kb;
          const uint32_t kst = acquire(2, kb);
          if (!lng) bar_sync(1 + wg, 256);
          fence_regs(q);
          fence_regs(s);
          if (half) {
            const uint32_t b = desc_lo(kst, 16);
            wg_fence();
#pragma unroll
            for (int kk = 0; kk < 8; kk++) wgmma_rs_n64_b0(reinterpret_cast<float(&)[32]>(s), q[4 * kk], q[4 * kk + 1], q[4 * kk + 2], q[4 * kk + 3], mk_desc(b + (kk >> 2) * 1024 + (kk & 3) * 2, DHI_SW128), kk);
            wg_commit();
            bar_arrive(2 - wg, 256);
            wg_wait<0>();
            fence_regs(s);
            causal_mask<0, 8>(s, lim0);
          } else {
            wg_fence();
            issue_s(kst);
            bar_arrive(2 - wg, 256);
            wg_wait<0>();
            fence_regs(s);
            causal_mask<8, 16>(s, lim0);
          }
          release(kb);
          TRF(2);
          softmax_max<FM_NJ>(s, m0, m1, a0, a1, c0, c1);
          softmax_exp<0, 8>(s, pr, c0, c1, t);
          if (half) {
#pragma unroll
            for (int i = 16; i < 32; i++) pr[i] = 0;
          } else {
            softmax_exp<8, 16>(s, pr, c0, c1, t);
          }
        };
        auto block = [&]() {
          const uint32_t kb = r.bar(), kp = r.par(), kst = sb + r.take(2) * M_GR;
          r.e++;
          const uint32_t vb = r.bar(), vp = r.par(), vst = sb + r.take(2) * M_GR;
          r.e++;
          mbar_wait2(sb + M_FULL + kb, kp, sb + M_FULL + vb, vp);
          fence_regs(o);
          fence_regs(pr);
          fence_regs(s);
          bar_sync(1 + wg, 256);
          wg_fence();
          issue_s(kst);
          issue_pv(vst);
          bar_arrive(2 - wg, 256);
          wg_wait<3>();
          release(kb);
          fence_regs(s);
          const float d0 = -m0 * SM_C, d1 = -m1 * SM_C;
          wg_wait<2>();
          fence_part<0, 8>(pr);
          softmax_exp<0, 4>(s, pr, d0, d1, t);
          fence_part<0, 8>(pr);
          sched_fence(kst);
          wg_wait<1>();
          fence_part<8, 16>(pr);
          softmax_exp<4, 8>(s, pr, d0, d1, t);
          fence_part<8, 16>(pr);
          sched_fence(vst);
          wg_wait<0>();
          release(vb);
          fence_regs(o);
          fence_part<16, 32>(pr);
          softmax_exp<8, 16>(s, pr, d0, d1, t);
        };
        auto check = [&](bool hlf) {
          if (__builtin_expect(__any_sync(0xffffffffu, !((t[0] + t[1]) + (t[2] + t[3]) < 1.8446744e19f)), 0)) {
            float a0, a1, c0, c1;
            if (hlf) {
#pragma unroll
              for (int i = 32; i < 64; i++) s[i] = -INFINITY;
            }
            softmax_max<16>(s, m0, m1, a0, a1, c0, c1);
            l0 *= a0;
            l1 *= a1;
#pragma unroll
            for (int i = 0; i < 16; i++) { o[4 * i] *= a0; o[4 * i + 1] *= a0; o[4 * i + 2] *= a1; o[4 * i + 3] *= a1; }
            softmax_exp<0, 16>(s, pr, c0, c1, t);
          }
          l0 += t[0] + t[1];
          l1 += t[2] + t[3];
        };
        if (!lng) skip();
        first();
        check(half);
        if (!lng) skip();
        TRF(3);
#pragma unroll 1
        for (int j = 1; j < n; j++) {
          if (j == n - 1) TRF(4);
          block();
          check(false);
        }
        TRF(5);
        uint32_t vb;
        const uint32_t vst = acquire(2, vb);
        fence_regs(o);
        fence_regs(pr);
        if (!lng) bar_sync(1 + wg, 256);
        wg_fence();
        issue_pv(vst);
        l0 += __shfl_xor_sync(0xffffffffu, l0, 1);
        l1 += __shfl_xor_sync(0xffffffffu, l1, 1);
        l0 += __shfl_xor_sync(0xffffffffu, l0, 2);
        l1 += __shfl_xor_sync(0xffffffffu, l1, 2);
        const float i0 = rcp(l0), i1 = rcp(l1);
        next_task();
        mbar_wait(sb + M_SFREE + 8 * wg, (ti & 1) ^ 1);
        wg_wait<0>();
        release(vb);
        fence_regs(o);
        fence_regs(pr);
        TRF(6);
        stage_tile<0, 16>(o, sb + M_STG + wg * 16384 + sa, i0, i1);
        fence_async_smem();
        __syncwarp();
        arrive_elect(sb + M_EPI + 8 * (sl * 2 + wg));
        TRF(7);
      } else if (type == T_NOP) {
        next_task();
        arrive_elect(sb + M_EPI + 8 * (sl * 2 + wg));
      } else if (type >= T_XA) {
        float acc[16];
#pragma unroll
        for (int i = 0; i < 16; i++) acc[i] = 0.f;
        uint32_t prev = 0;
#pragma unroll 1
        for (int kb = 0; kb < 16; kb++) {
          uint32_t bar;
          const uint32_t st = acquire(2, bar);
          if (ti == 0 && warp == 0 && (kb == 0 || kb == 6)) TRM(kb ? 7 : 6);
          if (ti == 0 && warp == 0 && (kb == 5 || kb == 12)) TRM(kb == 5 ? 8 : 9);
          const uint32_t a = desc_lo(st, 16), b = desc_lo(st + M_GR + wg * 64, 4096);
          wg_fence();
#pragma unroll
          for (int kk = 0; kk < 8; kk++) wgmma_ss_n32_a0b1(acc, mk_desc(a + (kk >> 2) * 512 + (kk & 3) * 2, DHI_SW128), mk_desc(b + kk * 128, DHI_SW128), kk | kb);
          wg_commit();
          if (kb > 0) { wg_wait<1>(); release(prev); }
          prev = bar;
        }
        next_task();
        uint32_t bar;
        const uint32_t st = acquire(2, bar);
        mbar_wait(sb + M_SFREE + 8 * wg, (ti & 1) ^ 1);
        wg_wait<0>();
        release(prev);
        fence_regs(acc);
        const uint32_t xa = st + M_GR + (wg * 64 + (threadIdx.x & 63)) * 16;
        if ((w4 >> 1) != rank) {
          const uint32_t ra = mapa(xa, rank ^ 1), rb = mapa(sb + M_XR, rank ^ 1);
#pragma unroll
          for (int i = 0; i < 4; i++) st_async128(ra + i * 2048, __float_as_uint(acc[4 * i]), __float_as_uint(acc[4 * i + 1]), __float_as_uint(acc[4 * i + 2]), __float_as_uint(acc[4 * i + 3]), rb);
        } else {
          if (wg + (w4 & 1) == 0 && elect()) mbar_expect(sb + M_XR, 8192);
          __syncwarp();
          mbar_wait(sb + M_XR, xph);
#pragma unroll
          for (int i = 0; i < 4; i++) {
            float4 v;
            asm volatile("ld.shared.v4.f32 {%0,%1,%2,%3}, [%4];" : "=f"(v.x), "=f"(v.y), "=f"(v.z), "=f"(v.w) : "r"(xa + i * 2048) : "memory");
            acc[4 * i] += v.x; acc[4 * i + 1] += v.y; acc[4 * i + 2] += v.z; acc[4 * i + 3] += v.w;
          }
          stage_tile<0, 4>(acc, st + (sa ^ (wg << 6)), 1.f, 1.f);
          fence_async_smem();
        }
        xph ^= 1;
        __syncwarp();
        arrive_elect(sb + M_EPI + 8 * (sl * 2 + wg));
      } else {
        float acc[96];
#pragma unroll
        for (int i = 0; i < 96; i++) acc[i] = 0.f;
        uint32_t prev = 0;
        for (int kb = 0; kb < 64; kb++) {
          uint32_t bar;
          const uint32_t st = acquire(3, bar);
          const uint32_t a = desc_lo(st + wg * 8192, 16), b = desc_lo(st + 16384, 4096);
          wg_fence();
#pragma unroll
          for (int kk = 0; kk < 4; kk++) wgmma_ss_n192_a0b1(acc, mk_desc(a + kk * 2, DHI_SW128), mk_desc(b + (kk >> 1) * 768 + (kk & 1) * 128, DHI_SW128), kk | kb);
          wg_commit();
          if (kb > 0) { wg_wait<1>(); release(prev); }
          prev = bar;
        }
        next_task();
        uint32_t bar;
        const uint32_t st = acquire(3, bar);
        mbar_wait(sb + M_SFREE + 8 * wg, (ti & 1) ^ 1);
        wg_wait<0>();
        release(prev);
        fence_regs(acc);
        stage_tile<0, 24>(acc, st + wg * 24576 + sa, 1.f, 1.f);
        fence_async_smem();
        __syncwarp();
        arrive_elect(sb + M_EPI + 8 * (sl * 2 + wg));
      }
#ifdef DEV_TRACE
      if (w4 == 0 && lane == 0 && ti < 250) { long long c; asm volatile("mov.u64 %0, %%globaltimer;" : "=l"(c)); g_trace[blockIdx.x * 4096 + ti * 8 + wg * 4 + 1] = c; }
#endif
    }
    cluster_sync();
  }
}

typedef CUresult (*EncodeFn)(CUtensorMap*, CUtensorMapDataType, cuuint32_t, void*, const cuuint64_t*, const cuuint64_t*, const cuuint32_t*,
                             const cuuint32_t*, CUtensorMapInterleave, CUtensorMapSwizzle, CUtensorMapL2promotion, CUtensorMapFloatOOBfill);

void map2d(EncodeFn enc, CUtensorMap* m, const void* p, int rows, int cols, int boxr) {
  cuuint64_t gd[2] = {(cuuint64_t)cols, (cuuint64_t)rows}, gs[1] = {(cuuint64_t)cols * 2};
  cuuint32_t bx[2] = {64, (cuuint32_t)boxr}, es[2] = {1, 1};
  enc(m, CU_TENSOR_MAP_DATA_TYPE_BFLOAT16, 2, (void*)p, gd, gs, bx, es, CU_TENSOR_MAP_INTERLEAVE_NONE, CU_TENSOR_MAP_SWIZZLE_128B,
      CU_TENSOR_MAP_L2_PROMOTION_L2_256B, CU_TENSOR_MAP_FLOAT_OOB_FILL_NONE);
}
void map3d(EncodeFn enc, CUtensorMap* m, const void* p, int rows, int cols, int boxr, int nch) {
  cuuint64_t gd[3] = {64, (cuuint64_t)rows, (cuuint64_t)cols / 64}, gs[2] = {(cuuint64_t)cols * 2, 128};
  cuuint32_t bx[3] = {64, (cuuint32_t)boxr, (cuuint32_t)nch}, es[3] = {1, 1, 1};
  enc(m, CU_TENSOR_MAP_DATA_TYPE_BFLOAT16, 3, (void*)p, gd, gs, bx, es, CU_TENSOR_MAP_INTERLEAVE_NONE, CU_TENSOR_MAP_SWIZZLE_128B,
      CU_TENSOR_MAP_L2_PROMOTION_L2_256B, CU_TENSOR_MAP_FLOAT_OOB_FILL_NONE);
}

#ifndef R_KR
#define R_KR 24
#endif
#ifndef R_VR
#define R_VR 9
#endif
constexpr int R_NS = 36 - R_KR;
constexpr int R_WQ = 0, R_WK = R_WQ + R_NS * 2048, R_WV = R_WK + R_NS * 2048;
constexpr int R_OS = 102 * 1024;
constexpr int R_RS = 103 * 1024;
static_assert(R_WV + (36 - R_VR) * 2048 <= R_OS, "weights");
constexpr int R_HC = 9216, R_H = 114 * 1024, R_HM = R_H + 4096;
__host__ __device__ constexpr int hoff(int c) { return (c < 8 ? 1 + (c >> 1) + 4 * (c & 1) : 0) * R_HC; }
constexpr int R_PS = R_H + 9 * R_HC;
constexpr int R_GS = 1056, R_HS = 12288, R_QS = 201 * 1024;
static_assert(R_PS + 5120 <= R_QS, "layout");
constexpr int R_BAR = R_QS + 2 * R_HS;
static_assert(3 * 73728 <= R_BAR, "prologue staging");
constexpr int RB_MEM = R_BAR  , RB_RS = R_BAR + 40, RB_QK = R_BAR + 48, RB_XF = R_BAR + 88  , RB_QXL = R_BAR + 104, RB_W = R_BAR + 112  ;
constexpr int RB_TF = R_BAR + 128  , RB_TE = R_BAR + 160  , RB_TR = R_BAR + 192;
constexpr int R_SMEM = R_BAR + 256;
static_assert(R_SMEM <= 232448, "smem");
constexpr int QK_TX = 2048 + 8 * R_GS;
constexpr int NB_P1 = 1, NB_P3 = 2, NB_PM = 3, NB_O = 4, NB_PX = 5, NB_RD = 6, NB_S = 7, NB_O2 = 8;
static_assert(R_NS >= 9 && R_NS <= 18, "R_KR");
__host__ __device__ constexpr int nsm(int c) { return c < R_NS - 9 ? 2 : 1; }
__host__ __device__ constexpr int sm0(int c) { return c < R_NS - 9 ? 2 * c : c + R_NS - 9; }
__host__ __device__ constexpr bool qk_in_reg(int k) { return (k & 3) >= nsm(k >> 2); }
__host__ __device__ constexpr int qk_slot(int k) { return qk_in_reg(k) ? k - sm0((k >> 2) + 1) : sm0(k >> 2) + (k & 3); }
__host__ __device__ constexpr int qk_step(int slot, bool reg) {
  for (int k = 0; k < 36; k++)
    if (qk_in_reg(k) == reg && qk_slot(k) == slot) return k;
  return -1;
}
#ifndef B_SEQ
#define B_SEQ "qkqkqkqkQkqkKqkq|QKQKQKqkQkqKqkQkqKqkQkqKqkQkqKqkQkqKqkQkqKqkQkqKqkQkqKqk"
#endif
__host__ __device__ constexpr int seq_count(char c, int n) {
  int r = 0;
  for (int i = 0; i < n; i++) r += B_SEQ[i] == c;
  return r;
}
static_assert(sizeof(B_SEQ) == 74 && seq_count('q', 73) == R_KR && seq_count('k', 73) == R_KR && seq_count('Q', 73) == R_NS && seq_count('K', 73) == R_NS, "B_SEQ");
#ifndef V_N1
#define V_N1 10
#endif
#ifndef V_PER
#define V_PER 3
#endif
#ifndef V_K0
#define V_K0 11
#endif
#ifndef QX_AFTER
#define QX_AFTER 2
#endif
#ifndef P1_PRE
#define P1_PRE 2
#endif
#ifndef B_DELAY
#define B_DELAY 0
#endif
#ifndef PUB_REL
#define PUB_REL 0
#endif
#ifndef PF_V
#define PF_V 0
#endif
#ifndef PF_MAIN
#define PF_MAIN 0
#endif
#ifndef PRE_EARLY
#define PRE_EARLY 1
#endif
#ifndef P3_EARLY
#define P3_EARLY 0
#endif
#ifndef POLL_STAG
#define POLL_STAG 80
#endif
#ifndef POLL_DELAY
#define POLL_DELAY 240
#endif
__host__ __device__ constexpr bool v_in_reg(int k) { return k >= V_K0 && (k - V_K0) % V_PER == 0 && (k - V_K0) / V_PER < R_VR; }
__host__ __device__ constexpr int v_nreg_before(int k) { return k <= V_K0 ? 0 : ((k - V_K0 + V_PER - 1) / V_PER < R_VR ? (k - V_K0 + V_PER - 1) / V_PER : R_VR); }
__host__ __device__ constexpr int v_slot(int k) { return v_in_reg(k) ? (k - V_K0) / V_PER : k - v_nreg_before(k); }
static_assert(V_K0 + (R_VR - 1) * V_PER < 36, "Wv split");

struct RmtParams {
  CUtensorMap wq, wk, wv, wo, x, mem, ox, ox128, wo3;
  const __nv_bfloat16 *ckv, *wuk, *wuv;
  uint32_t* out;
};
constexpr int XCH_CL = 16 * 288, XCH_SLOT = 4 * XCH_CL;
__device__ uint32_t g_xch[2 * XCH_SLOT];
#ifdef DEV_TRACE
__device__ long long g_trace_b[64 * 4096];
#ifndef TR_S0
#define TR_S0 24
#endif
#ifndef TR_MASK
#define TR_MASK 0xffffffffu
#endif
#define TRW(slot, w) do { if (((TR_MASK >> (slot)) & 1) && w4 == (w) && s >= TR_S0 && s < TR_S0 + 16) { uint32_t c_; asm volatile("mov.u32 %0, %%clock;" : "=r"(c_)::"memory"); sts32(sb + R_QS + R_GS + ((s >> 3) & 1) * R_HS + (s & 7) * 128 + (slot) * 4, c_); } } while (0)
#else
#define TRW(slot, w)
#endif
#define TRB(slot) TRW(slot, 0)
#ifdef DEV_TRACE
#ifndef TRG_MASK
#define TRG_MASK 0x41
#endif
#define TRT(slot, w) do { if (warp == (w) && (threadIdx.x & 31) == 0) { long long c_; asm volatile("mov.u64 %0, %%globaltimer;" : "=l"(c_)); g_trace_b[bid * 4096 + 2200 + (slot)] = c_; } } while (0)
#define TRG(slot) do { if (((slot) >= 16 || ((TRG_MASK >> (slot)) & 1)) && (threadIdx.x & 127) == 0) { long long c_; asm volatile("mov.u64 %0, %%globaltimer;" : "=l"(c_)); g_trace_b[bid * 4096 + 2048 + (slot)] = c_; if ((slot) < 8) g_trace_b[bid * 4096 + 2056 + (slot)] = clock64(); } } while (0)
#else
#define TRG(slot)
#define TRT(slot, w)
#endif

__device__ __forceinline__ void ldsm4(uint32_t (&r)[4], uint32_t a) {
  asm volatile("ldmatrix.sync.aligned.m8n8.x4.shared.b16 {%0,%1,%2,%3}, [%4];" : "=r"(r[0]), "=r"(r[1]), "=r"(r[2]), "=r"(r[3]) : "r"(a) : "memory");
}
__device__ __forceinline__ void ldsm4t(uint32_t (&r)[4], uint32_t a) {
  asm volatile("ldmatrix.sync.aligned.m8n8.x4.trans.shared.b16 {%0,%1,%2,%3}, [%4];" : "=r"(r[0]), "=r"(r[1]), "=r"(r[2]), "=r"(r[3]) : "r"(a) : "memory");
}
__device__ __forceinline__ void stsm4t(uint32_t a, uint32_t r0, uint32_t r1, uint32_t r2, uint32_t r3) {
  asm volatile("stmatrix.sync.aligned.m8n8.x4.trans.shared.b16 [%0], {%1,%2,%3,%4};" ::"r"(a), "r"(r0), "r"(r1), "r"(r2), "r"(r3) : "memory");
}
__device__ __forceinline__ void stsm2t(uint32_t a, uint32_t r0, uint32_t r1) {
  asm volatile("stmatrix.sync.aligned.m8n8.x2.trans.shared.b16 [%0], {%1,%2};" ::"r"(a), "r"(r0), "r"(r1) : "memory");
}
__device__ __forceinline__ void mma16816(float (&c)[4], const uint32_t (&a)[4], uint32_t b0, uint32_t b1) {
  asm volatile("mma.sync.aligned.m16n8k16.row.col.f32.bf16.bf16.f32 {%0,%1,%2,%3}, {%4,%5,%6,%7}, {%8,%9}, {%0,%1,%2,%3};"
               : "+f"(c[0]), "+f"(c[1]), "+f"(c[2]), "+f"(c[3])
               : "r"(a[0]), "r"(a[1]), "r"(a[2]), "r"(a[3]), "r"(b0), "r"(b1));
}
__device__ __forceinline__ void sts32(uint32_t a, uint32_t v) { asm volatile("st.shared.b32 [%0], %1;" ::"r"(a), "r"(v) : "memory"); }
__device__ __forceinline__ uint2 lds64(uint32_t a) {
  uint2 v;
  asm volatile("ld.shared.v2.b32 {%0,%1}, [%2];" : "=r"(v.x), "=r"(v.y) : "r"(a) : "memory");
  return v;
}
__device__ __forceinline__ float4 lds128f(uint32_t a) {
  float4 v;
  asm volatile("ld.shared.v4.f32 {%0,%1,%2,%3}, [%4];" : "=f"(v.x), "=f"(v.y), "=f"(v.z), "=f"(v.w) : "r"(a) : "memory");
  return v;
}
__device__ __forceinline__ uint4 ld_relaxed128(const uint32_t* p) {
  uint4 v;
  asm volatile("ld.relaxed.gpu.global.v4.u32 {%0,%1,%2,%3}, [%4];" : "=r"(v.x), "=r"(v.y), "=r"(v.z), "=r"(v.w) : "l"(p) : "memory");
  return v;
}
__device__ __forceinline__ void st_relaxed32(uint32_t* p, uint32_t v) { asm volatile("st.relaxed.gpu.global.u32 [%0], %1;" ::"l"(p), "r"(v) : "memory"); }

__device__ __forceinline__ void mma1688(float (&c)[4], uint32_t a0, uint32_t a1, uint32_t b0) {
  asm volatile("mma.sync.aligned.m16n8k8.row.col.f32.bf16.bf16.f32 {%0,%1,%2,%3}, {%4,%5}, {%6}, {%0,%1,%2,%3};"
               : "+f"(c[0]), "+f"(c[1]), "+f"(c[2]), "+f"(c[3])
               : "r"(a0), "r"(a1), "r"(b0));
}
__device__ __forceinline__ uint2 ld_relaxed64(const uint32_t* p) {
  uint2 v;
  asm volatile("{.reg .b64 t; ld.relaxed.gpu.global.b64 t, [%2]; mov.b64 {%0,%1}, t;}" : "=r"(v.x), "=r"(v.y) : "l"(p) : "memory");
  return v;
}
__device__ __forceinline__ void st_relaxed64(uint32_t* p, uint32_t a, uint32_t b) { asm volatile("{.reg .b64 t; mov.b64 t, {%1,%2}; st.relaxed.gpu.global.b64 [%0], t;}" ::"l"(p), "r"(a), "r"(b) : "memory"); }

__device__ __forceinline__ void mma16816z(float (&c)[4], const uint32_t (&a)[4], uint32_t b0, uint32_t b1) {
  asm volatile("mma.sync.aligned.m16n8k16.row.col.f32.bf16.bf16.f32 {%0,%1,%2,%3}, {%4,%5,%6,%7}, {%8,%9}, {0f00000000,0f00000000,0f00000000,0f00000000};"
               : "=f"(c[0]), "=f"(c[1]), "=f"(c[2]), "=f"(c[3])
               : "r"(a[0]), "r"(a[1]), "r"(a[2]), "r"(a[3]), "r"(b0), "r"(b1));
}
template <int NB> __device__ __forceinline__ uint2 xch_reduce(uint32_t a, int key, uint32_t* dst, uint32_t tag) {
  uint32_t m[NB][4];
  float c[2][4];
#pragma unroll
  for (int j = 0; j < NB; j++) ldsm4t(m[j], a ^ (j << 5));
#pragma unroll
  for (int j = 0; j < NB; j++) {
    const uint32_t one = key == j ? 0x3f803f80u : 0u;
    if (j < 2) mma16816z(c[j], m[j], one, one);
    else mma16816(c[j & 1], m[j], one, one);
  }
  const uint2 o = make_uint2((__float_as_uint(c[0][0] + c[1][0]) & ~1u) | tag, __float_as_uint(c[0][2] + c[1][2]));
  st_relaxed64(dst, o.x, o.y);
  return o;
}
__device__ __forceinline__ uint32_t xch_sum(const uint2 (&v)[4]) {
  return pack_bf16((__uint_as_float(v[0].x) + __uint_as_float(v[1].x)) + (__uint_as_float(v[2].x) + __uint_as_float(v[3].x)),
                   (__uint_as_float(v[0].y) + __uint_as_float(v[1].y)) + (__uint_as_float(v[2].y) + __uint_as_float(v[3].y)));
}
__device__ __forceinline__ void xch_probe(uint2 (&v)[4], const uint32_t* x, int cl) {
#pragma unroll
  for (int c = 0; c < 4; c++)
    asm volatile("{.reg .pred p; .reg .b64 t; setp.ne.s32 p, %3, %4; mov.b64 t, {%0,%1}; @p ld.relaxed.gpu.global.b64 t, [%2]; mov.b64 {%0,%1}, t;}"
                 : "+r"(v[c].x), "+r"(v[c].y) : "l"(x + c * XCH_CL), "r"(cl), "r"(c) : "memory");
}
__device__ __forceinline__ uint32_t xch_bad(const uint2 (&v)[4]) {
  uint32_t bad;
  asm("{.reg .b32 t; lop3.b32 t, %1, %2, %3, 0x7e; lop3.b32 %0, t, %4, %3, 0xf6;}" : "=r"(bad) : "r"(v[0].x), "r"(v[1].x), "r"(v[2].x), "r"(v[3].x));
  return bad;
}
template <bool TWO> __device__ __forceinline__ uint32_t xch_poll(const uint32_t* x, int cl, uint2 o, const uint32_t* x2, uint2 o2, uint32_t& r2) {
  uint2 v[4] = {o, o, o, o}, w[4] = {o2, o2, o2, o2};
  uint32_t r;
#pragma unroll 1
  for (int it = 0;; it++) {
    xch_probe(v, x, cl);
    if (TWO) xch_probe(w, x2, cl);
    if (it > (1 << 20)) __trap();
    uint32_t bad = xch_bad(v);
    if (TWO) { bad |= xch_bad(w); r2 = xch_sum(w); }
    r = xch_sum(v);
    if (!__any_sync(0xffffffffu, bad & 1)) break;
  }
  return r;
}
constexpr uint32_t CTA1 = 1u << 24;
template <int NSEND, int NPRE> struct XSend {
  uint32_t d[NPRE], b[NPRE];
  static __device__ constexpr uint32_t off(int i) { return ((2 * i + 2 * i / NSEND) & (NSEND - 1)) * CTA1; }
  __device__ __forceinline__ XSend(uint32_t dst, uint32_t bar) {
#pragma unroll
    for (int i = 0; i < NPRE; i++) { d[i] = dst ^ off(i); b[i] = bar ^ off(i); }
    fence_regs(d);
    fence_regs(b);
  }
  __device__ __forceinline__ void send(uint32_t v) {
    asm volatile("" : "+r"(d[0]), "+r"(b[0]));
#pragma unroll
    for (int i = 0; i < NSEND; i++) st_async32(i < NPRE ? d[i] : d[0] ^ off(i), v, i < NPRE ? b[i] : b[0] ^ off(i));
  }
};
__device__ __forceinline__ uint32_t mbar_try_addr(uint32_t bar, uint32_t par, uint32_t good) {
  uint32_t r;
  asm volatile("{.reg .pred p; .reg .b32 t; mbarrier.try_wait.parity.shared::cta.b64 p, [%1], %2; xor.b32 t, %3, 16; selp.b32 %0, %3, t, p;}" : "=r"(r) : "r"(bar), "r"(par), "r"(good) : "memory");
  return r;
}

#ifdef DEV_TRACE
__device__ __noinline__ void trace_sync() {
  if (threadIdx.x == 0) {
    uint32_t g0, g1, c_;
    asm volatile("mov.u32 %0, %%globaltimer_lo;" : "=r"(g0));
    do { asm volatile("mov.u32 %0, %%globaltimer_lo;" : "=r"(g1)); asm volatile("mov.u32 %0, %%clock;" : "=r"(c_)); } while ((g1 >> 10) == (g0 >> 10));
    g_trace_b[(int)blockIdx.x * 4096 + 2160] = g1; g_trace_b[(int)blockIdx.x * 4096 + 2161] = c_;
  }
}
#endif
template <bool MASK>
__device__ __forceinline__ void rmt_softmax_row(const float (&d)[20], int u, int lim, uint32_t pax, uint32_t pam) {
  constexpr float C = 0.08838834764831845f * 1.4426950408889634f;
  float v[10];
#pragma unroll
  for (int j = 0; j < 5; j++) {
    v[2 * j] = (!MASK || j == 4 || 2 * j <= lim) ? d[4 * j + 2 * u] : -INFINITY;
    v[2 * j + 1] = (!MASK || j == 4 || 2 * j + 1 <= lim) ? d[4 * j + 2 * u + 1] : -INFINITY;
  }
  float m = fmaxf(fmaxf(fmaxf(v[0], v[1]), fmaxf(v[2], v[3])), fmaxf(fmaxf(fmaxf(v[4], v[5]), fmaxf(v[6], v[7])), fmaxf(v[8], v[9])));
  m = fmaxf(m, __shfl_xor_sync(0xffffffffu, m, 1));
  m = fmaxf(m, __shfl_xor_sync(0xffffffffu, m, 2));
  const float mc = -m * C;
#pragma unroll
  for (int i = 0; i < 10; i++) v[i] = ex2(fmaf(v[i], C, mc));
  float l = ((v[0] + v[1]) + (v[2] + v[3])) + (((v[4] + v[5]) + (v[6] + v[7])) + (v[8] + v[9]));
  l += __shfl_xor_sync(0xffffffffu, l, 1);
  l += __shfl_xor_sync(0xffffffffu, l, 2);
  const float inv = rcp(l);
  sts128(pax, pack_bf16(v[0] * inv, v[1] * inv), pack_bf16(v[2] * inv, v[3] * inv), pack_bf16(v[4] * inv, v[5] * inv), pack_bf16(v[6] * inv, v[7] * inv));
  sts32(pam, pack_bf16(v[8] * inv, v[9] * inv));
}

__global__ void __launch_bounds__(256, 1) rmt_kernel(const __grid_constant__ RmtParams P) {
  extern __shared__ __align__(1024) uint8_t smem_rmt[];
  const uint32_t sb = (uint32_t)__cvta_generic_to_shared(smem_rmt);
  const int warp = __shfl_sync(0xffffffffu, threadIdx.x >> 5, 0);
  const int lane = __shfl_sync(0xffffffffu, threadIdx.x & 31, threadIdx.x & 31);
  const int w4 = warp & 3, g = lane >> 2, t4 = lane & 3, rho = lane & 7, li = lane >> 3;
  uint32_t rank;
  asm("mov.u32 %0, %%cluster_ctarank;" : "=r"(rank));
  constexpr int ST_O = R_WV, ST_Q = ST_O + 73728, ST_K = ST_Q + R_KR * 2048, ST_V0 = R_OS, ST_V1 = ST_K + R_KR * 2048 - 6 * 2048;
  static_assert(ST_V0 + 6 * 2048 <= R_H && ST_V0 + 6 * 2048 <= ST_Q && ST_V1 + R_VR * 2048 <= R_BAR, "staging");

#ifdef DEV_SYNC
  trace_sync();
#endif
  if (threadIdx.x == 0) {
    if ((sb & 1023) || mapa(sb, 15) != (mapa(sb, 0) ^ (15 * CTA1))) __trap();
    for (int i = 0; i < 6; i++) mbar_init(sb + RB_MEM + 8 * i, 1);
    mbar_init(sb + RB_QK, 5); mbar_init(sb + RB_XF, 1); mbar_init(sb + RB_XF + 8, 1); mbar_init(sb + RB_QXL, 4); mbar_init(sb + RB_W, 1); mbar_init(sb + RB_W + 8, 1);
    for (int i = 0; i < 4; i++) { mbar_init(sb + RB_TF + 8 * i, 1); mbar_init(sb + RB_TE + 8 * i, 4); }
    mbar_init(sb + RB_TR, 1);
    asm volatile("fence.mbarrier_init.release.cluster;" ::: "memory");
    mbar_expect(sb + RB_TR, 49152);
    mbar_expect(sb + RB_W, 2 * 73728);
    mbar_expect(sb + RB_W + 8, 73728);
  }
  if (threadIdx.x == 32) TRE(blockIdx.x);
  asm volatile("griddepcontrol.launch_dependents;");
  const int cl = blockIdx.x >> 4;
  __syncthreads();
  const int bid = cl * 16 + rank, c0 = bid * 64;
  if (warp == 0) TRG(0);
  auto prefetch_main = [&]() {
    asm volatile("cp.async.bulk.prefetch.L2.global [%0], 4096;" ::"l"(P.ckv + (bid * 8 + warp) * 2048) : "memory");
    asm volatile("cp.async.bulk.prefetch.L2.global [%0], 1280;" ::"l"(P.wuk + (bid * 8 + warp) * HDALL) : "memory");
    asm volatile("cp.async.bulk.prefetch.L2.global [%0], 1280;" ::"l"(P.wuv + (bid * 8 + warp) * HDALL) : "memory");
  };
  if (PF_MAIN == 1 && elect()) prefetch_main();
  __syncwarp();
  if (B_DELAY > 0) __nanosleep(B_DELAY);
  if (elect()) {
    for (int i = warp; i < 9; i += 8) tma2d(sb + ST_O + i * 8192, &P.wo, i * 64, c0, sb + RB_W + 8);
    if (warp == 1 && bid < 27) asm volatile("cp.async.bulk.prefetch.tensor.2d.L2.global [%0, {%1,%2}];" ::"l"(bid < 18 ? &P.x : &P.mem), "r"(bid % 9 * 64), "r"(bid / 9 % 2 * 32) : "memory");
    for (int k = warp; k < 36; k += 8) {
      const int o = qk_slot(k) * 2048;
      tma2d(sb + (qk_in_reg(k) ? ST_Q : R_WQ) + o, &P.wq, c0, k * 16, sb + RB_W);
      tma2d(sb + (qk_in_reg(k) ? ST_K : R_WK) + o, &P.wk, c0, k * 16, sb + RB_W);
    }
    if (PF_V) for (int i = warp; i < 36; i += 8) asm volatile("cp.async.bulk.prefetch.tensor.2d.L2.global [%0, {%1,%2}];" ::"l"(&P.wv), "r"(c0), "r"(i * 16) : "memory");
    if (PF_MAIN == 2) prefetch_main();
  }
  __syncwarp();
  uint32_t wa = sb + ((li >> 1) * 8 + rho) * 128 + (((2 * w4 + (li & 1)) ^ rho) << 4);
  uint32_t la = sb + rho * 128 + ((li ^ rho) << 4);
  int ln = lane;
  if (warp == 0) TRG(1);
  mbar_wait(sb + RB_W + 8 * (warp >> 2), 0);
  if (warp == 0) TRG(2);

  if (warp < 4) {
    uint32_t wq[R_KR][4], wk[R_KR][4];
#pragma unroll
    for (int k = 0; k < R_KR; k++) { ldsm4t(wq[k], wa + ST_Q + k * 2048); ldsm4t(wk[k], wa + ST_K + k * 2048); }
    fence_async_smem();
    bar_sync(NB_P3, 256);
    asm volatile("barrier.cluster.arrive.relaxed.aligned;" ::: "memory");
    if (w4 < 2 && elect()) {
      mbar_expect(sb + RB_XF + 8 * w4, 9 * 4096);
      for (int i = 0; i < 9; i++) tma2d(sb + R_H + hoff(i) + w4 * 5120, &P.x, i * 64, w4 * 32, sb + RB_XF + 8 * w4);
    }
    if (w4 == 3 && elect()) {
      mbar_expect(sb + RB_QK, QK_TX);
      for (int i = 0; i < 5; i++) mbar_expect(sb + RB_MEM + 8 * i, i < 4 ? 2048 : 1024);
      for (int i = 0; i < 9; i++) tma2d(sb + R_HM + hoff(i), &P.mem, i * 64, 0, sb + RB_MEM + 8 * (i >> 1));
    }
    if (w4 == 2) sts128(sb + R_PS + (8 + lane) * 128 + ((5 ^ rho) << 4), 0u, 0u, 0u, 0u);
    __syncwarp();
    uint32_t qm = __shfl_sync(0xffffffffu, sb + R_QS + (rank & 1) * R_HS + (w4 * 16 + g) * 16 + t4 * 4, lane);
    const uint32_t peer = mapa(sb, rank ^ 1) - sb;

    uint32_t aq[P1_PRE][4], ak[P1_PRE][4];
    auto preload = [&]() {
#pragma unroll
      for (int i = 0; i < P1_PRE; i++) { ldsm4t(aq[i], wa + R_WQ + i * 2048); ldsm4t(ak[i], wa + R_WK + i * 2048); }
    };
    auto chain = [&](int s) {
      const bool LAST = s == 63;
      float cq[2][4], ck[2][4];
      for (;;) {
        uint32_t b[3][4];
        if (!PRE_EARLY) preload();
        mbar_wait(sb + RB_MEM, s & 1);
        TRB(0);
        uint32_t lb = la, bad = 0;
        ldsm4(b[0], lb + R_HM + hoff(0));
        ldsm4(b[1], (lb ^ 64) + R_HM + hoff(0));
#pragma unroll
        for (int hc = 0; hc < 18; hc++) {
          if (hc + 2 < 18) {
            if ((hc & 3) == 2) { lb = mbar_try_addr(sb + RB_MEM + 8 * ((hc + 2) >> 2), s & 1, la); bad |= lb ^ la; }
            ldsm4(b[(hc + 2) % 3], ((hc & 1) ? (lb ^ 64) : lb) + R_HM + hoff((hc + 2) >> 1));
          }
#pragma unroll
          for (int j = 0; j < 2; j++) {
            const int k = 2 * hc + j, sl = qk_slot(k);
            if (qk_in_reg(k)) {
              mma16816(cq[j], wq[sl], b[hc % 3][2 * j], b[hc % 3][2 * j + 1]);
              mma16816(ck[j], wk[sl], b[hc % 3][2 * j], b[hc % 3][2 * j + 1]);
            } else {
              static_assert(nsm(0) == 2, "first two steps come from shared memory");
              if (hc == 0) {
                mma16816z(cq[j], aq[j], b[0][2 * j], b[0][2 * j + 1]);
                mma16816z(ck[j], ak[j], b[0][2 * j], b[0][2 * j + 1]);
              } else {
                mma16816(cq[j], aq[sl % P1_PRE], b[hc % 3][2 * j], b[hc % 3][2 * j + 1]);
                mma16816(ck[j], ak[sl % P1_PRE], b[hc % 3][2 * j], b[hc % 3][2 * j + 1]);
              }
              if (sl + P1_PRE < R_NS) { ldsm4t(aq[sl % P1_PRE], wa + R_WQ + (sl + P1_PRE) * 2048); ldsm4t(ak[sl % P1_PRE], wa + R_WK + (sl + P1_PRE) * 2048); }
            }
          }
        }
        if (!__any_sync(0xffffffffu, bad)) break;
#pragma unroll 1
        for (int i = 1; i < 5; i++) mbar_wait(sb + RB_MEM + 8 * i, s & 1);
        if (PRE_EARLY) preload();
      }
      const uint32_t q0 = pack_bf16(cq[0][0] + cq[1][0], cq[0][1] + cq[1][1]), q1 = pack_bf16(cq[0][2] + cq[1][2], cq[0][3] + cq[1][3]);
      const uint32_t k0 = pack_bf16(ck[0][0] + ck[1][0], ck[0][1] + ck[1][1]), k1 = pack_bf16(ck[0][2] + ck[1][2], ck[0][3] + ck[1][3]);
      const uint32_t qp = qm + peer, bp = sb + RB_QK + peer;
      st_async32(qp, q0, bp);
      st_async32(qp + 128, q1, bp);
      st_async32(qp + 10 * R_GS, k0, bp);
      st_async32(qp + 10 * R_GS + 128, k1, bp);
      sts32(qm, q0);
      sts32(qm + 128, q1);
      sts32(qm + 10 * R_GS, k0);
      sts32(qm + 10 * R_GS + 128, k1);
      bar_arrive(NB_P1, 256);
      fence_async_smem();
      __syncwarp();
      arrive_elect(sb + RB_QK);
      TRB(1);
      float d[20];
#pragma unroll
      for (int i = 0; i < 20; i++) d[i] = 0.f;
      constexpr uint32_t HI = R_GS >> 4;
      const uint32_t qd = desc_lo(sb + R_QS, 128);
      mbar_wait(sb + RB_QK, s & 1);
      TRB(16);
      wg_fence();
#pragma unroll
      for (int k = 0; k < 8; k++) wgmma_ss_n40_a1b1(d, mk_desc(qd + (k >> 2) * (R_HS >> 4) + (k & 3) * 16, HI), mk_desc(qd + (k >> 2) * (R_HS >> 4) + (k & 3) * 16 + 6 * HI, HI), k != 0);
      wg_commit();
      bar_arrive(NB_S, 256);
      const int ln = (qm >> 2) & 31, tt = ln & 3;
      if (w4 == 0) {
        const int gg = ln >> 2;
        const uint32_t pa = sb + R_PS + gg * 128;
        const uint32_t pax = pa + ((tt ^ gg) << 4), pam = pa + ((4 ^ gg) << 4) + tt * 4;
        wg_wait<0>();
        fence_regs(d);
        TRB(17);
        rmt_softmax_row<false>(d, 0, 0, pax, pam);
        bar_arrive(NB_PM, 160);
        TRB(18);
      } else if (w4 < 3) {
        const int tq = (ln & 24) + 4 * (w4 - 1) + ((ln >> 2) & 1), r7 = tq & 7;
        const uint32_t pa = sb + R_PS + (8 + tq) * 128;
        wg_wait<0>();
        fence_regs(d);
        rmt_softmax_row<true>(d, 0, tq - 8 * tt, pa + ((tt ^ r7) << 4), pa + ((4 ^ r7) << 4) + tt * 4);
        rmt_softmax_row<true>(d, 1, tq + 2 - 8 * tt, pa + 256 + ((tt ^ r7 ^ 2) << 4), pa + 256 + ((6 ^ r7) << 4) + tt * 4);
        fence_async_smem();
        bar_arrive(NB_PX, 192);
        TRW(15, 1);
      } else {
        if (!LAST) {
          if (ln < 7) mbar_expect(sb + RB_MEM + 8 * ln, ln == 6 ? QK_TX : ln == 5 ? 9216 : ln == 4 ? 1024 : 2048);
          if (ln == 11 && s < 62) mbar_expect(sb + RB_XF + 8 * (s & 1), 9 * 4096);
          __syncwarp();
        }
        wg_wait<0>();
        fence_regs(d);
      }
    };
    auto bulk = [&](int s) {
      const bool FIRST = s < 0;
      float dq[16], dk[16];
#pragma unroll
      for (int i = 0; i < 16; i++) dq[i] = dk[i] = 0.f;
      mbar_wait(sb + RB_XF + 8 * ((s + 1) & 1), ((s + 1) >> 1) & 1);
      const uint32_t hd = desc_lo(sb + R_H + ((s + 1) & 1) * 5120, 16), wd = desc_lo(sb + R_WQ, 16);
      auto bdesc = [&](int k) { return mk_desc(hd + (hoff(k >> 2) >> 4) + (k & 3) * 2, DHI_SW128); };
      const uint32_t qx = qm + 2 * R_GS + (qm & 12) * (R_GS / 4 - 1);
      if (!FIRST) bar_sync(NB_P3, 256);
      TRB(2);
      wg_fence();
      static_for<0, 73>([&](auto i_) {
        constexpr int i = decltype(i_)::value;
        constexpr char c = B_SEQ[i];
        constexpr int r = seq_count(c, i), nq = seq_count('q', i) + seq_count('Q', i), nk = seq_count('k', i) + seq_count('K', i);
        if constexpr (c == 'q') wgmma_rs_n32_b0(dq, wq[r][0], wq[r][1], wq[r][2], wq[r][3], bdesc(qk_step(r, true)), nq != 0);
        if constexpr (c == 'k') wgmma_rs_n32_b0(dk, wk[r][0], wk[r][1], wk[r][2], wk[r][3], bdesc(qk_step(r, true)), nk != 0);
        if constexpr (c == 'Q') wgmma_ss_n32_a1b0(dq, mk_desc(wd + r * 128, DHI_SW128), bdesc(qk_step(r, false)), nq != 0);
        if constexpr (c == 'K') wgmma_ss_n32_a1b0(dk, mk_desc(wd + (R_NS + r) * 128, DHI_SW128), bdesc(qk_step(r, false)), nk != 0);
        if constexpr (c == '|') {
          if (!FIRST) bar_sync(NB_RD, 256);
          TRB(6);
        }
      });
      wg_commit();
      if (FIRST) asm volatile("barrier.cluster.wait.aligned;" ::: "memory");
      if (PRE_EARLY) preload();
      wg_wait<0>();
      fence_regs(dq);
      fence_regs(dk);
      TRB(3);
#pragma unroll
      for (int r = 0; r < 2; r++) {
        sts128(qx + r * 128, pack_bf16(dq[2 * r], dq[2 * r + 1]), pack_bf16(dq[4 + 2 * r], dq[5 + 2 * r]), pack_bf16(dq[8 + 2 * r], dq[9 + 2 * r]), pack_bf16(dq[12 + 2 * r], dq[13 + 2 * r]));
        sts128(qx + 4 * R_GS + r * 128, pack_bf16(dk[2 * r], dk[2 * r + 1]), pack_bf16(dk[4 + 2 * r], dk[5 + 2 * r]), pack_bf16(dk[8 + 2 * r], dk[9 + 2 * r]), pack_bf16(dk[12 + 2 * r], dk[13 + 2 * r]));
      }
      __syncwarp();
      arrive_elect(sb + RB_QXL);
      TRB(4);
    };
    TRG(3);
#pragma unroll 1
    for (int s = -1; s < 63;) {
      asm volatile("" : "+r"(wa), "+r"(la), "+r"(qm));
      bulk(s);
      s++;
#ifdef DEV_TRS
      TRG(16 + s);
#endif
      chain(s);
    }
#ifdef DEV_TRACE
    bar_sync(NB_S, 256);
    for (int i = threadIdx.x; i < 16 * 32; i += 128) g_trace_b[bid * 4096 + i] = lds32(sb + R_QS + R_GS + ((i >> 8) ^ 1) * R_HS + (i & 255) * 4);
#endif
  } else {
    uint32_t wo[9][4][4], wv[R_VR][4];
#pragma unroll
    for (int i = 0; i < 9; i++) {
      const int T = i < 8 ? 8 * (i >> 1) + 2 * w4 + (i & 1) : 32 + 2 * (w4 & 1) + (w4 >> 1);
      const int quad = i < 8 ? (g >> 2) * 2 + (g & 1) : g & 3, odd = i < 8 ? (g >> 1) & 1 : g >> 2;
      const uint32_t a = sb + ST_O + (T >> 2) * 8192 + t4 * 256 + (quad & 1) * 8;
      const uint32_t ch = (T & 3) * 2 + (quad >> 1), sel = odd ? 0x7632 : 0x5410;
      const uint32_t a0 = a + ((ch ^ (2 * t4)) << 4), a1 = a + 128 + ((ch ^ (2 * t4 + 1)) << 4);
#pragma unroll
      for (int k = 0; k < 8; k++) {
        const uint2 x = lds64(a0 + k * 1024), y = lds64(a1 + k * 1024);
        wo[i][k >> 1][(k & 1) * 2] = __byte_perm(x.x, y.x, sel);
        wo[i][k >> 1][(k & 1) * 2 + 1] = __byte_perm(x.y, y.y, sel);
      }
    }
    fence_async_smem();
    bar_arrive(NB_P3, 256);
    bar_sync(NB_O, 128);
    if (w4 == 0 && elect()) mbar_expect(sb + RB_W + 8, 73728);
    if (elect())
      for (int k = w4; k < 36; k += 4) {
        const int sl = v_slot(k);
        tma2d(sb + (v_in_reg(k) ? (sl < 6 ? ST_V0 : ST_V1) : R_WV) + sl * 2048, &P.wv, c0, k * 16, sb + RB_W + 8);
      }
    __syncwarp();
    mbar_wait(sb + RB_W + 8, 1);
#pragma unroll
    for (int r = 0; r < R_VR; r++) ldsm4t(wv[r], wa + (r < 6 ? ST_V0 : ST_V1) + r * 2048);
    fence_async_smem();
    asm volatile("barrier.cluster.arrive.relaxed.aligned;" ::: "memory");
    const uint32_t sb0 = mapa(sb, 0), tok = rank & 7;
    uint32_t rsb = mapa(sb + RB_RS, (w4 & 1) * 8 + 2 * t4);
    const uint32_t rrow = rank ^ ((t4 & 1) << 3) ^ (t4 & 2), nrow = rank ^ ((t4 & 1) << 2);
    uint32_t rsA = rsb + (R_RS - RB_RS) + rrow * 128 + (((w4 >> 1) * 64 + g * 8) ^ ((rrow & 7) << 4));
    uint32_t rsN = rsb + (R_RS + 8192 - RB_RS) + nrow * 64 + (((w4 >> 1) * 32 + g * 4) ^ (((nrow >> 1) & 3) << 4));
    const uint32_t cp = 16 * (t4 >> 1) + 8 * ((g >> 1) & 1) + 4 * (t4 & 1) + 2 * (g >> 2) + (g & 1);
    uint32_t agd = sb0 + R_HM + tok * 128 + hoff(2 * w4 + (cp >> 4)) + ((((rank >> 3) * 4 + ((cp & 15) >> 2)) ^ tok) << 4) + (cp & 3) * 4;
    uint32_t* xb = g_xch + rank * 288 + w4 * 64 + lane * 2;
    uint32_t vx[8];
#pragma unroll
    for (int i = 0; i < 8; i++) vx[i] = 0;

    auto step = [&](int s) {
      const bool FIRST = s < 0, LAST = s == 63, MID = !FIRST && !LAST;
      const int par = (s + 1) & 1;
      float d[20];
#pragma unroll
      for (int i = 0; i < 20; i++) d[i] = 0.f;
      if (!LAST) mbar_wait(sb + RB_XF + 8 * par, ((s + 1) >> 1) & 1);
      const uint32_t hd = desc_lo(sb + R_H + par * 4096, 16), vd = desc_lo(sb + R_WV, 16);
      if (!FIRST) {
        if (w4 == 0) {
          mbar_wait(sb + RB_QXL, s & 1);
          mbar_wait(sb + RB_MEM + QX_AFTER * 8, s & 1);
          fence_async_smem();
          if (elect()) {
            const uint32_t src = sb + R_QS + (rank & 1) * R_HS + 2 * R_GS, dst = mapa(src, rank ^ 1), bar = mapa(sb + RB_QK, rank ^ 1), cut = 256 + rank * 512;
            asm volatile("cp.async.bulk.shared::cluster.shared::cta.mbarrier::complete_tx::bytes [%0], [%1], %2, [%3];" ::"r"(dst + cut), "r"(src + cut), "r"(8 * R_GS - cut), "r"(bar) : "memory");
            asm volatile("cp.async.bulk.shared::cluster.shared::cta.mbarrier::complete_tx::bytes [%0], [%1], %2, [%3];" ::"r"(dst), "r"(src), "r"(cut), "r"(bar) : "memory");
          }
          __syncwarp();
          TRW(7, 0);
        }
#pragma unroll
        for (int i = 0; i < 5; i++) { mbar_wait(sb + RB_MEM + 8 * i, s & 1); if (i == 4) TRW(30, 2); }
        fence_async_smem();
        bar_sync(NB_P1, 256);
      }
      wg_fence();
#pragma unroll
      for (int k = 0; k < 36; k++) {
        if (k == V_N1 && !FIRST) bar_sync(NB_S, 256);
        const uint64_t db = mk_desc(hd + (hoff(k >> 2) >> 4) + (k & 3) * 2, DHI_SW128);
        if (v_in_reg(k)) wgmma_rs_n40_b0(d, wv[v_slot(k)][0], wv[v_slot(k)][1], wv[v_slot(k)][2], wv[v_slot(k)][3], db, 1);
        else wgmma_ss_n40_a1b0(d, mk_desc(vd + v_slot(k) * 128, DHI_SW128), db, k != 0);
      }
      wg_commit();
      TRB(8);
      uint32_t vm0, vm1, vn[8];
      auto pack_v = [&]() {
#pragma unroll
        for (int i = 0; i < 8; i++) vn[i] = par ? pack_bf16(d[2 * i + 4], d[2 * i + 5]) : pack_bf16(d[2 * i], d[2 * i + 1]);
      };
      if (MID) {
        float o[4] = {0.f, 0.f, 0.f, 0.f};
        uint32_t b0[4], b1[4];
        bar_sync(NB_PM, 160);
        ldsm4(b0, la + R_PS);
        ldsm4(b1, (la ^ 64) + R_PS);
        {
          const uint32_t x0[4] = {vx[0], vx[1], vx[2], vx[3]}, x1[4] = {vx[4], vx[5], vx[6], vx[7]};
          float o2[4] = {0.f, 0.f, 0.f, 0.f};
          wg_wait<0>();
          fence_regs(d);
          TRB(9);
          mma16816(o, x0, b0[0], b0[1]);
          mma16816(o2, x1, b0[2], b0[3]);
          vm0 = par ? pack_bf16(d[0], d[1]) : pack_bf16(d[16], d[17]);
          vm1 = par ? pack_bf16(d[2], d[3]) : pack_bf16(d[18], d[19]);
          float o3[4] = {0.f, 0.f, 0.f, 0.f};
          mma1688(o3, vm0, vm1, b1[0]);
          stsm2t(wa + R_OS, pack_bf16(o[0] + o2[0] + o3[0], o[1] + o2[1] + o3[1]), pack_bf16(o[2] + o2[2] + o3[2], o[3] + o2[3] + o3[3]));
        }
        bar_sync(NB_O, 128);
        TRB(11);
        ldsm4(b0, la + R_OS);
        ldsm4(b1, (la ^ 64) + R_OS);
        auto send = [&](int j, const float (&c0_)[4], const float (&c1_)[4]) {
          st_async64(rsA + j * 2048, pack_bf16(c0_[0], c0_[2]), pack_bf16(c1_[0], c1_[2]), rsb);
          st_async64(rsA + j * 2048 + CTA1, pack_bf16(c0_[1], c0_[3]), pack_bf16(c1_[1], c1_[3]), rsb + CTA1);
        };
        auto tile = [&](float (&c)[4], int i, int k) {
          if (k == 0) mma16816z(c, wo[i][0], b0[0], b0[1]);
          else mma16816(c, wo[i][k], k < 2 ? b0[2 * k] : b1[2 * k - 4], k < 2 ? b0[2 * k + 1] : b1[2 * k - 3]);
        };
        {
          float c[4][4];
          mma16816z(c[0], wo[0][0], b0[0], b0[1]);
          mma16816z(c[1], wo[1][0], b0[0], b0[1]);
          mma16816z(c[2], wo[0][2], b1[0], b1[1]);
          mma16816z(c[3], wo[1][2], b1[0], b1[1]);
          mma16816(c[0], wo[0][1], b0[2], b0[3]);
          mma16816(c[1], wo[1][1], b0[2], b0[3]);
          mma16816(c[2], wo[0][3], b1[2], b1[3]);
          mma16816(c[3], wo[1][3], b1[2], b1[3]);
          pack_v();
#pragma unroll
          for (int i = 0; i < 4; i++) { c[0][i] += c[2][i]; c[1][i] += c[3][i]; }
          send(0, c[0], c[1]);
          fence_regs(vn);
        }
        sched_fence(rsb);
        TRB(13);
        {
          float c[3][4];
#pragma unroll
          for (int k = 0; k < 4; k++) { tile(c[0], 8, k); tile(c[1], 2, k); tile(c[2], 3, k); }
          st_async32(rsN, pack_bf16(c[0][0], c[0][2]), rsb);
          st_async32(rsN + CTA1, pack_bf16(c[0][1], c[0][3]), rsb + CTA1);
          send(1, c[1], c[2]);
        }
        sched_fence(la);
        {
          float c[4][4];
#pragma unroll
          for (int k = 0; k < 4; k++)
#pragma unroll
            for (int i = 0; i < 4; i++) tile(c[i], 4 + i, k);
          if (P3_EARLY == 1) { sched_fence(rsA); bar_arrive(NB_P3, 256); }
          send(2, c[0], c[1]);
          send(3, c[2], c[3]);
          if (P3_EARLY == 2) bar_arrive(NB_P3, 256);
        }
        TRB(12);
      } else {
        if (LAST) bar_sync(NB_PM, 160);
        wg_wait<0>();
        fence_regs(d);
        vm0 = pack_bf16(d[16], d[17]);
        vm1 = pack_bf16(d[18], d[19]);
        pack_v();
      }
      if (FIRST) {
        asm volatile("barrier.cluster.wait.aligned;" ::: "memory");
        TRG(7);
      } else {
        float e[16];
#pragma unroll
        for (int i = 0; i < 16; i++) e[i] = 0.f;
        uint32_t z0 = 0, z1 = 0;
        asm volatile("" : "+r"(z0), "+r"(z1), "+r"(vm0), "+r"(vm1));
        const uint32_t pd = desc_lo(sb + R_PS + 1024, 16);
        fence_regs(vx);
        bar_sync(NB_PX, 192);
        wg_fence();
        wgmma_rs_n32_b0(e, vx[0], vx[1], vx[2], vx[3], mk_desc(pd, DHI_SW128), 0);
        wgmma_rs_n32_b0(e, vx[4], vx[5], vx[6], vx[7], mk_desc(pd + 2, DHI_SW128), 1);
        wgmma_rs_n32_b0(e, vm0, vm1, z0, z1, mk_desc(pd + 4, DHI_SW128), 1);
        wg_commit();
        if (!P3_EARLY && !LAST) bar_arrive(NB_P3, 256);
        wg_wait<0>();
        fence_regs(e);
        fence_regs(vx);
        bar_sync(NB_O, 128);
        stsm4t(wa + R_PS + 1024, pack_bf16(e[0], e[1]), pack_bf16(e[2], e[3]), pack_bf16(e[4], e[5]), pack_bf16(e[6], e[7]));
        stsm4t(wa + R_PS + 3072, pack_bf16(e[8], e[9]), pack_bf16(e[10], e[11]), pack_bf16(e[12], e[13]), pack_bf16(e[14], e[15]));
        TRB(14);
      }
      auto store_x = [&]() {
        fence_async_smem();
        if (w4 == 2) bar_sync(NB_O2, 128); else bar_arrive(NB_O2, 128);
        if (w4 == 2 && elect()) {
          asm volatile("cp.async.bulk.tensor.2d.global.shared::cta.bulk_group [%0, {%1,%2}], [%3];" ::"l"(&P.ox), "r"(c0), "r"(3 * SEQ + s * 32), "r"(sb + R_PS + 1024) : "memory");
          asm volatile("cp.async.bulk.commit_group;" ::: "memory");
        }
        __syncwarp();
      };
      if (MID) {
        const uint32_t tag = ((s >> 1) & 1) ^ 1;
        uint32_t* x = xb + (s & 1) * XCH_SLOT;
        uint32_t* xw = x + cl * XCH_CL;
        const int src = (ln & 7) + (ln >> 4) * 8, hf = (ln >> 3) & 1;
        const uint32_t ra = sb + R_RS + w4 * 2048 + src * 128 + ((hf ^ (ln & 7)) << 4);
        auto delay = [&](uint32_t t0) {
          while ((uint32_t)clock() - t0 < POLL_DELAY + w4 * POLL_STAG) {}
        };
        uint32_t rn;
        const uint32_t agb = sb0 + RB_MEM + 8 * w4 + (uint32_t)(ln >> 5);
        if (w4 == 3) {
          const int cn = 8 * (ln & 1) + (ln >> 2), no = 64 + 2 * (cn - ln);
          const uint32_t rb = sb + R_RS + 8192 + src * 64 + ((hf ^ ((ln >> 1) & 3)) << 4);
          mbar_wait(sb + RB_RS, s & 1);
          const uint2 o = xch_reduce<4>(ra, ln >> 3, xw, tag);
          const uint2 on = xch_reduce<2>(rb, hf, xw + no, tag);
          const uint32_t t0 = clock();
          bar_arrive(NB_RD, 256);
          TRW(27, 3);
          store_x();
          const uint32_t off = (ln & 2) * 4 * CTA1;
          const uint32_t agn = sb0 + R_HM + tok * 128 + hoff(8) + ((((rank >> 3) * 4 + (cn >> 2)) ^ tok) << 4) + (cn & 3) * 4;
          XSend<16, 6> xs(agd, agb);
          delay(t0);
          const uint32_t r = xch_poll<true>(x, cl, o, x + no, on, rn);
          TRW(28, 3);
          xs.send(r);
          XSend<8, 1>(agn ^ off, (agb + 8) ^ off).send(rn);
          TRW(22, 3);
        } else {
          mbar_wait(sb + RB_RS, s & 1);
          TRB(19);
          const uint2 o = xch_reduce<4>(ra, ln >> 3, xw, tag);
          const uint32_t t0 = clock();
          bar_arrive(NB_RD, 256);
          TRB(25);
          store_x();
          if (w4 == 1 && rank < 9 && s < 62 && elect()) {
            tma2d_mc(sb + R_H + hoff(rank) + (s & 1) * 5120, &P.x, rank * 64, (s + 2) * 32, sb + RB_XF + 8 * (s & 1), 0xffff);
            asm volatile("cp.async.bulk.prefetch.tensor.2d.L2.global [%0, {%1,%2}];" ::"l"(&P.x), "r"(rank * 64), "r"(min(s + 3 + cl, 63) * 32) : "memory");
          }
          __syncwarp();
          XSend<16, 12> xs(agd, agb);
          delay(t0);
          asm volatile("cp.async.bulk.wait_group.read 0;" ::: "memory");
          const uint32_t r = xch_poll<false>(x, cl, o, x, o, rn);
          TRB(26); TRW(10, 1); TRW(20, 2);
          xs.send(r);
          TRB(21); TRW(23, 1); TRW(24, 2);
          if (w4 == 2 && (s & 3) == 3) {
            asm volatile("cp.async.bulk.wait_group 0;" ::: "memory");
#if PUB_REL
            asm volatile("{.reg .pred q; elect.sync _|q, 0xffffffff; @q red.release.gpu.global.add.u32 [%0], 1;}" ::"l"(&g_sync[SY_OX + (s >> 2)]) : "memory");
#else
            asm volatile("{.reg .pred q; elect.sync _|q, 0xffffffff; @q red.relaxed.gpu.global.add.u32 [%0], 1;}" ::"l"(&g_sync[SY_OX + (s >> 2)]) : "memory");
#endif
          }
        }
      }
#pragma unroll
      for (int i = 0; i < 8; i++) vx[i] = vn[i];
    };
    TRG(5);
#pragma unroll 1
    for (int s = -1; s < 64; s++) {
      asm volatile("" : "+r"(wa), "+r"(la), "+r"(rsb), "+r"(rsA), "+r"(rsN), "+r"(agd), "+r"(ln), "+l"(xb));
      step(s);
    }
    if (threadIdx.x == 128) TRE(64 + blockIdx.x);
    fence_async_smem();
    bar_sync(NB_O2, 128);
    if (w4 == 2) {
      if (elect()) {
        asm volatile("cp.async.bulk.tensor.2d.global.shared::cta.bulk_group [%0, {%1,%2}], [%3];" ::"l"(&P.ox), "r"(c0), "r"(3 * SEQ + 63 * 32), "r"(sb + R_PS + 1024) : "memory");
        asm volatile("cp.async.bulk.commit_group;" ::: "memory");
        asm volatile("cp.async.bulk.wait_group 0;" ::: "memory");
#if PUB_REL
        asm volatile("red.release.gpu.global.add.u32 [%0], 1;" ::"l"(&g_sync[SY_OX + 15]) : "memory");
#else
        asm volatile("red.relaxed.gpu.global.add.u32 [%0], 1;" ::"l"(&g_sync[SY_OX + 15]) : "memory");
#endif
      }
      __syncwarp();
    } else {
      uint32_t* z = g_xch + XCH_SLOT + cl * XCH_CL + rank * 288 + (w4 == 3 ? 64 : w4 * 32) + ln;
      st_relaxed32(z, 0u); st_relaxed32(z + 96, 0u); st_relaxed32(z + 192, 0u);
    }
#ifdef DEV_TRACE
    bar_sync(NB_S, 256);
#endif
  }
  cluster_sync();
  {
    const int lane = threadIdx.x & 31, wg = warp >> 2, u = rank >> 1, blk = cl == 3 ? 12 + (rank & 1) : 14 + (rank & 1), nn = min(cl, 2);
    constexpr int T_E = 40960, T_R = 4 * T_E;
    auto load_w = [&](int kb) {
      const uint32_t fb = sb + RB_TF + 8 * (kb & 3);
      mbar_expect(fb, T_E);
      tma3d_mc(sb + (kb & 3) * T_E + 16384 + (rank & 1) * 12288, &P.wo3, 0, u * 512 + kb * 64 + (rank & 1) * 32, nn * 3, fb, 3 << (rank & 14));
    };
    auto load_a = [&](int kb) { tma2d(sb + (kb & 3) * T_E, &P.ox128, u * 512 + kb * 64, 3 * SEQ + blk * 128, sb + RB_TF + 8 * (kb & 3)); };
    TRT(0, 0);
    if (warp == 0 && elect()) {
#pragma unroll 1
      for (int kb = 0; kb < 4; kb++) load_w(kb);
      for (int it = 0; ld_acquire(g_sync + SY_OX + blk) < OX_TARGET; it++)
        if (it > (1 << 22)) __trap();
#pragma unroll 1
      for (int kb = 0; kb < 4; kb++) load_a(kb);
    }
    __syncwarp();
    TRT(1, 0);
    float acc[96];
#pragma unroll
    for (int i = 0; i < 96; i++) acc[i] = 0.f;
    const uint32_t te = mapa(sb + RB_TE, (rank & 14) + (lane & 1));
#pragma unroll 1
    for (int kb = 0; kb < 8; kb++) {
      const uint32_t st = sb + (kb & 3) * T_E, a = desc_lo(st + wg * 8192, 16), b = desc_lo(st + 16384, 4096);
      mbar_wait(sb + RB_TF + 8 * (kb & 3), kb >> 2);
      if (kb == 0) TRT(2, 0);
      wg_fence();
#pragma unroll
      for (int kk = 0; kk < 4; kk++) wgmma_ss_n192_a0b1(acc, mk_desc(a + kk * 2, DHI_SW128), mk_desc(b + (kk >> 1) * 768 + (kk & 1) * 128, DHI_SW128), 1);
      wg_commit();
      wg_wait<1>();
      if (kb >= 1 && kb <= 4) {
        if (w4 == 0 && lane < 2) mbar_arrive_cl(te + 8 * (kb - 1));
        if (warp == 0) {
          mbar_wait(sb + RB_TE + 8 * (kb - 1), 0);
          if (elect()) { load_w(kb + 3); load_a(kb + 3); }
        }
        __syncwarp();
      }
    }
    wg_wait<0>();
    fence_regs(acc);
    TRT(3, 0);
    const uint32_t ra = mapa(sb + T_R + u * 6144 + ((lane ^ u) << 4), 2 * warp + (rank & 1)), rb = mapa(sb + RB_TR, 2 * warp + (rank & 1));
#pragma unroll
    for (int j = 0; j < 12; j++) {
      const int o = 16 * (j >> 1) + (j & 1);
      st_async128(ra + j * 512, pack_bf16(acc[o], acc[o + 2]), pack_bf16(acc[o + 4], acc[o + 6]), pack_bf16(acc[o + 8], acc[o + 10]), pack_bf16(acc[o + 12], acc[o + 14]), rb);
    }
    TRT(4, 0);
    const int r = lane & 7, m = lane >> 3, g = lane >> 2;
    const uint32_t la = sb + T_R + r * 6144 + wg * 3072 + (m >> 1) * 512;
    uint32_t* out = P.out + (blk * 128 + u * 16 + 2 * w4 + 8 * (g & 1)) * DM + DM / 2 + nn * 96 + wg * 48 + (g >> 1) * 4 + (lane & 3);
    mbar_wait(sb + RB_TR, 0);
    TRT(5, 0);
    asm volatile("barrier.cluster.arrive.relaxed.aligned;" ::: "memory");
#pragma unroll 1
    for (int J = 0; J < 3; J++) {
      float c[2][4];
      uint32_t v[4][4];
#pragma unroll
      for (int j = 0; j < 4; j++) ldsm4t(v[j], la + J * 1024 + (((8 * w4 + 4 * (m & 1) + j) ^ r) << 4));
#pragma unroll
      for (int j = 0; j < 4; j++) {
        const uint32_t b0 = g == 2 * j ? 0x3f803f80u : 0u, b1 = g == 2 * j + 1 ? 0x3f803f80u : 0u;
        if (j < 2) mma16816z(c[j], v[j], b0, b1);
        else mma16816(c[j & 1], v[j], b0, b1);
      }
      out[J * 16] = pack_bf16(c[0][0] + c[1][0], c[0][1] + c[1][1]);
      out[J * 16 + DM] = pack_bf16(c[0][2] + c[1][2], c[0][3] + c[1][3]);
    }
    TRT(6, 0);
    if (warp == 0) TRG(6);
    asm volatile("barrier.cluster.wait.aligned;" ::: "memory");
  }
  if (threadIdx.x == 96) TRE(128 + blockIdx.x);
}

void rmt_setup() {
  cudaFuncSetAttribute(rmt_kernel, cudaFuncAttributeMaxDynamicSharedMemorySize, R_SMEM);
  cudaFuncSetAttribute(rmt_kernel, cudaFuncAttributeNonPortableClusterSizeAllowed, 1);
}
void rmt_launch(EncodeFn enc, void* const* d_in, void* scr, void* out) {
  RmtParams R;
  map2d(enc, &R.wq, d_in[8], DM, HDALL, 16);
  map2d(enc, &R.wk, d_in[9], DM, HDALL, 16);
  map2d(enc, &R.wv, d_in[10], DM, HDALL, 16);
  map2d(enc, &R.wo, d_in[11], HDALL, DM, 64);
  map2d(enc, &R.x, d_in[6], SEQ, DM, 32);
  map2d(enc, &R.mem, d_in[7], 8, DM, 8);
  map2d(enc, &R.ox, scr, 4 * SEQ, HDALL, 32);
  cudaLaunchConfig_t cfg = {};
  map2d(enc, &R.ox128, scr, 4 * SEQ, HDALL, 128);
  map3d(enc, &R.wo3, d_in[11], HDALL, DM, 32, 3);
  R.out = (uint32_t*)out;
  R.ckv = (const __nv_bfloat16*)d_in[1]; R.wuk = (const __nv_bfloat16*)d_in[3]; R.wuv = (const __nv_bfloat16*)d_in[4];
  cfg.gridDim = dim3(64);
  cfg.blockDim = dim3(256);
  cfg.dynamicSmemBytes = R_SMEM;
  cfg.stream = cudaStreamPerThread;
  cudaLaunchAttribute at[1];
  at[0].id = cudaLaunchAttributeClusterDimension;
  at[0].val.clusterDim.x = 16;
  at[0].val.clusterDim.y = 1;
  at[0].val.clusterDim.z = 1;
  cfg.attrs = at;
  cfg.numAttrs = 1;
  cudaLaunchKernelEx(&cfg, rmt_kernel, R);
}


const uint16_t h_order[] = {
    4096, 4097, 34, 35, 36, 37, 38, 39, 40, 41, 42, 43, 44, 45, 46, 47, 48, 49, 50, 51,
    52, 53, 54, 55, 56, 57, 58, 59, 60, 61, 62, 63, 64, 65, 66, 67, 68, 69, 70, 71,
    72, 73, 74, 75, 76, 77, 78, 79, 80, 81, 82, 83, 84, 85, 86, 87, 88, 89, 90, 91,
    92, 93, 94, 95, 96, 97, 98, 99, 100, 101, 102, 103, 4103, 4102, 4101, 4100, 4099, 4098, 104, 105,
    106, 107, 108, 109, 110, 111, 4111, 4110, 4109, 4108, 4107, 4106, 112, 113, 114, 115, 116, 117, 118, 119,
    4119, 4118, 4117, 4116, 4115, 4114, 120, 121, 122, 123, 124, 125, 126, 127, 4127, 4126, 4125, 4124, 4123, 4122,
    128, 129, 130, 131, 132, 133, 134, 135, 4135, 4134, 4133, 4132, 4131, 4130, 136, 137, 138, 139, 140, 141,
    142, 143, 4143, 4142, 4141, 4140, 4139, 4138, 144, 145, 146, 147, 148, 149, 150, 151, 4151, 4150, 4149, 4148,
    4147, 4146, 152, 12288, 12544, 12800, 153, 154, 155, 156, 157, 158, 159, 4159, 4158, 4157, 4156, 4155, 4154, 160,
    161, 162, 163, 164, 165, 166, 167, 4167, 4166, 4165, 4164, 4163, 4162, 168, 169, 170, 171, 172, 173, 174,
    175, 4175, 4174, 4173, 4172, 4171, 4170, 176, 177, 178, 179, 180, 181, 182, 183, 4183, 4182, 4181, 4180, 4179,
    4178, 184, 185, 186, 187, 188, 189, 190, 191, 4191, 4190, 4189, 4188, 4187, 4186, 192, 193, 194, 195, 196,
    197, 198, 199, 4199, 4198, 4197, 4196, 4195, 4194, 200, 201, 202, 203, 12289, 12545, 12801, 204, 205, 206, 207,
    4207, 4206, 4205, 4204, 4203, 4202, 208, 209, 210, 211, 212, 213, 214, 215, 4215, 4214, 4213, 4212, 4211, 4210,
    216, 217, 218, 219, 220, 221, 222, 223, 4223, 4222, 4221, 4220, 4219, 12290, 12546, 12802, 4218, 224, 225, 226,
    227, 228, 229, 230, 231, 4231, 4230, 4229, 4228, 4227, 4226, 232, 233, 234, 235, 236, 237, 238, 239, 4239,
    4238, 4237, 4236, 4235, 4234, 240, 241, 242, 243, 244, 245, 246, 247, 4247, 4246, 4245, 4244, 4243, 4242, 248,
    249, 250, 251, 252, 253, 254, 255, 4255, 4254, 12291, 12547, 12803, 4253, 4252, 4251, 4250, 4263, 4262, 4261, 4260,
    4259, 4258, 4271, 4270, 4269, 4268, 4267, 4266, 4279, 4278, 4277, 4276, 4275, 4274, 4287, 4286, 4285, 4284, 4283, 4282,
    4295, 4294, 4293, 4292, 4291, 4290, 4303, 4302, 4301, 4300, 4299, 4298, 4311, 12292, 12548, 12804, 4310, 4309, 4308, 4307,
    4306, 4319, 4318, 4317, 4316, 4315, 4314, 4327, 4326, 4325, 4324, 4323, 4322, 4335, 4334, 4333, 4332, 4331, 4330, 4343,
    4342, 4341, 4340, 4339, 4338, 4351, 4350, 4349, 4348, 4347, 4346, 4105, 4104, 4113, 8199, 8455, 8711, 4112, 4121, 4120,
    4129, 4128, 8194, 8450, 8706, 4137, 4136, 4145, 4144, 4153, 4152, 4161, 4160, 4169, 4168, 4177, 4176, 4185, 4184, 4193,
    4192, 4201, 4200, 4209, 4208, 4217, 4216, 4225, 4224, 4233, 12294, 12550, 4232, 4241, 4240, 4249, 8192, 8448, 8704, 8197,
    8453, 8709, 8198, 8454, 8710, 4248, 4257, 8193, 8449, 8705, 8195, 8451, 8707, 8196, 8452, 8708, 12293, 12549, 12805, 4256,
    4265, 4264, 4273, 4272, 4281, 4280, 4289, 4288, 4297, 4296, 4305, 4304, 4313, 4312, 4321, 4320, 4329, 4328, 4337, 4336,
    4345, 4344,
};
int build_tasks(uint16_t* t) {
  int n = 0;
#ifdef DEV_ORDER
  if (const char* fn = getenv("ORDER")) {
    FILE* f = fopen(fn, "r");
    int v;
    while (fscanf(f, "%d", &v) == 1) t[n++] = v;
    fclose(f);
    return n;
  }
#endif
  static_assert(sizeof(h_order) / 2 <= MAXTASK, "tasks");
  for (; n < (int)(sizeof(h_order) / 2); n++) t[n] = h_order[n];
  return n;
}

}

extern "C" void kernel_launch(void* const* d_in, const int* in_sizes, int n_in, void* d_out, int out_size) {
  (void)in_sizes; (void)n_in; (void)out_size;
  static EncodeFn enc = nullptr;
  static void* scr = nullptr;
  if (!enc) {
    cudaDriverEntryPointQueryResult q;
    cudaGetDriverEntryPoint("cuTensorMapEncodeTiled", (void**)&enc, cudaEnableDefault, &q);
    cudaGetSymbolAddress(&scr, g_scr);
    cudaFuncSetAttribute(main_kernel, cudaFuncAttributeMaxDynamicSharedMemorySize, M_SMEM);
    rmt_setup();
  }
  rmt_launch(enc, d_in, scr, d_out);

  MainParams P;
  map2d(enc, &P.ckv, d_in[1], SEQ, 512, 128);
  map3d(enc, &P.wuk, d_in[3], 512, HDALL, 64, 2);
  map3d(enc, &P.wuv, d_in[4], 512, HDALL, 64, 2);
  map2d(enc, &P.ax, d_in[0], SEQ, DM, 64);
  map2d(enc, &P.wq, d_in[2], DM, HDALL, 64);
  map2d(enc, &P.scr, scr, 4 * SEQ, HDALL, 128);
  map3d(enc, &P.woa, d_in[5], HDALL, DM, 32, 3);
  map3d(enc, &P.wob, d_in[11], HDALL, DM, 32, 3);
  map2d(enc, &P.scr_st, scr, 4 * SEQ, HDALL, ST_ROWS);
  map2d(enc, &P.out_st, d_out, SEQ, 2 * DM, ST_ROWS);
  map2d(enc, &P.woa1, d_in[5], HDALL, DM, 128);
  map2d(enc, &P.wob1, d_in[11], HDALL, DM, 128);
  map3d(enc, &P.scr64, scr, 4 * SEQ, HDALL, 64, 2);
  P.ntask = build_tasks(P.tasks);

  cudaLaunchConfig_t cfg = {};
  cfg.gridDim = dim3(2 * NCL);
  cfg.blockDim = dim3(384);
  cfg.dynamicSmemBytes = M_SMEM;
  cfg.stream = cudaStreamPerThread;
  cudaLaunchAttribute at[1];
  at[0].id = cudaLaunchAttributeProgrammaticStreamSerialization;
  at[0].val.programmaticStreamSerializationAllowed = 1;
  cfg.attrs = at;
  cfg.numAttrs = 1;
#ifdef DEV_SERIAL
  cfg.numAttrs = 0;
#endif
  cudaLaunchKernelEx(&cfg, main_kernel, P);
}
```

```cpp
#include <cuda_runtime.h>
#include <cuda_bf16.h>
#include <cuda.h>
#include <stdint.h>
#ifdef DEV_ORDER
#include <stdio.h>
#include <stdlib.h>
#endif

namespace {

constexpr int SEQ = 2048, DM = 576, HDALL = 4096;

__device__ __nv_bfloat16 g_scr[4ull * SEQ * HDALL];
constexpr int SY_Q = 0, SY_EXIT = 16, SY_KV = 32, SY_CTX = 32 + 256, SY_OX = 32 + 512, SY_N = 32 + 512 + 32;
__device__ unsigned g_sync[SY_N];

#ifdef DEV_END
__device__ long long g_end[512];
#define TRE(i) do { long long c_; asm volatile("mov.u64 %0, %%globaltimer;" : "=l"(c_)); g_end[i] = c_; } while (0)
#else
#define TRE(i)
#endif
#ifdef DEV_TRACE
__device__ long long g_trace[132 * 4096];
#ifdef DEV_TRF
#define TRF(slot) do { if (w4 == 0 && ti < 60) { uint32_t c_; asm volatile("mov.u32 %0, %%clock;" : "=r"(c_)::"memory"); if (elect()) g_trace[blockIdx.x * 4096 + 2048 + ti * 32 + wg * 16 + (slot)] = c_; __syncwarp(); } } while (0)
#else
#define TRF(slot)
#endif
#define TRM(slot) do { if ((threadIdx.x & 31) == 0) { long long c_; asm volatile("mov.u64 %0, %%globaltimer;" : "=l"(c_)); g_trace[blockIdx.x * 4096 + 4080 + (slot)] = c_; } } while (0)
#else
#define TRM(slot)
#define TRF(slot)
#endif

__device__ __forceinline__ void wgmma_ss_n256_a0b1(float (&d)[128], uint64_t da, uint64_t db, int sc) {
  asm volatile("{.reg .pred p; setp.ne.b32 p, %130, 0; wgmma.mma_async.sync.aligned.m64n256k16.f32.bf16.bf16 {%0,%1,%2,%3,%4,%5,%6,%7,%8,%9,%10,%11,%12,%13,%14,%15,%16,%17,%18,%19,%20,%21,%22,%23,%24,%25,%26,%27,%28,%29,%30,%31,%32,%33,%34,%35,%36,%37,%38,%39,%40,%41,%42,%43,%44,%45,%46,%47,%48,%49,%50,%51,%52,%53,%54,%55,%56,%57,%58,%59,%60,%61,%62,%63,%64,%65,%66,%67,%68,%69,%70,%71,%72,%73,%74,%75,%76,%77,%78,%79,%80,%81,%82,%83,%84,%85,%86,%87,%88,%89,%90,%91,%92,%93,%94,%95,%96,%97,%98,%99,%100,%101,%102,%103,%104,%105,%106,%107,%108,%109,%110,%111,%112,%113,%114,%115,%116,%117,%118,%119,%120,%121,%122,%123,%124,%125,%126,%127}, %128, %129, p, 1, 1, 0, 1;}"
    : "+f"(d[0]),"+f"(d[1]),"+f"(d[2]),"+f"(d[3]),"+f"(d[4]),"+f"(d[5]),"+f"(d[6]),"+f"(d[7]),"+f"(d[8]),"+f"(d[9]),"+f"(d[10]),"+f"(d[11]),"+f"(d[12]),"+f"(d[13]),"+f"(d[14]),"+f"(d[15]),"+f"(d[16]),"+f"(d[17]),"+f"(d[18]),"+f"(d[19]),"+f"(d[20]),"+f"(d[21]),"+f"(d[22]),"+f"(d[23]),"+f"(d[24]),"+f"(d[25]),"+f"(d[26]),"+f"(d[27]),"+f"(d[28]),"+f"(d[29]),"+f"(d[30]),"+f"(d[31]),"+f"(d[32]),"+f"(d[33]),"+f"(d[34]),"+f"(d[35]),"+f"(d[36]),"+f"(d[37]),"+f"(d[38]),"+f"(d[39]),"+f"(d[40]),"+f"(d[41]),"+f"(d[42]),"+f"(d[43]),"+f"(d[44]),"+f"(d[45]),"+f"(d[46]),"+f"(d[47]),"+f"(d[48]),"+f"(d[49]),"+f"(d[50]),"+f"(d[51]),"+f"(d[52]),"+f"(d[53]),"+f"(d[54]),"+f"(d[55]),"+f"(d[56]),"+f"(d[57]),"+f"(d[58]),"+f"(d[59]),"+f"(d[60]),"+f"(d[61]),"+f"(d[62]),"+f"(d[63]),"+f"(d[64]),"+f"(d[65]),"+f"(d[66]),"+f"(d[67]),"+f"(d[68]),"+f"(d[69]),"+f"(d[70]),"+f"(d[71]),"+f"(d[72]),"+f"(d[73]),"+f"(d[74]),"+f"(d[75]),"+f"(d[76]),"+f"(d[77]),"+f"(d[78]),"+f"(d[79]),"+f"(d[80]),"+f"(d[81]),"+f"(d[82]),"+f"(d[83]),"+f"(d[84]),"+f"(d[85]),"+f"(d[86]),"+f"(d[87]),"+f"(d[88]),"+f"(d[89]),"+f"(d[90]),"+f"(d[91]),"+f"(d[92]),"+f"(d[93]),"+f"(d[94]),"+f"(d[95]),"+f"(d[96]),"+f"(d[97]),"+f"(d[98]),"+f"(d[99]),"+f"(d[100]),"+f"(d[101]),"+f"(d[102]),"+f"(d[103]),"+f"(d[104]),"+f"(d[105]),"+f"(d[106]),"+f"(d[107]),"+f"(d[108]),"+f"(d[109]),"+f"(d[110]),"+f"(d[111]),"+f"(d[112]),"+f"(d[113]),"+f"(d[114]),"+f"(d[115]),"+f"(d[116]),"+f"(d[117]),"+f"(d[118]),"+f"(d[119]),"+f"(d[120]),"+f"(d[121]),"+f"(d[122]),"+f"(d[123]),"+f"(d[124]),"+f"(d[125]),"+f"(d[126]),"+f"(d[127])
    : "l"(da), "l"(db), "r"(sc));
}
__device__ __forceinline__ void wgmma_ss_n192_a0b1(float (&d)[96], uint64_t da, uint64_t db, int sc) {
  asm volatile("{.reg .pred p; setp.ne.b32 p, %98, 0; wgmma.mma_async.sync.aligned.m64n192k16.f32.bf16.bf16 {%0,%1,%2,%3,%4,%5,%6,%7,%8,%9,%10,%11,%12,%13,%14,%15,%16,%17,%18,%19,%20,%21,%22,%23,%24,%25,%26,%27,%28,%29,%30,%31,%32,%33,%34,%35,%36,%37,%38,%39,%40,%41,%42,%43,%44,%45,%46,%47,%48,%49,%50,%51,%52,%53,%54,%55,%56,%57,%58,%59,%60,%61,%62,%63,%64,%65,%66,%67,%68,%69,%70,%71,%72,%73,%74,%75,%76,%77,%78,%79,%80,%81,%82,%83,%84,%85,%86,%87,%88,%89,%90,%91,%92,%93,%94,%95}, %96, %97, p, 1, 1, 0, 1;}"
    : "+f"(d[0]),"+f"(d[1]),"+f"(d[2]),"+f"(d[3]),"+f"(d[4]),"+f"(d[5]),"+f"(d[6]),"+f"(d[7]),"+f"(d[8]),"+f"(d[9]),"+f"(d[10]),"+f"(d[11]),"+f"(d[12]),"+f"(d[13]),"+f"(d[14]),"+f"(d[15]),"+f"(d[16]),"+f"(d[17]),"+f"(d[18]),"+f"(d[19]),"+f"(d[20]),"+f"(d[21]),"+f"(d[22]),"+f"(d[23]),"+f"(d[24]),"+f"(d[25]),"+f"(d[26]),"+f"(d[27]),"+f"(d[28]),"+f"(d[29]),"+f"(d[30]),"+f"(d[31]),"+f"(d[32]),"+f"(d[33]),"+f"(d[34]),"+f"(d[35]),"+f"(d[36]),"+f"(d[37]),"+f"(d[38]),"+f"(d[39]),"+f"(d[40]),"+f"(d[41]),"+f"(d[42]),"+f"(d[43]),"+f"(d[44]),"+f"(d[45]),"+f"(d[46]),"+f"(d[47]),"+f"(d[48]),"+f"(d[49]),"+f"(d[50]),"+f"(d[51]),"+f"(d[52]),"+f"(d[53]),"+f"(d[54]),"+f"(d[55]),"+f"(d[56]),"+f"(d[57]),"+f"(d[58]),"+f"(d[59]),"+f"(d[60]),"+f"(d[61]),"+f"(d[62]),"+f"(d[63]),"+f"(d[64]),"+f"(d[65]),"+f"(d[66]),"+f"(d[67]),"+f"(d[68]),"+f"(d[69]),"+f"(d[70]),"+f"(d[71]),"+f"(d[72]),"+f"(d[73]),"+f"(d[74]),"+f"(d[75]),"+f"(d[76]),"+f"(d[77]),"+f"(d[78]),"+f"(d[79]),"+f"(d[80]),"+f"(d[81]),"+f"(d[82]),"+f"(d[83]),"+f"(d[84]),"+f"(d[85]),"+f"(d[86]),"+f"(d[87]),"+f"(d[88]),"+f"(d[89]),"+f"(d[90]),"+f"(d[91]),"+f"(d[92]),"+f"(d[93]),"+f"(d[94]),"+f"(d[95])
    : "l"(da), "l"(db), "r"(sc));
}
__device__ __forceinline__ void wgmma_rs_n64_b0(float (&d)[32], uint32_t a0, uint32_t a1, uint32_t a2, uint32_t a3, uint64_t db, int sc) {
  asm volatile("{.reg .pred p; setp.ne.b32 p, %37, 0; wgmma.mma_async.sync.aligned.m64n64k16.f32.bf16.bf16 {%0,%1,%2,%3,%4,%5,%6,%7,%8,%9,%10,%11,%12,%13,%14,%15,%16,%17,%18,%19,%20,%21,%22,%23,%24,%25,%26,%27,%28,%29,%30,%31}, {%32,%33,%34,%35}, %36, p, 1, 1, 0;}"
    : "+f"(d[0]),"+f"(d[1]),"+f"(d[2]),"+f"(d[3]),"+f"(d[4]),"+f"(d[5]),"+f"(d[6]),"+f"(d[7]),"+f"(d[8]),"+f"(d[9]),"+f"(d[10]),"+f"(d[11]),"+f"(d[12]),"+f"(d[13]),"+f"(d[14]),"+f"(d[15]),"+f"(d[16]),"+f"(d[17]),"+f"(d[18]),"+f"(d[19]),"+f"(d[20]),"+f"(d[21]),"+f"(d[22]),"+f"(d[23]),"+f"(d[24]),"+f"(d[25]),"+f"(d[26]),"+f"(d[27]),"+f"(d[28]),"+f"(d[29]),"+f"(d[30]),"+f"(d[31])
    : "r"(a0), "r"(a1), "r"(a2), "r"(a3), "l"(db), "r"(sc));
}
__device__ __forceinline__ void wgmma_ss_n128_a0b1(float (&d)[64], uint64_t da, uint64_t db, int sc) {
  asm volatile("{.reg .pred p; setp.ne.b32 p, %66, 0; wgmma.mma_async.sync.aligned.m64n128k16.f32.bf16.bf16 {%0,%1,%2,%3,%4,%5,%6,%7,%8,%9,%10,%11,%12,%13,%14,%15,%16,%17,%18,%19,%20,%21,%22,%23,%24,%25,%26,%27,%28,%29,%30,%31,%32,%33,%34,%35,%36,%37,%38,%39,%40,%41,%42,%43,%44,%45,%46,%47,%48,%49,%50,%51,%52,%53,%54,%55,%56,%57,%58,%59,%60,%61,%62,%63}, %64, %65, p, 1, 1, 0, 1;}"
    : "+f"(d[0]),"+f"(d[1]),"+f"(d[2]),"+f"(d[3]),"+f"(d[4]),"+f"(d[5]),"+f"(d[6]),"+f"(d[7]),"+f"(d[8]),"+f"(d[9]),"+f"(d[10]),"+f"(d[11]),"+f"(d[12]),"+f"(d[13]),"+f"(d[14]),"+f"(d[15]),"+f"(d[16]),"+f"(d[17]),"+f"(d[18]),"+f"(d[19]),"+f"(d[20]),"+f"(d[21]),"+f"(d[22]),"+f"(d[23]),"+f"(d[24]),"+f"(d[25]),"+f"(d[26]),"+f"(d[27]),"+f"(d[28]),"+f"(d[29]),"+f"(d[30]),"+f"(d[31]),"+f"(d[32]),"+f"(d[33]),"+f"(d[34]),"+f"(d[35]),"+f"(d[36]),"+f"(d[37]),"+f"(d[38]),"+f"(d[39]),"+f"(d[40]),"+f"(d[41]),"+f"(d[42]),"+f"(d[43]),"+f"(d[44]),"+f"(d[45]),"+f"(d[46]),"+f"(d[47]),"+f"(d[48]),"+f"(d[49]),"+f"(d[50]),"+f"(d[51]),"+f"(d[52]),"+f"(d[53]),"+f"(d[54]),"+f"(d[55]),"+f"(d[56]),"+f"(d[57]),"+f"(d[58]),"+f"(d[59]),"+f"(d[60]),"+f"(d[61]),"+f"(d[62]),"+f"(d[63])
    : "l"(da), "l"(db), "r"(sc));
}
__device__ __forceinline__ void wgmma_rs_n128_b0(float (&d)[64], uint32_t a0, uint32_t a1, uint32_t a2, uint32_t a3, uint64_t db, int sc) {
  asm volatile("{.reg .pred p; setp.ne.b32 p, %69, 0; wgmma.mma_async.sync.aligned.m64n128k16.f32.bf16.bf16 {%0,%1,%2,%3,%4,%5,%6,%7,%8,%9,%10,%11,%12,%13,%14,%15,%16,%17,%18,%19,%20,%21,%22,%23,%24,%25,%26,%27,%28,%29,%30,%31,%32,%33,%34,%35,%36,%37,%38,%39,%40,%41,%42,%43,%44,%45,%46,%47,%48,%49,%50,%51,%52,%53,%54,%55,%56,%57,%58,%59,%60,%61,%62,%63}, {%64,%65,%66,%67}, %68, p, 1, 1, 0;}"
    : "+f"(d[0]),"+f"(d[1]),"+f"(d[2]),"+f"(d[3]),"+f"(d[4]),"+f"(d[5]),"+f"(d[6]),"+f"(d[7]),"+f"(d[8]),"+f"(d[9]),"+f"(d[10]),"+f"(d[11]),"+f"(d[12]),"+f"(d[13]),"+f"(d[14]),"+f"(d[15]),"+f"(d[16]),"+f"(d[17]),"+f"(d[18]),"+f"(d[19]),"+f"(d[20]),"+f"(d[21]),"+f"(d[22]),"+f"(d[23]),"+f"(d[24]),"+f"(d[25]),"+f"(d[26]),"+f"(d[27]),"+f"(d[28]),"+f"(d[29]),"+f"(d[30]),"+f"(d[31]),"+f"(d[32]),"+f"(d[33]),"+f"(d[34]),"+f"(d[35]),"+f"(d[36]),"+f"(d[37]),"+f"(d[38]),"+f"(d[39]),"+f"(d[40]),"+f"(d[41]),"+f"(d[42]),"+f"(d[43]),"+f"(d[44]),"+f"(d[45]),"+f"(d[46]),"+f"(d[47]),"+f"(d[48]),"+f"(d[49]),"+f"(d[50]),"+f"(d[51]),"+f"(d[52]),"+f"(d[53]),"+f"(d[54]),"+f"(d[55]),"+f"(d[56]),"+f"(d[57]),"+f"(d[58]),"+f"(d[59]),"+f"(d[60]),"+f"(d[61]),"+f"(d[62]),"+f"(d[63])
    : "r"(a0), "r"(a1), "r"(a2), "r"(a3), "l"(db), "r"(sc));
}
__device__ __forceinline__ void wgmma_rs_n128_b1(float (&d)[64], uint32_t a0, uint32_t a1, uint32_t a2, uint32_t a3, uint64_t db, int sc) {
  asm volatile("{.reg .pred p; setp.ne.b32 p, %69, 0; wgmma.mma_async.sync.aligned.m64n128k16.f32.bf16.bf16 {%0,%1,%2,%3,%4,%5,%6,%7,%8,%9,%10,%11,%12,%13,%14,%15,%16,%17,%18,%19,%20,%21,%22,%23,%24,%25,%26,%27,%28,%29,%30,%31,%32,%33,%34,%35,%36,%37,%38,%39,%40,%41,%42,%43,%44,%45,%46,%47,%48,%49,%50,%51,%52,%53,%54,%55,%56,%57,%58,%59,%60,%61,%62,%63}, {%64,%65,%66,%67}, %68, p, 1, 1, 1;}"
    : "+f"(d[0]),"+f"(d[1]),"+f"(d[2]),"+f"(d[3]),"+f"(d[4]),"+f"(d[5]),"+f"(d[6]),"+f"(d[7]),"+f"(d[8]),"+f"(d[9]),"+f"(d[10]),"+f"(d[11]),"+f"(d[12]),"+f"(d[13]),"+f"(d[14]),"+f"(d[15]),"+f"(d[16]),"+f"(d[17]),"+f"(d[18]),"+f"(d[19]),"+f"(d[20]),"+f"(d[21]),"+f"(d[22]),"+f"(d[23]),"+f"(d[24]),"+f"(d[25]),"+f"(d[26]),"+f"(d[27]),"+f"(d[28]),"+f"(d[29]),"+f"(d[30]),"+f"(d[31]),"+f"(d[32]),"+f"(d[33]),"+f"(d[34]),"+f"(d[35]),"+f"(d[36]),"+f"(d[37]),"+f"(d[38]),"+f"(d[39]),"+f"(d[40]),"+f"(d[41]),"+f"(d[42]),"+f"(d[43]),"+f"(d[44]),"+f"(d[45]),"+f"(d[46]),"+f"(d[47]),"+f"(d[48]),"+f"(d[49]),"+f"(d[50]),"+f"(d[51]),"+f"(d[52]),"+f"(d[53]),"+f"(d[54]),"+f"(d[55]),"+f"(d[56]),"+f"(d[57]),"+f"(d[58]),"+f"(d[59]),"+f"(d[60]),"+f"(d[61]),"+f"(d[62]),"+f"(d[63])
    : "r"(a0), "r"(a1), "r"(a2), "r"(a3), "l"(db), "r"(sc));
}
__device__ __forceinline__ void wgmma_rs_n32_b0(float (&d)[16], uint32_t a0, uint32_t a1, uint32_t a2, uint32_t a3, uint64_t db, int sc) {
  asm volatile("{.reg .pred p; setp.ne.b32 p, %21, 0; wgmma.mma_async.sync.aligned.m64n32k16.f32.bf16.bf16 {%0,%1,%2,%3,%4,%5,%6,%7,%8,%9,%10,%11,%12,%13,%14,%15}, {%16,%17,%18,%19}, %20, p, 1, 1, 0;}"
    : "+f"(d[0]),"+f"(d[1]),"+f"(d[2]),"+f"(d[3]),"+f"(d[4]),"+f"(d[5]),"+f"(d[6]),"+f"(d[7]),"+f"(d[8]),"+f"(d[9]),"+f"(d[10]),"+f"(d[11]),"+f"(d[12]),"+f"(d[13]),"+f"(d[14]),"+f"(d[15])
    : "r"(a0), "r"(a1), "r"(a2), "r"(a3), "l"(db), "r"(sc));
}
__device__ __forceinline__ void wgmma_ss_n32_a1b0(float (&d)[16], uint64_t da, uint64_t db, int sc) {
  asm volatile("{.reg .pred p; setp.ne.b32 p, %18, 0; wgmma.mma_async.sync.aligned.m64n32k16.f32.bf16.bf16 {%0,%1,%2,%3,%4,%5,%6,%7,%8,%9,%10,%11,%12,%13,%14,%15}, %16, %17, p, 1, 1, 1, 0;}"
    : "+f"(d[0]),"+f"(d[1]),"+f"(d[2]),"+f"(d[3]),"+f"(d[4]),"+f"(d[5]),"+f"(d[6]),"+f"(d[7]),"+f"(d[8]),"+f"(d[9]),"+f"(d[10]),"+f"(d[11]),"+f"(d[12]),"+f"(d[13]),"+f"(d[14]),"+f"(d[15])
    : "l"(da), "l"(db), "r"(sc));
}
__device__ __forceinline__ void wgmma_ss_n40_a1b0(float (&d)[20], uint64_t da, uint64_t db, int sc) {
  asm volatile("{.reg .pred p; setp.ne.b32 p, %22, 0; wgmma.mma_async.sync.aligned.m64n40k16.f32.bf16.bf16 {%0,%1,%2,%3,%4,%5,%6,%7,%8,%9,%10,%11,%12,%13,%14,%15,%16,%17,%18,%19}, %20, %21, p, 1, 1, 1, 0;}"
    : "+f"(d[0]),"+f"(d[1]),"+f"(d[2]),"+f"(d[3]),"+f"(d[4]),"+f"(d[5]),"+f"(d[6]),"+f"(d[7]),"+f"(d[8]),"+f"(d[9]),"+f"(d[10]),"+f"(d[11]),"+f"(d[12]),"+f"(d[13]),"+f"(d[14]),"+f"(d[15]),"+f"(d[16]),"+f"(d[17]),"+f"(d[18]),"+f"(d[19])
    : "l"(da), "l"(db), "r"(sc));
}
__device__ __forceinline__ void wgmma_ss_n40_a1b1(float (&d)[20], uint64_t da, uint64_t db, int sc) {
  asm volatile("{.reg .pred p; setp.ne.b32 p, %22, 0; wgmma.mma_async.sync.aligned.m64n40k16.f32.bf16.bf16 {%0,%1,%2,%3,%4,%5,%6,%7,%8,%9,%10,%11,%12,%13,%14,%15,%16,%17,%18,%19}, %20, %21, p, 1, 1, 1, 1;}"
    : "+f"(d[0]),"+f"(d[1]),"+f"(d[2]),"+f"(d[3]),"+f"(d[4]),"+f"(d[5]),"+f"(d[6]),"+f"(d[7]),"+f"(d[8]),"+f"(d[9]),"+f"(d[10]),"+f"(d[11]),"+f"(d[12]),"+f"(d[13]),"+f"(d[14]),"+f"(d[15]),"+f"(d[16]),"+f"(d[17]),"+f"(d[18]),"+f"(d[19])
    : "l"(da), "l"(db), "r"(sc));
}
__device__ __forceinline__ void wgmma_rs_n40_b0(float (&d)[20], uint32_t a0, uint32_t a1, uint32_t a2, uint32_t a3, uint64_t db, int sc) {
  asm volatile("{.reg .pred p; setp.ne.b32 p, %25, 0; wgmma.mma_async.sync.aligned.m64n40k16.f32.bf16.bf16 {%0,%1,%2,%3,%4,%5,%6,%7,%8,%9,%10,%11,%12,%13,%14,%15,%16,%17,%18,%19}, {%20,%21,%22,%23}, %24, p, 1, 1, 0;}"
    : "+f"(d[0]),"+f"(d[1]),"+f"(d[2]),"+f"(d[3]),"+f"(d[4]),"+f"(d[5]),"+f"(d[6]),"+f"(d[7]),"+f"(d[8]),"+f"(d[9]),"+f"(d[10]),"+f"(d[11]),"+f"(d[12]),"+f"(d[13]),"+f"(d[14]),"+f"(d[15]),"+f"(d[16]),"+f"(d[17]),"+f"(d[18]),"+f"(d[19])
    : "r"(a0), "r"(a1), "r"(a2), "r"(a3), "l"(db), "r"(sc));
}
__device__ __forceinline__ void wgmma_ssz_n256_a0b1(float (&d)[128], uint64_t da, uint64_t db) {
  asm volatile("{.reg .pred p; setp.ne.b32 p, 0, 0; wgmma.mma_async.sync.aligned.m64n256k16.f32.bf16.bf16 {%0,%1,%2,%3,%4,%5,%6,%7,%8,%9,%10,%11,%12,%13,%14,%15,%16,%17,%18,%19,%20,%21,%22,%23,%24,%25,%26,%27,%28,%29,%30,%31,%32,%33,%34,%35,%36,%37,%38,%39,%40,%41,%42,%43,%44,%45,%46,%47,%48,%49,%50,%51,%52,%53,%54,%55,%56,%57,%58,%59,%60,%61,%62,%63,%64,%65,%66,%67,%68,%69,%70,%71,%72,%73,%74,%75,%76,%77,%78,%79,%80,%81,%82,%83,%84,%85,%86,%87,%88,%89,%90,%91,%92,%93,%94,%95,%96,%97,%98,%99,%100,%101,%102,%103,%104,%105,%106,%107,%108,%109,%110,%111,%112,%113,%114,%115,%116,%117,%118,%119,%120,%121,%122,%123,%124,%125,%126,%127}, %128, %129, p, 1, 1, 0, 1;}"
    : "=f"(d[0]),"=f"(d[1]),"=f"(d[2]),"=f"(d[3]),"=f"(d[4]),"=f"(d[5]),"=f"(d[6]),"=f"(d[7]),"=f"(d[8]),"=f"(d[9]),"=f"(d[10]),"=f"(d[11]),"=f"(d[12]),"=f"(d[13]),"=f"(d[14]),"=f"(d[15]),"=f"(d[16]),"=f"(d[17]),"=f"(d[18]),"=f"(d[19]),"=f"(d[20]),"=f"(d[21]),"=f"(d[22]),"=f"(d[23]),"=f"(d[24]),"=f"(d[25]),"=f"(d[26]),"=f"(d[27]),"=f"(d[28]),"=f"(d[29]),"=f"(d[30]),"=f"(d[31]),"=f"(d[32]),"=f"(d[33]),"=f"(d[34]),"=f"(d[35]),"=f"(d[36]),"=f"(d[37]),"=f"(d[38]),"=f"(d[39]),"=f"(d[40]),"=f"(d[41]),"=f"(d[42]),"=f"(d[43]),"=f"(d[44]),"=f"(d[45]),"=f"(d[46]),"=f"(d[47]),"=f"(d[48]),"=f"(d[49]),"=f"(d[50]),"=f"(d[51]),"=f"(d[52]),"=f"(d[53]),"=f"(d[54]),"=f"(d[55]),"=f"(d[56]),"=f"(d[57]),"=f"(d[58]),"=f"(d[59]),"=f"(d[60]),"=f"(d[61]),"=f"(d[62]),"=f"(d[63]),"=f"(d[64]),"=f"(d[65]),"=f"(d[66]),"=f"(d[67]),"=f"(d[68]),"=f"(d[69]),"=f"(d[70]),"=f"(d[71]),"=f"(d[72]),"=f"(d[73]),"=f"(d[74]),"=f"(d[75]),"=f"(d[76]),"=f"(d[77]),"=f"(d[78]),"=f"(d[79]),"=f"(d[80]),"=f"(d[81]),"=f"(d[82]),"=f"(d[83]),"=f"(d[84]),"=f"(d[85]),"=f"(d[86]),"=f"(d[87]),"=f"(d[88]),"=f"(d[89]),"=f"(d[90]),"=f"(d[91]),"=f"(d[92]),"=f"(d[93]),"=f"(d[94]),"=f"(d[95]),"=f"(d[96]),"=f"(d[97]),"=f"(d[98]),"=f"(d[99]),"=f"(d[100]),"=f"(d[101]),"=f"(d[102]),"=f"(d[103]),"=f"(d[104]),"=f"(d[105]),"=f"(d[106]),"=f"(d[107]),"=f"(d[108]),"=f"(d[109]),"=f"(d[110]),"=f"(d[111]),"=f"(d[112]),"=f"(d[113]),"=f"(d[114]),"=f"(d[115]),"=f"(d[116]),"=f"(d[117]),"=f"(d[118]),"=f"(d[119]),"=f"(d[120]),"=f"(d[121]),"=f"(d[122]),"=f"(d[123]),"=f"(d[124]),"=f"(d[125]),"=f"(d[126]),"=f"(d[127])
    : "l"(da), "l"(db));
}
__device__ __forceinline__ void wgmma_ssz_n128_a0b1(float (&d)[64], uint64_t da, uint64_t db) {
  asm volatile("{.reg .pred p; setp.ne.b32 p, 0, 0; wgmma.mma_async.sync.aligned.m64n128k16.f32.bf16.bf16 {%0,%1,%2,%3,%4,%5,%6,%7,%8,%9,%10,%11,%12,%13,%14,%15,%16,%17,%18,%19,%20,%21,%22,%23,%24,%25,%26,%27,%28,%29,%30,%31,%32,%33,%34,%35,%36,%37,%38,%39,%40,%41,%42,%43,%44,%45,%46,%47,%48,%49,%50,%51,%52,%53,%54,%55,%56,%57,%58,%59,%60,%61,%62,%63}, %64, %65, p, 1, 1, 0, 1;}"
    : "=f"(d[0]),"=f"(d[1]),"=f"(d[2]),"=f"(d[3]),"=f"(d[4]),"=f"(d[5]),"=f"(d[6]),"=f"(d[7]),"=f"(d[8]),"=f"(d[9]),"=f"(d[10]),"=f"(d[11]),"=f"(d[12]),"=f"(d[13]),"=f"(d[14]),"=f"(d[15]),"=f"(d[16]),"=f"(d[17]),"=f"(d[18]),"=f"(d[19]),"=f"(d[20]),"=f"(d[21]),"=f"(d[22]),"=f"(d[23]),"=f"(d[24]),"=f"(d[25]),"=f"(d[26]),"=f"(d[27]),"=f"(d[28]),"=f"(d[29]),"=f"(d[30]),"=f"(d[31]),"=f"(d[32]),"=f"(d[33]),"=f"(d[34]),"=f"(d[35]),"=f"(d[36]),"=f"(d[37]),"=f"(d[38]),"=f"(d[39]),"=f"(d[40]),"=f"(d[41]),"=f"(d[42]),"=f"(d[43]),"=f"(d[44]),"=f"(d[45]),"=f"(d[46]),"=f"(d[47]),"=f"(d[48]),"=f"(d[49]),"=f"(d[50]),"=f"(d[51]),"=f"(d[52]),"=f"(d[53]),"=f"(d[54]),"=f"(d[55]),"=f"(d[56]),"=f"(d[57]),"=f"(d[58]),"=f"(d[59]),"=f"(d[60]),"=f"(d[61]),"=f"(d[62]),"=f"(d[63])
    : "l"(da), "l"(db));
}


__device__ __forceinline__ void wg_fence() { asm volatile("wgmma.fence.sync.aligned;" ::: "memory"); }
__device__ __forceinline__ void wg_commit() { asm volatile("wgmma.commit_group.sync.aligned;" ::: "memory"); }
template <int N> __device__ __forceinline__ void wg_wait() { asm volatile("wgmma.wait_group.sync.aligned %0;" ::"n"(N) : "memory"); }
template <int N> __device__ __forceinline__ void fence_regs(float (&d)[N]) {
#pragma unroll
  for (int i = 0; i < N; i++) asm volatile("" : "+f"(d[i])::"memory");
}
template <int N> __device__ __forceinline__ void fence_regs(uint32_t (&d)[N]) {
#pragma unroll
  for (int i = 0; i < N; i++) asm volatile("" : "+r"(d[i])::"memory");
}
__device__ __forceinline__ uint64_t mk_desc(uint32_t lo, uint32_t hi) {
  uint64_t d;
  asm("mov.b64 %0, {%1,%2};" : "=l"(d) : "r"(lo), "r"(hi));
  return d;
}
constexpr uint32_t DHI_SW128 = (1024u >> 4) | (1u << 30);
__device__ __forceinline__ uint32_t desc_lo(uint32_t addr, uint32_t lbo) { return ((addr & 0x3FFFF) >> 4) | ((lbo >> 4) << 16); }

__device__ __forceinline__ void mbar_init(uint32_t bar, uint32_t cnt) { asm volatile("mbarrier.init.shared::cta.b64 [%0], %1;" ::"r"(bar), "r"(cnt) : "memory"); }
__device__ __forceinline__ uint32_t mbar_try(uint32_t bar, uint32_t par) {
  uint32_t ok;
  asm volatile("{.reg .pred p; mbarrier.try_wait.parity.shared::cta.b64 p, [%1], %2; selp.u32 %0, 1, 0, p;}" : "=r"(ok) : "r"(bar), "r"(par) : "memory");
  return ok;
}
__device__ __noinline__ void mbar_wait_slow(uint32_t bar, uint32_t par) {
  for (int i = 0; i < (1 << 22); i++)
    if (mbar_try(bar, par)) return;
  __trap();
}
__device__ __forceinline__ void mbar_wait(uint32_t bar, uint32_t par) {
  asm volatile(
      "{\n.reg .pred p;\n.reg .u32 c;\n"
      "mbarrier.try_wait.parity.shared::cta.b64 p, [%0], %1;\n"
      "@p bra DONE;\n"
      "mov.u32 c, 0;\n"
      "LOOP:\n"
      "mbarrier.try_wait.parity.shared::cta.b64 p, [%0], %1;\n"
      "@p bra DONE;\n"
      "add.u32 c, c, 1;\n"
      "setp.lt.u32 p, c, 4000000;\n"
      "@p bra LOOP;\n"
      "trap;\n"
      "DONE:\n}" ::"r"(bar), "r"(par) : "memory");
}
__device__ __forceinline__ void mbar_wait2(uint32_t b0, uint32_t p0, uint32_t b1, uint32_t p1) {
  asm volatile(
      "{\n.reg .pred p, q;\n.reg .u32 c;\n"
      "mov.u32 c, 0;\n"
      "LOOP:\n"
      "mbarrier.try_wait.parity.shared::cta.b64 p, [%0], %1;\n"
      "mbarrier.try_wait.parity.shared::cta.b64 q, [%2], %3;\n"
      "and.pred p, p, q;\n"
      "@p bra DONE;\n"
      "add.u32 c, c, 1;\n"
      "setp.lt.u32 p, c, 4000000;\n"
      "@p bra LOOP;\n"
      "trap;\n"
      "DONE:\n}" ::"r"(b0), "r"(p0), "r"(b1), "r"(p1) : "memory");
}
__device__ __forceinline__ void mbar_wait_cl(uint32_t bar, uint32_t par) {
  asm volatile(
      "{\n.reg .pred p;\n.reg .u32 c;\n"
      "mbarrier.try_wait.parity.acquire.cluster.shared::cta.b64 p, [%0], %1;\n"
      "@p bra DONE;\n"
      "mov.u32 c, 0;\n"
      "LOOP:\n"
      "mbarrier.try_wait.parity.acquire.cluster.shared::cta.b64 p, [%0], %1;\n"
      "@p bra DONE;\n"
      "add.u32 c, c, 1;\n"
      "setp.lt.u32 p, c, 4000000;\n"
      "@p bra LOOP;\n"
      "trap;\n"
      "DONE:\n}" ::"r"(bar), "r"(par) : "memory");
}
__device__ __forceinline__ void mbar_arrive(uint32_t bar) { asm volatile("mbarrier.arrive.shared::cta.b64 _, [%0];" ::"r"(bar) : "memory"); }
__device__ __forceinline__ void mbar_arrive_cl(uint32_t bar) { asm volatile("mbarrier.arrive.shared::cluster.b64 _, [%0];" ::"r"(bar) : "memory"); }
__device__ __forceinline__ void mbar_expect(uint32_t bar, uint32_t bytes) { asm volatile("mbarrier.arrive.expect_tx.shared::cta.b64 _, [%0], %1;" ::"r"(bar), "r"(bytes) : "memory"); }
__device__ __forceinline__ void mbar_expect_cl(uint32_t bar, uint32_t bytes) { asm volatile("mbarrier.arrive.expect_tx.shared::cluster.b64 _, [%0], %1;" ::"r"(bar), "r"(bytes) : "memory"); }
__device__ __forceinline__ uint32_t mapa(uint32_t addr, uint32_t rank) {
  uint32_t r;
  asm("mapa.shared::cluster.u32 %0, %1, %2;" : "=r"(r) : "r"(addr), "r"(rank));
  return r;
}
__device__ __forceinline__ void st_async32(uint32_t addr, uint32_t v, uint32_t bar) {
  asm volatile("st.async.shared::cluster.mbarrier::complete_tx::bytes.b32 [%0], %1, [%2];" ::"r"(addr), "r"(v), "r"(bar) : "memory");
}
__device__ __forceinline__ void st_async64(uint32_t addr, uint32_t a, uint32_t b, uint32_t bar) {
  asm volatile("st.async.shared::cluster.mbarrier::complete_tx::bytes.v2.b32 [%0], {%1,%2}, [%3];" ::"r"(addr), "r"(a), "r"(b), "r"(bar) : "memory");
}
__device__ __forceinline__ void st_async128(uint32_t addr, uint32_t a, uint32_t b, uint32_t c, uint32_t d, uint32_t bar) {
  asm volatile("st.async.shared::cluster.mbarrier::complete_tx::bytes.v4.b32 [%0], {%1,%2,%3,%4}, [%5];" ::"r"(addr), "r"(a), "r"(b), "r"(c), "r"(d), "r"(bar) : "memory");
}
__device__ __forceinline__ void bar_sync(int id, int n) { asm volatile("bar.sync %0, %1;" ::"r"(id), "r"(n) : "memory"); }
__device__ __forceinline__ void bar_arrive(int id, int n) { asm volatile("bar.arrive %0, %1;" ::"r"(id), "r"(n) : "memory"); }
__device__ __forceinline__ void cluster_sync() { asm volatile("barrier.cluster.arrive.aligned;\nbarrier.cluster.wait.aligned;" ::: "memory"); }
__device__ __forceinline__ bool elect() {
  uint32_t p;
  asm volatile("{.reg .pred q; elect.sync _|q, 0xffffffff; selp.u32 %0, 1, 0, q;}" : "=r"(p));
  return p != 0;
}
__device__ __forceinline__ void fence_async_smem() { asm volatile("fence.proxy.async.shared::cta;" ::: "memory"); }
__device__ __forceinline__ void fence_async_all() { asm volatile("fence.proxy.async;" ::: "memory"); }
__device__ __forceinline__ void tma2d(uint32_t dst, const CUtensorMap* m, int c0, int c1, uint32_t bar) {
  asm volatile("cp.async.bulk.tensor.2d.shared::cluster.global.mbarrier::complete_tx::bytes [%0], [%1, {%2,%3}], [%4];" ::"r"(dst), "l"(m), "r"(c0), "r"(c1), "r"(bar) : "memory");
}
__device__ __forceinline__ void tma2d_mc(uint32_t dst, const CUtensorMap* m, int c0, int c1, uint32_t bar, uint16_t mask) {
  asm volatile("cp.async.bulk.tensor.2d.shared::cluster.global.mbarrier::complete_tx::bytes.multicast::cluster [%0], [%1, {%2,%3}], [%4], %5;" ::"r"(dst), "l"(m), "r"(c0), "r"(c1), "r"(bar), "h"(mask) : "memory");
}
__device__ __forceinline__ void tma3d(uint32_t dst, const CUtensorMap* m, int c0, int c1, int c2, uint32_t bar) {
  asm volatile("cp.async.bulk.tensor.3d.shared::cluster.global.mbarrier::complete_tx::bytes [%0], [%1, {%2,%3,%4}], [%5];" ::"r"(dst), "l"(m), "r"(c0), "r"(c1), "r"(c2), "r"(bar) : "memory");
}
__device__ __forceinline__ void tma3d_mc(uint32_t dst, const CUtensorMap* m, int c0, int c1, int c2, uint32_t bar, uint16_t mask) {
  asm volatile("cp.async.bulk.tensor.3d.shared::cluster.global.mbarrier::complete_tx::bytes.multicast::cluster [%0], [%1, {%2,%3,%4}], [%5], %6;" ::"r"(dst), "l"(m), "r"(c0), "r"(c1), "r"(c2), "r"(bar), "h"(mask) : "memory");
}
__device__ __forceinline__ uint32_t ld_acquire(const unsigned* p) {
  uint32_t v;
  asm volatile("ld.acquire.gpu.global.u32 %0, [%1];" : "=r"(v) : "l"(p) : "memory");
  return v;
}
__device__ __forceinline__ uint32_t pack_bf16(float lo, float hi) {
  uint32_t r;
  asm("cvt.rn.bf16x2.f32 %0, %1, %2;" : "=r"(r) : "f"(hi), "f"(lo));
  return r;
}
__device__ __forceinline__ float ex2(float x) {
  float y;
  asm("ex2.approx.ftz.f32 %0, %1;" : "=f"(y) : "f"(x));
  return y;
}
__device__ __forceinline__ float rcp(float x) {
  float y;
  asm("rcp.approx.ftz.f32 %0, %1;" : "=f"(y) : "f"(x));
  return y;
}
__device__ __forceinline__ void stg128(void* p, uint32_t a, uint32_t b, uint32_t c, uint32_t d) {
  asm volatile("st.global.v4.b32 [%0], {%1,%2,%3,%4};" ::"l"(p), "r"(a), "r"(b), "r"(c), "r"(d) : "memory");
}
__device__ __forceinline__ void sts128(uint32_t a, uint32_t x, uint32_t y, uint32_t z, uint32_t w) {
  asm volatile("st.shared.v4.b32 [%0], {%1,%2,%3,%4};" ::"r"(a), "r"(x), "r"(y), "r"(z), "r"(w) : "memory");
}
__device__ __forceinline__ void stsm4(uint32_t a, uint32_t r0, uint32_t r1, uint32_t r2, uint32_t r3) {
  asm volatile("stmatrix.sync.aligned.m8n8.x4.shared.b16 [%0], {%1,%2,%3,%4};" ::"r"(a), "r"(r0), "r"(r1), "r"(r2), "r"(r3) : "memory");
}
__device__ __forceinline__ void arrive_elect(uint32_t bar) {
  asm volatile("{.reg .pred q; elect.sync _|q, 0xffffffff; @q mbarrier.arrive.shared::cta.b64 _, [%0];}" ::"r"(bar) : "memory");
}
__device__ __forceinline__ void sched_fence(uint32_t v) { asm volatile("{.reg .pred p; setp.eq.u32 p, %0, 0; @p trap;}" ::"r"(v) : "memory"); }
template <int V> struct IC { static constexpr int value = V; };
template <int A, int B, class F> __device__ __forceinline__ void static_for(F&& f) {
  if constexpr (A < B) {
    f(IC<A>());
    static_for<A + 1, B>(f);
  }
}
__device__ __forceinline__ uint32_t lds32(uint32_t a) {
  uint32_t v;
  asm volatile("ld.shared.b32 %0, [%1];" : "=r"(v) : "r"(a) : "memory");
  return v;
}

constexpr int MAXTASK = 256 + 256 + 200;
constexpr int T_KV = 0, T_FA = 1, T_OA = 2, T_OB = 3, T_MA = 4, T_MB = 5;
constexpr uint32_t TASK_END = 0xFFFF;
constexpr int NCL = 34;
struct MainParams {
  CUtensorMap ckv, wuk, wuv, ax, wq, scr, woa, wob, scr_st, out_st, woa2, wob2;
  uint32_t ntask;
  uint16_t tasks[MAXTASK];
};

constexpr int M_GR = 16384, M_NG = 12;
constexpr int M_STG = M_GR * M_NG;
constexpr int M_BAR = M_STG + 32768;
constexpr int M_FULL = M_BAR, M_EMPTY = M_BAR + 64, M_TFULL = M_BAR + 128, M_TEMPTY = M_BAR + 160, M_EPI = M_BAR + 192, M_SFREE = M_BAR + 224, M_GO = M_BAR + 240,
              M_TSLOT = M_BAR + 256;
constexpr int M_SMEM = M_BAR + 512 + 1024;
constexpr int OX_TARGET = 64;

#ifndef PF_ON
#define PF_ON 0
#endif
#ifndef ST_ROWS
#define ST_ROWS 16
#endif
#ifndef ST_DEPTH
#define ST_DEPTH 1
#endif
#ifndef KV_SKEW
#define KV_SKEW 7
#endif
#ifndef FM_NJ
#define FM_NJ 2
#endif
#ifndef Q_SKEW
#define Q_SKEW 6
#endif
struct Ring {
  uint32_t e, g;
  __device__ __forceinline__ uint32_t take(int z) {
    if (g + z > M_NG) g = 0;
    const uint32_t r = g;
    g += z;
    return r;
  }
  __device__ __forceinline__ uint32_t bar() const { return (e & 7) * 8; }
  __device__ __forceinline__ uint32_t par() const { return (e >> 3) & 1; }
};
__device__ __forceinline__ int task_entries(int type, int p) { return type == T_KV ? 9 : type == T_FA ? 9 + 2 * (2 * p + 2) : 65; }
__device__ __forceinline__ int entry_size(int type, int it) { return type == T_FA || (type == T_KV && it == 8) || type >= T_MA ? 2 : 3; }

__device__ __forceinline__ void need_flag(uint32_t& v, int bit, const unsigned* flag, unsigned target) {
  for (int it = 0; !((__ballot_sync(0xffffffffu, v >= target) >> bit) & 1); it++) {
    if (it > (1 << 21)) __trap();
    if (it) __nanosleep(40);
    v = ld_acquire(flag);
  }
}

constexpr float SM_C = 0.08838834764831845f * 1.4426950408889634f;
template <int NJ> __device__ __forceinline__ void softmax_max(const float (&s)[64], float& m0, float& m1, float& a0, float& a1, float& c0, float& c1) {
  float x0 = fmaxf(s[0], s[4]), y0 = fmaxf(s[1], s[5]), x1 = fmaxf(s[2], s[6]), y1 = fmaxf(s[3], s[7]);
#pragma unroll
  for (int j = 2; j < NJ; j++) {
    x0 = fmaxf(x0, s[4 * j]);
    y0 = fmaxf(y0, s[4 * j + 1]);
    x1 = fmaxf(x1, s[4 * j + 2]);
    y1 = fmaxf(y1, s[4 * j + 3]);
  }
  x0 = fmaxf(x0, y0);
  x1 = fmaxf(x1, y1);
  x0 = fmaxf(x0, __shfl_xor_sync(0xffffffffu, x0, 1));
  x1 = fmaxf(x1, __shfl_xor_sync(0xffffffffu, x1, 1));
  x0 = fmaxf(x0, __shfl_xor_sync(0xffffffffu, x0, 2));
  x1 = fmaxf(x1, __shfl_xor_sync(0xffffffffu, x1, 2));
  const float n0 = fmaxf(m0, x0), n1 = fmaxf(m1, x1);
  a0 = ex2((m0 - n0) * SM_C);
  a1 = ex2((m1 - n1) * SM_C);
  m0 = n0;
  m1 = n1;
  c0 = -n0 * SM_C;
  c1 = -n1 * SM_C;
}
template <int J0, int J1> __device__ __forceinline__ void softmax_exp(const float (&s)[64], uint32_t (&p)[32], float c0, float c1, float (&t)[4]) {
#pragma unroll
  for (int j = J0; j < J1; j++) {
    const float e0 = ex2(fmaf(s[4 * j], SM_C, c0)), e1 = ex2(fmaf(s[4 * j + 1], SM_C, c0));
    const float e2 = ex2(fmaf(s[4 * j + 2], SM_C, c1)), e3 = ex2(fmaf(s[4 * j + 3], SM_C, c1));
    p[2 * j] = pack_bf16(e0, e1);
    p[2 * j + 1] = pack_bf16(e2, e3);
    if (j == 0) { t[0] = e0; t[1] = e1; t[2] = e2; t[3] = e3; }
    else { t[0] += e0; t[1] += e1; t[2] += e2; t[3] += e3; }
  }
}
template <int I0, int I1> __device__ __forceinline__ void fence_part(uint32_t (&d)[32]) {
#pragma unroll
  for (int i = I0; i < I1; i++) asm volatile("" : "+r"(d[i])::"memory");
}
template <int J0, int J1, int N> __device__ __forceinline__ void stage_tile(const float (&d)[N], uint32_t a, float f0, float f1) {
#pragma unroll
  for (int j = J0; j < J1; j += 2)
    stsm4((a ^ (((j - J0) & 7) << 4)) + ((j - J0) >> 3) * 8192, pack_bf16(d[4 * j] * f0, d[4 * j + 1] * f0), pack_bf16(d[4 * j + 2] * f1, d[4 * j + 3] * f1),
          pack_bf16(d[4 * j + 4] * f0, d[4 * j + 5] * f0), pack_bf16(d[4 * j + 6] * f1, d[4 * j + 7] * f1));
}
template <int J0, int J1> __device__ __forceinline__ void causal_mask(float (&s)[64], int lim0) {
#pragma unroll
  for (int j = J0; j < J1; j++) {
    if (8 * j > lim0) s[4 * j] = -INFINITY;
    if (8 * j + 1 > lim0) s[4 * j + 1] = -INFINITY;
    if (8 * j > lim0 + 8) s[4 * j + 2] = -INFINITY;
    if (8 * j + 1 > lim0 + 8) s[4 * j + 3] = -INFINITY;
  }
}

__global__ void __cluster_dims__(2, 1, 1) __launch_bounds__(384, 1) main_kernel(const __grid_constant__ MainParams P) {
  extern __shared__ uint8_t smem_raw[];
  const uint32_t sb = ((uint32_t)__cvta_generic_to_shared(smem_raw) + 1023u) & ~1023u;
  const int warp = __shfl_sync(0xffffffffu, threadIdx.x >> 5, 0), lane = threadIdx.x & 31;
  uint32_t rank;
  asm("mov.u32 %0, %%cluster_ctarank;" : "=r"(rank));
  rank = __shfl_sync(0xffffffffu, rank, 0);
#ifdef DEV_TRACE
  if (threadIdx.x == 0) { long long c; asm volatile("mov.u64 %0, %%globaltimer;" : "=l"(c)); g_trace[blockIdx.x * 4096 + 4090] = c; }
#endif
  const uint32_t cluster = blockIdx.x >> 1;
  static_assert(M_EMPTY == M_FULL + 64 && M_TFULL == M_FULL + 128 && M_TEMPTY == M_FULL + 160 && M_EPI == M_FULL + 192 && M_SFREE == M_FULL + 224, "barriers");
  if (warp == 8 && elect()) {
#pragma unroll 1
    for (int i = 0; i < 4; i++) {
      const uint32_t st = sb + i * 3 * M_GR, fb = sb + M_FULL + 8 * i;
      mbar_init(fb, 1);
      mbar_expect(fb, 49152);
      tma2d(st, &P.ckv, i * 64, (cluster & 7) * 256 + rank * 128, fb);
      tma3d(st + 16384, &P.wuk, 0, i * 64, (cluster >> 3) * 2, fb);
      tma3d(st + 32768, &P.wuv, 0, i * 64, (cluster >> 3) * 2, fb);
    }
    asm volatile("fence.mbarrier_init.release.cluster;" ::: "memory");
  }
  const uint32_t task0 = cluster;
  if (warp >= 1 && warp < 8 && elect()) {
    const uint32_t b = sb + M_FULL + 32 * warp, cnt = (warp & 14) == 2 ? 16 : warp == 5 ? 22 : warp == 6 ? 4 : 1;
#pragma unroll
    for (int i = 0; i < 4; i++) mbar_init(b + 8 * i, cnt);
    asm volatile("fence.mbarrier_init.release.cluster;" ::: "memory");
  }
  __syncwarp();
  if (warp == 8) TRM(5);
  asm volatile("barrier.cluster.arrive.relaxed.aligned;" ::: "memory");
  auto started = [&]() { asm volatile("barrier.cluster.wait.aligned;" ::: "memory"); };
  const uint32_t tempty0 = mapa(sb + M_TEMPTY, 0);
  auto read_task = [&](int ti) -> uint32_t {
    if (ti == 0) return task0;
    mbar_wait(sb + M_TFULL + 8 * ((ti - 1) & 3), ((ti - 1) >> 2) & 1);
    return __shfl_sync(0xffffffffu, lds32(sb + M_TSLOT + 4 * ((ti - 1) & 3)), 0);
  };
  auto free_task = [&](int ti) {
    if (ti > 0 && lane == 0) mbar_arrive_cl(tempty0 + 8 * ((ti - 1) & 3));
  };

  if (warp >= 8) {
    asm volatile("setmaxnreg.dec.sync.aligned.u32 40;");
    if (warp == 8) {
      if (lane >= 3 && lane < 12) asm volatile("prefetch.tensormap [%0];" ::"l"(&P.ckv + lane) : "memory");
      __syncwarp();
      started();
      TRM(4);
      Ring r{0, 0};
      uint32_t lin = 0;
      uint32_t mypos = 0, mypar = 2;
      const uint32_t myempty = sb + M_EMPTY + 8 * (lane & 7);
      auto alloc = [&](int z, uint32_t& fb) -> uint32_t {
        if (r.g + z > M_NG) lin += M_NG - r.g;
        const uint32_t st = sb + r.take(z) * M_GR;
        const uint32_t need = mypar < 2 && lin + z - mypos > M_NG;
        for (int it = 0;; it++) {
          uint32_t ok;
          asm volatile("{.reg .pred p, q; setp.eq.u32 q, %3, 0; mov.pred p, q; @!q mbarrier.try_wait.parity.shared::cta.b64 p, [%1], %2; selp.u32 %0, 1, 0, p;}"
                       : "=r"(ok) : "r"(myempty), "r"(mypar), "r"(need) : "memory");
          if (__all_sync(0xffffffffu, ok)) break;
          if (it > 4000000) __trap();
        }
        mypar = need ? 2 : mypar;
        if (lane == (r.e & 7)) { mypos = lin; mypar = r.par(); }
        lin += z;
        fb = sb + M_FULL + r.bar();
        r.e++;
        return st;
      };
      auto go = [&]() { if (rank == 0) arrive_elect(sb + M_GO); };
      for (int ti = 0;; ti++) {
        const uint32_t task = read_task(ti);
        free_task(ti);
        if (task == TASK_END) break;
        const int type = task >> 12, nn = (task >> 8) & 15, h = (task >> 3) & 31, p = task & 7;
        uint32_t fb, fv = 0;
        if (type == T_KV) {
          const CUtensorMap* w = rank ? &P.wuv : &P.wuk;
          const int row = p * 256 + rank * 128;
#pragma unroll 1
          for (int k = 0; k < 512; k += 64) {
            const uint32_t st = alloc(3, fb);
            if ((ti > 0 || k >= 256) && elect()) {
              mbar_expect(fb, 49152);
              tma2d(st, &P.ckv, k, row, fb);
              tma3d_mc(st + 16384 + rank * 16384, w, 0, k, h * 2, fb, 3);
            }
            if (k == 384) go();
            if (PF_ON && ti == 0 && h < 4 && k == 192 && elect()) {
              asm volatile("cp.async.bulk.prefetch.tensor.3d.L2.global [%0, {0,%1,%2}];" ::"l"(w), "r"(p * 64), "r"((h + 4) * 2) : "memory");
              if (h == 0) asm volatile("cp.async.bulk.prefetch.tensor.3d.L2.global [%0, {0,%1,%2}];" ::"l"(w), "r"(p * 64), "r"(16) : "memory");
            }
            if (PF_ON && ti == 1 && h < 8 && k >= 192 && elect()) {
              const int c = (k - 192) / 32 + rank;
              if (c < 9) asm volatile("cp.async.bulk.prefetch.tensor.2d.L2.global [%0, {%1,%2}];" ::"l"(&P.ax), "r"(c * 64), "r"(p * 256 + (h & 3) * 64) : "memory");
              if (k == 192) asm volatile("cp.async.bulk.prefetch.tensor.2d.L2.global [%0, {%1,%2}];" ::"l"(&P.wq), "r"((h & 3) * 128 + rank * 64), "r"(p * 64) : "memory");
            }
            __syncwarp();
          }
          alloc(2, fb);
          arrive_elect(fb);
        } else if (type == T_FA) {
          const unsigned* flag = g_sync + SY_KV + h * 8 + (lane & 7);
          asm volatile("ld.relaxed.gpu.global.u32 %0, [%1];" : "=r"(fv) : "l"(flag) : "memory");
          const int r0 = p * 256 + rank * 64, r1 = p * 256 + 192 - rank * 64, col = h * 128 + rank * 64;
#pragma unroll 1
          for (int k = 0; k < 576; k += 64) {
            const uint32_t st = alloc(2, fb);
            if (elect()) {
              mbar_expect(fb, 32768);
              tma2d(st, &P.ax, k, r0, fb);
              tma2d(st + 8192, &P.ax, k, r1, fb);
              tma2d_mc(st + 16384 + rank * 8192, &P.wq, col, k, fb, 3);
            }
          }
          auto kv = [&](int row) {
            const uint32_t st = alloc(2, fb);
            if (elect()) {
              mbar_expect(fb, 32768);
              tma2d_mc(st + rank * 16384, &P.scr, col, row, fb, 3);
            }
          };
          need_flag(fv, p, flag, 4);
          kv((2 * p + 1) * 128);
#pragma unroll 1
          for (int j = 2 * p; j >= 0; j--) {
            need_flag(fv, j >> 1, flag, 4);
            if (j == 0) go();
            kv(j * 128);
            kv(SEQ + (j + 1) * 128);
          }
          kv(SEQ);
        } else {
          const int part = type & 1;
          const unsigned* flag = g_sync + (part ? SY_OX + 2 * p + 1 : SY_CTX + p * 32 + lane);
          const unsigned target = part ? OX_TARGET : 4;
          const int row = (2 + part) * SEQ + p * 256 + rank * 128;
          const int nch = type >= T_MA ? 2 : 3;
          const CUtensorMap* w = &P.woa + part + (type >= T_MA ? 4 : 0);
#pragma unroll 1
          for (int k = 0; k < HDALL; k += 64) {
            need_flag(fv, k >> 7, flag, target);
            const uint32_t st = alloc(nch, fb);
            if (elect()) {
              mbar_expect(fb, 16384 + nch * 8192);
              tma2d(st, &P.scr, k, row, fb);
              tma3d_mc(st + 16384 + rank * nch * 4096, w, 0, k + rank * 32, nn * nch, fb, 3);
            }
            if (k == HDALL - 192) go();
          }
          alloc(nch, fb);
          arrive_elect(fb);
        }
      }
    } else if (warp == 9) {
      started();
      TRM(0);
      if (rank == 0) {
        for (int ti = 0;; ti++) {
          uint32_t q = 0;
          mbar_wait(sb + M_GO, ti & 1);
          if (lane == 0) q = atomicAdd(&g_sync[SY_Q], 1u);
          q = __shfl_sync(0xffffffffu, q, 0);
          if (ti == 0 && q < 100000) TRM(1);
          const uint32_t t = q < P.ntask ? (uint32_t)P.tasks[q] : TASK_END;
          if (ti == 0 && t < 100000) TRM(2);
          mbar_wait(sb + M_TEMPTY + 8 * (ti & 3), ((ti >> 2) & 1) ^ 1);
          if (lane < 2) {
            const uint32_t b = mapa(sb + M_TFULL + 8 * (ti & 3), lane);
            mbar_expect_cl(b, 4);
            st_async32(mapa(sb + M_TSLOT + 4 * (ti & 3), lane), t, b);
          }
          __syncwarp();
          if (t == TASK_END) break;
        }
      }
    } else {
      const int wg = warp - 10;
      const uint32_t emptyx = mapa(sb + M_EMPTY, lane & 1);
      Ring r{0, 0};
      int lead = wg;
      started();
      for (int ti = 0;; ti++) {
        const int sl = ti & 1;
        const uint32_t task = read_task(ti);
        const int type = task >> 12, nn = (task >> 8) & 15, h = (task >> 3) & 31, p = task & 7;
        if (task != TASK_END) {
          const int nit = task_entries(type, p);
          uint32_t st = 0;
          for (int it = 0; it < nit; it++) st = r.take(entry_size(type, it));
          r.e += nit - 1;
          int row = p * 256 + rank * 128 + wg * 64;
          if (type == T_FA) {
            row = 2 * SEQ + p * 256 + (lead ? 3 - (int)rank : (int)rank) * 64;
            lead ^= 1;
          }
          mbar_wait(sb + M_EPI + 8 * (sl * 2 + wg), (ti >> 1) & 1);
          auto store = [&](const CUtensorMap* m, uint32_t src, int r0, int c0, int n32, bool fast = true) {
            if (lane == 0) {
#pragma unroll 1
              for (int i = 0; i < n32 * (32 / ST_ROWS); i++) {
                asm volatile("cp.async.bulk.tensor.2d.global.shared::cta.bulk_group [%0, {%1,%2}], [%3];" ::"l"(m), "r"((c0 + i / (64 / ST_ROWS)) * 64), "r"(r0 + i % (64 / ST_ROWS) * ST_ROWS), "r"(src + i * ST_ROWS * 128) : "memory");
                asm volatile("cp.async.bulk.commit_group;" ::: "memory");
                if (fast) asm volatile("cp.async.bulk.wait_group.read %0;" ::"n"(ST_DEPTH) : "memory");
                else asm volatile("cp.async.bulk.wait_group.read 0;" ::: "memory");
              }
              asm volatile("cp.async.bulk.wait_group.read 0;" ::: "memory");
            }
            __syncwarp();
          };
          if (type != T_FA) {
            if (type == T_KV) store(&P.scr_st, sb + st * M_GR + wg * 16384, SEQ + row, h * 2, 4);
            else if (type < T_MA) store(&P.out_st, sb + st * M_GR + wg * 24576, row, (type & 1) * 9 + nn * 3, 6);
            else store(&P.out_st, sb + st * M_GR + wg * 16384, row, (type & 1) * 9 + nn * 2, 4);
            if (lane < 2) asm volatile("mbarrier.arrive.shared::cluster.b64 _, [%0], 4;" ::"r"(emptyx + r.bar()) : "memory");
          }
          r.e++;
          if (type <= T_FA) store(&P.scr_st, sb + M_STG + wg * 16384, row, h * 2, 4, false);
          if (lane == 0) mbar_arrive(sb + M_SFREE + 8 * wg);
          if (lane == 0) {
            asm volatile("cp.async.bulk.wait_group 0;" ::: "memory");
            if (type <= T_FA) {
              __threadfence();
              atomicAdd(type == T_KV ? &g_sync[SY_KV + h * 8 + p] : &g_sync[SY_CTX + p * 32 + h], 1u);
            }
          }
        }
        __syncwarp();
        free_task(ti);
        if (task == TASK_END) break;
      }
    }
    __syncwarp();
    cluster_sync();
    if (threadIdx.x == 288) TRE(256 + blockIdx.x);
    if (warp == 9) {
      uint32_t old = 0;
      if (lane == 0) {
        __threadfence();
        old = atomicAdd(&g_sync[SY_EXIT], 1u);
        __threadfence();
      }
      if (__shfl_sync(0xffffffffu, old, 0) == gridDim.x - 1) {
        asm volatile("griddepcontrol.wait;" ::: "memory");
        for (int i = lane; i < SY_N; i += 32) g_sync[i] = 0;
      }
    }
  } else {
    asm volatile("setmaxnreg.inc.sync.aligned.u32 232;");
    if (warp == 0) TRM(3);
    const int wg = warp >> 2, w4 = warp & 3, g = lane >> 2, t4 = lane & 3;
    const uint32_t emptyx = mapa(sb + M_EMPTY, lane & 1);
    Ring r{0, 0};
    int lead = wg;
    auto release = [&](uint32_t bar) {
      if (lane < 2) mbar_arrive_cl(emptyx + bar);
    };
    auto acquire = [&](int z, uint32_t& bar) -> uint32_t {
      bar = r.bar();
      mbar_wait(sb + M_FULL + bar, r.par());
      r.e++;
      return sb + r.take(z) * M_GR;
    };
    const uint32_t sa = (w4 * 16 + ((lane >> 3) & 1) * 8 + (lane & 7)) * 128 + (((lane >> 4) ^ (lane & 7)) << 4);
    uint32_t ntask = task0;
    started();
    for (int ti = 0;; ti++) {
      const int sl = ti & 1;
      const uint32_t task = ntask;
      if (task == TASK_END) break;
      auto next_task = [&]() { ntask = read_task(ti + 1); free_task(ti + 1); };
      const int type = task >> 12, p = task & 7;
#ifdef DEV_TRACE
      if (w4 == 0 && lane == 0 && ti < 250) { long long c; asm volatile("mov.u64 %0, %%globaltimer;" : "=l"(c)); g_trace[blockIdx.x * 4096 + ti * 8 + wg * 4] = c; g_trace[blockIdx.x * 4096 + ti * 8 + wg * 4 + 2] = task; g_trace[blockIdx.x * 4096 + ti * 8 + wg * 4 + 3] = clock64(); }
#endif
      if (type == T_KV) {
        float acc[128];
        uint32_t prev;
        {
          const uint32_t st = acquire(3, prev);
          if (ti == 0 && warp == 0) TRM(6);
          const uint32_t a = desc_lo(st + wg * 8192, 16), b = desc_lo(st + 16384, 8192);
          wg_fence();
          wgmma_ssz_n256_a0b1(acc, mk_desc(a, DHI_SW128), mk_desc(b, DHI_SW128));
#pragma unroll
          for (int kk = 1; kk < 4; kk++) wgmma_ss_n256_a0b1(acc, mk_desc(a + kk * 2, DHI_SW128), mk_desc(b + kk * 128, DHI_SW128), 1);
          wg_commit();
        }
#pragma unroll 1
        for (int kb = 1; kb < 8; kb++) {
          uint32_t bar;
          const uint32_t st = acquire(3, bar);
          const uint32_t a = desc_lo(st + wg * 8192, 16), b = desc_lo(st + 16384, 8192);
          if (KV_SKEW < 8 && kb == KV_SKEW && !lead) {
            wg_wait<0>();
            release(prev);
            bar_sync(5, 256);
          }
          wg_fence();
#pragma unroll
          for (int kk = 0; kk < 4; kk++) wgmma_ss_n256_a0b1(acc, mk_desc(a + kk * 2, DHI_SW128), mk_desc(b + kk * 128, DHI_SW128), 1);
          wg_commit();
          if (KV_SKEW < 8 && kb == 7 && lead) bar_arrive(5, 256);
          if (KV_SKEW < 8 && kb == KV_SKEW && !lead) { prev = bar; continue; }
          wg_wait<1>();
          release(prev);
          prev = bar;
        }
        if (ti == 0 && warp == 0) TRM(7);
        next_task();
        uint32_t bar;
        const uint32_t st = acquire(2, bar);
        mbar_wait(sb + M_SFREE + 8 * wg, (ti & 1) ^ 1);
        wg_wait<0>();
        release(prev);
        fence_regs(acc);
        stage_tile<16, 32>(acc, st + wg * 16384 + sa, 1.f, 1.f);
        stage_tile<0, 16>(acc, sb + M_STG + wg * 16384 + sa, 1.f, 1.f);
        fence_async_smem();
        __syncwarp();
        arrive_elect(sb + M_EPI + 8 * (sl * 2 + wg));
      } else if (type == T_FA) {
        const int lng = lead;
        lead ^= 1;
        const int grp = lng ? 3 - (int)rank : (int)rank;
        const int n = 2 * p + 1 + lng;
        float s[64], o[64];
        uint32_t pr[32], q[32];
        TRF(0);
        {
          uint32_t prev;
          {
            const uint32_t st = acquire(2, prev);
            const uint32_t a = desc_lo(st + lng * 8192, 16), b = desc_lo(st + 16384, 8192);
            wg_fence();
            wgmma_ssz_n128_a0b1(s, mk_desc(a, DHI_SW128), mk_desc(b, DHI_SW128));
#pragma unroll
            for (int kk = 1; kk < 4; kk++) wgmma_ss_n128_a0b1(s, mk_desc(a + kk * 2, DHI_SW128), mk_desc(b + kk * 128, DHI_SW128), 1);
            wg_commit();
          }
#pragma unroll 1
          for (int kb = 1; kb < 9; kb++) {
            uint32_t bar;
            if (kb == 1) TRF(8);
            if (kb == 5) TRF(9);
            const uint32_t st = acquire(2, bar);
            const uint32_t a = desc_lo(st + lng * 8192, 16), b = desc_lo(st + 16384, 8192);
            const bool hold = kb == Q_SKEW && !lng;
            if (hold) {
              wg_wait<0>();
              release(prev);
              bar_sync(5, 256);
            }
            wg_fence();
#pragma unroll
            for (int kk = 0; kk < 4; kk++) wgmma_ss_n128_a0b1(s, mk_desc(a + kk * 2, DHI_SW128), mk_desc(b + kk * 128, DHI_SW128), 1);
            wg_commit();
            if (Q_SKEW < 9 && kb == 8 && lng) bar_arrive(5, 256);
            if (hold) { prev = bar; continue; }
            wg_wait<1>();
            release(prev);
            prev = bar;
          }
#pragma unroll
          for (int i = 0; i < 64; i++) o[i] = 0.f;
          wg_wait<0>();
          release(prev);
          fence_regs(s);
#pragma unroll
          for (int i = 0; i < 32; i++) q[i] = pack_bf16(s[2 * i], s[2 * i + 1]);
        }
        TRF(1);
        const int lim0 = (grp & 1) * 64 + w4 * 16 + g - 2 * t4;
        float m0 = -INFINITY, m1 = -INFINITY, l0 = 0.f, l1 = 0.f;
        auto issue_s = [&](uint32_t st) {
          const uint32_t b = desc_lo(st, 16);
#pragma unroll
          for (int kk = 0; kk < 8; kk++) wgmma_rs_n128_b0(s, q[4 * kk], q[4 * kk + 1], q[4 * kk + 2], q[4 * kk + 3], mk_desc(b + (kk >> 2) * 1024 + (kk & 3) * 2, DHI_SW128), kk);
          wg_commit();
        };
        auto issue_pv = [&](uint32_t st) {
          const uint32_t b = desc_lo(st, 16384);
#pragma unroll
          for (int kk = 0; kk < 8; kk++) {
            wgmma_rs_n128_b1(o, pr[4 * kk], pr[4 * kk + 1], pr[4 * kk + 2], pr[4 * kk + 3], mk_desc(b + kk * 128, DHI_SW128), 1);
            if (kk == 1 || kk == 3 || kk == 7) wg_commit();
          }
        };
        auto skip = [&]() {
          uint32_t bar;
          acquire(2, bar);
          release(bar);
        };
        const bool half = !(grp & 1);
        float t[4];
        auto first = [&]() {
          float a0, a1, c0, c1;
          uint32_t kb;
          const uint32_t kst = acquire(2, kb);
          if (!lng) bar_sync(1 + wg, 256);
          fence_regs(q);
          fence_regs(s);
          if (half) {
            const uint32_t b = desc_lo(kst, 16);
            wg_fence();
#pragma unroll
            for (int kk = 0; kk < 8; kk++) wgmma_rs_n64_b0(reinterpret_cast<float(&)[32]>(s), q[4 * kk], q[4 * kk + 1], q[4 * kk + 2], q[4 * kk + 3], mk_desc(b + (kk >> 2) * 1024 + (kk & 3) * 2, DHI_SW128), kk);
            wg_commit();
            bar_arrive(2 - wg, 256);
            wg_wait<0>();
            fence_regs(s);
            causal_mask<0, 8>(s, lim0);
          } else {
            wg_fence();
            issue_s(kst);
            bar_arrive(2 - wg, 256);
            wg_wait<0>();
            fence_regs(s);
            causal_mask<8, 16>(s, lim0);
          }
          release(kb);
          TRF(2);
          softmax_max<FM_NJ>(s, m0, m1, a0, a1, c0, c1);
          softmax_exp<0, 8>(s, pr, c0, c1, t);
          if (half) {
#pragma unroll
            for (int i = 16; i < 32; i++) pr[i] = 0;
          } else {
            softmax_exp<8, 16>(s, pr, c0, c1, t);
          }
        };
        auto block = [&]() {
          const uint32_t kb = r.bar(), kp = r.par(), kst = sb + r.take(2) * M_GR;
          r.e++;
          const uint32_t vb = r.bar(), vp = r.par(), vst = sb + r.take(2) * M_GR;
          r.e++;
          mbar_wait2(sb + M_FULL + kb, kp, sb + M_FULL + vb, vp);
          fence_regs(o);
          fence_regs(pr);
          fence_regs(s);
          bar_sync(1 + wg, 256);
          wg_fence();
          issue_s(kst);
          issue_pv(vst);
          bar_arrive(2 - wg, 256);
          wg_wait<3>();
          release(kb);
          fence_regs(s);
          const float d0 = -m0 * SM_C, d1 = -m1 * SM_C;
          wg_wait<2>();
          fence_part<0, 8>(pr);
          softmax_exp<0, 4>(s, pr, d0, d1, t);
          fence_part<0, 8>(pr);
          sched_fence(kst);
          wg_wait<1>();
          fence_part<8, 16>(pr);
          softmax_exp<4, 8>(s, pr, d0, d1, t);
          fence_part<8, 16>(pr);
          sched_fence(vst);
          wg_wait<0>();
          release(vb);
          fence_regs(o);
          fence_part<16, 32>(pr);
          softmax_exp<8, 16>(s, pr, d0, d1, t);
        };
        auto check = [&](bool hlf) {
          if (__builtin_expect(__any_sync(0xffffffffu, !((t[0] + t[1]) + (t[2] + t[3]) < 1.8446744e19f)), 0)) {
            float a0, a1, c0, c1;
            if (hlf) {
#pragma unroll
              for (int i = 32; i < 64; i++) s[i] = -INFINITY;
            }
            softmax_max<16>(s, m0, m1, a0, a1, c0, c1);
            l0 *= a0;
            l1 *= a1;
#pragma unroll
            for (int i = 0; i < 16; i++) { o[4 * i] *= a0; o[4 * i + 1] *= a0; o[4 * i + 2] *= a1; o[4 * i + 3] *= a1; }
            softmax_exp<0, 16>(s, pr, c0, c1, t);
          }
          l0 += t[0] + t[1];
          l1 += t[2] + t[3];
        };
        if (!lng) skip();
        first();
        check(half);
        if (!lng) skip();
        TRF(3);
#pragma unroll 1
        for (int j = 1; j < n; j++) {
          if (j == n - 1) TRF(4);
          block();
          check(false);
        }
        TRF(5);
        uint32_t vb;
        const uint32_t vst = acquire(2, vb);
        fence_regs(o);
        fence_regs(pr);
        if (!lng) bar_sync(1 + wg, 256);
        wg_fence();
        issue_pv(vst);
        l0 += __shfl_xor_sync(0xffffffffu, l0, 1);
        l1 += __shfl_xor_sync(0xffffffffu, l1, 1);
        l0 += __shfl_xor_sync(0xffffffffu, l0, 2);
        l1 += __shfl_xor_sync(0xffffffffu, l1, 2);
        const float i0 = rcp(l0), i1 = rcp(l1);
        next_task();
        mbar_wait(sb + M_SFREE + 8 * wg, (ti & 1) ^ 1);
        wg_wait<0>();
        release(vb);
        fence_regs(o);
        fence_regs(pr);
        TRF(6);
        stage_tile<0, 16>(o, sb + M_STG + wg * 16384 + sa, i0, i1);
        fence_async_smem();
        __syncwarp();
        arrive_elect(sb + M_EPI + 8 * (sl * 2 + wg));
        TRF(7);
      } else if (type >= T_MA) {
        float acc[64];
#pragma unroll
        for (int i = 0; i < 64; i++) acc[i] = 0.f;
        uint32_t prev = 0;
        for (int kb = 0; kb < 64; kb++) {
          uint32_t bar;
          const uint32_t st = acquire(2, bar);
          const uint32_t a = desc_lo(st + wg * 8192, 16), b = desc_lo(st + 16384, 4096);
          wg_fence();
#pragma unroll
          for (int kk = 0; kk < 4; kk++) wgmma_ss_n128_a0b1(acc, mk_desc(a + kk * 2, DHI_SW128), mk_desc(b + (kk >> 1) * 512 + (kk & 1) * 128, DHI_SW128), kk | kb);
          wg_commit();
          if (kb > 0) { wg_wait<1>(); release(prev); }
          prev = bar;
        }
        next_task();
        uint32_t bar;
        const uint32_t st = acquire(2, bar);
        mbar_wait(sb + M_SFREE + 8 * wg, (ti & 1) ^ 1);
        wg_wait<0>();
        release(prev);
        fence_regs(acc);
        stage_tile<0, 16>(acc, st + wg * 16384 + sa, 1.f, 1.f);
        fence_async_smem();
        __syncwarp();
        arrive_elect(sb + M_EPI + 8 * (sl * 2 + wg));
      } else {
        float acc[96];
#pragma unroll
        for (int i = 0; i < 96; i++) acc[i] = 0.f;
        uint32_t prev = 0;
        for (int kb = 0; kb < 64; kb++) {
          uint32_t bar;
          const uint32_t st = acquire(3, bar);
          const uint32_t a = desc_lo(st + wg * 8192, 16), b = desc_lo(st + 16384, 4096);
          wg_fence();
#pragma unroll
          for (int kk = 0; kk < 4; kk++) wgmma_ss_n192_a0b1(acc, mk_desc(a + kk * 2, DHI_SW128), mk_desc(b + (kk >> 1) * 768 + (kk & 1) * 128, DHI_SW128), kk | kb);
          wg_commit();
          if (kb > 0) { wg_wait<1>(); release(prev); }
          prev = bar;
        }
        next_task();
        uint32_t bar;
        const uint32_t st = acquire(3, bar);
        mbar_wait(sb + M_SFREE + 8 * wg, (ti & 1) ^ 1);
        wg_wait<0>();
        release(prev);
        fence_regs(acc);
        stage_tile<0, 24>(acc, st + wg * 24576 + sa, 1.f, 1.f);
        fence_async_smem();
        __syncwarp();
        arrive_elect(sb + M_EPI + 8 * (sl * 2 + wg));
      }
#ifdef DEV_TRACE
      if (w4 == 0 && lane == 0 && ti < 250) { long long c; asm volatile("mov.u64 %0, %%globaltimer;" : "=l"(c)); g_trace[blockIdx.x * 4096 + ti * 8 + wg * 4 + 1] = c; }
#endif
    }
    cluster_sync();
  }
}

typedef CUresult (*EncodeFn)(CUtensorMap*, CUtensorMapDataType, cuuint32_t, void*, const cuuint64_t*, const cuuint64_t*, const cuuint32_t*,
                             const cuuint32_t*, CUtensorMapInterleave, CUtensorMapSwizzle, CUtensorMapL2promotion, CUtensorMapFloatOOBfill);

void map2d(EncodeFn enc, CUtensorMap* m, const void* p, int rows, int cols, int boxr) {
  cuuint64_t gd[2] = {(cuuint64_t)cols, (cuuint64_t)rows}, gs[1] = {(cuuint64_t)cols * 2};
  cuuint32_t bx[2] = {64, (cuuint32_t)boxr}, es[2] = {1, 1};
  enc(m, CU_TENSOR_MAP_DATA_TYPE_BFLOAT16, 2, (void*)p, gd, gs, bx, es, CU_TENSOR_MAP_INTERLEAVE_NONE, CU_TENSOR_MAP_SWIZZLE_128B,
      CU_TENSOR_MAP_L2_PROMOTION_L2_256B, CU_TENSOR_MAP_FLOAT_OOB_FILL_NONE);
}
void map3d(EncodeFn enc, CUtensorMap* m, const void* p, int rows, int cols, int boxr, int nch) {
  cuuint64_t gd[3] = {64, (cuuint64_t)rows, (cuuint64_t)cols / 64}, gs[2] = {(cuuint64_t)cols * 2, 128};
  cuuint32_t bx[3] = {64, (cuuint32_t)boxr, (cuuint32_t)nch}, es[3] = {1, 1, 1};
  enc(m, CU_TENSOR_MAP_DATA_TYPE_BFLOAT16, 3, (void*)p, gd, gs, bx, es, CU_TENSOR_MAP_INTERLEAVE_NONE, CU_TENSOR_MAP_SWIZZLE_128B,
      CU_TENSOR_MAP_L2_PROMOTION_L2_256B, CU_TENSOR_MAP_FLOAT_OOB_FILL_NONE);
}

#ifndef R_KR
#define R_KR 24
#endif
#ifndef R_VR
#define R_VR 9
#endif
constexpr int R_NS = 36 - R_KR;
constexpr int R_WQ = 0, R_WK = R_WQ + R_NS * 2048, R_WV = R_WK + R_NS * 2048;
constexpr int R_OS = 102 * 1024;
constexpr int R_RS = 103 * 1024;
static_assert(R_WV + (36 - R_VR) * 2048 <= R_OS, "weights");
constexpr int R_HC = 9216, R_H = 114 * 1024, R_HM = R_H + 4096;
__host__ __device__ constexpr int hoff(int c) { return (c < 8 ? 1 + (c >> 1) + 4 * (c & 1) : 0) * R_HC; }
constexpr int R_PS = R_H + 9 * R_HC;
constexpr int R_GS = 1056, R_HS = 12288, R_QS = 201 * 1024;
static_assert(R_PS + 5120 <= R_QS, "layout");
constexpr int R_BAR = R_QS + 2 * R_HS;
static_assert(3 * 73728 <= R_BAR, "prologue staging");
constexpr int RB_MEM = R_BAR  , RB_RS = R_BAR + 40, RB_QK = R_BAR + 48, RB_XF = R_BAR + 88  , RB_QXL = R_BAR + 104, RB_W = R_BAR + 112  ;
constexpr int RB_TF = R_BAR + 128  , RB_TE = R_BAR + 160  , RB_TR = R_BAR + 192;
constexpr int R_SMEM = R_BAR + 256;
static_assert(R_SMEM <= 232448, "smem");
constexpr int QK_TX = 2048 + 8 * R_GS;
constexpr int NB_P1 = 1, NB_P3 = 2, NB_PM = 3, NB_O = 4, NB_PX = 5, NB_RD = 6, NB_S = 7, NB_O2 = 8;
static_assert(R_NS >= 9 && R_NS <= 18, "R_KR");
__host__ __device__ constexpr int nsm(int c) { return c < R_NS - 9 ? 2 : 1; }
__host__ __device__ constexpr int sm0(int c) { return c < R_NS - 9 ? 2 * c : c + R_NS - 9; }
__host__ __device__ constexpr bool qk_in_reg(int k) { return (k & 3) >= nsm(k >> 2); }
__host__ __device__ constexpr int qk_slot(int k) { return qk_in_reg(k) ? k - sm0((k >> 2) + 1) : sm0(k >> 2) + (k & 3); }
__host__ __device__ constexpr int qk_step(int slot, bool reg) {
  for (int k = 0; k < 36; k++)
    if (qk_in_reg(k) == reg && qk_slot(k) == slot) return k;
  return -1;
}
#ifndef B_SEQ
#define B_SEQ "qkqkqkqkQkqkKqkq|QKQKQKqkQkqKqkQkqKqkQkqKqkQkqKqkQkqKqkQkqKqkQkqKqkQkqKqk"
#endif
__host__ __device__ constexpr int seq_count(char c, int n) {
  int r = 0;
  for (int i = 0; i < n; i++) r += B_SEQ[i] == c;
  return r;
}
static_assert(sizeof(B_SEQ) == 74 && seq_count('q', 73) == R_KR && seq_count('k', 73) == R_KR && seq_count('Q', 73) == R_NS && seq_count('K', 73) == R_NS, "B_SEQ");
#ifndef V_N1
#define V_N1 10
#endif
#ifndef V_PER
#define V_PER 3
#endif
#ifndef V_K0
#define V_K0 11
#endif
#ifndef QX_AFTER
#define QX_AFTER 2
#endif
#ifndef P1_PRE
#define P1_PRE 2
#endif
#ifndef B_DELAY
#define B_DELAY 0
#endif
#ifndef PUB_REL
#define PUB_REL 0
#endif
#ifndef PF_V
#define PF_V 0
#endif
#ifndef PF_MAIN
#define PF_MAIN 0
#endif
#ifndef PRE_EARLY
#define PRE_EARLY 1
#endif
#ifndef P3_EARLY
#define P3_EARLY 0
#endif
#ifndef POLL_STAG
#define POLL_STAG 80
#endif
#ifndef POLL_DELAY
#define POLL_DELAY 240
#endif
__host__ __device__ constexpr bool v_in_reg(int k) { return k >= V_K0 && (k - V_K0) % V_PER == 0 && (k - V_K0) / V_PER < R_VR; }
__host__ __device__ constexpr int v_nreg_before(int k) { return k <= V_K0 ? 0 : ((k - V_K0 + V_PER - 1) / V_PER < R_VR ? (k - V_K0 + V_PER - 1) / V_PER : R_VR); }
__host__ __device__ constexpr int v_slot(int k) { return v_in_reg(k) ? (k - V_K0) / V_PER : k - v_nreg_before(k); }
static_assert(V_K0 + (R_VR - 1) * V_PER < 36, "Wv split");

struct RmtParams {
  CUtensorMap wq, wk, wv, wo, x, mem, ox, ox128, wo3;
  const __nv_bfloat16 *ckv, *wuk, *wuv;
  uint32_t* out;
};
constexpr int XCH_CL = 16 * 288, XCH_SLOT = 4 * XCH_CL;
__device__ uint32_t g_xch[2 * XCH_SLOT];
#ifdef DEV_TRACE
__device__ long long g_trace_b[64 * 4096];
#ifndef TR_S0
#define TR_S0 24
#endif
#ifndef TR_MASK
#define TR_MASK 0xffffffffu
#endif
#define TRW(slot, w) do { if (((TR_MASK >> (slot)) & 1) && w4 == (w) && s >= TR_S0 && s < TR_S0 + 16) { uint32_t c_; asm volatile("mov.u32 %0, %%clock;" : "=r"(c_)::"memory"); sts32(sb + R_QS + R_GS + ((s >> 3) & 1) * R_HS + (s & 7) * 128 + (slot) * 4, c_); } } while (0)
#else
#define TRW(slot, w)
#endif
#define TRB(slot) TRW(slot, 0)
#ifdef DEV_TRACE
#ifndef TRG_MASK
#define TRG_MASK 0x41
#endif
#define TRT(slot, w) do { if (warp == (w) && (threadIdx.x & 31) == 0) { long long c_; asm volatile("mov.u64 %0, %%globaltimer;" : "=l"(c_)); g_trace_b[bid * 4096 + 2200 + (slot)] = c_; } } while (0)
#define TRG(slot) do { if (((slot) >= 16 || ((TRG_MASK >> (slot)) & 1)) && (threadIdx.x & 127) == 0) { long long c_; asm volatile("mov.u64 %0, %%globaltimer;" : "=l"(c_)); g_trace_b[bid * 4096 + 2048 + (slot)] = c_; if ((slot) < 8) g_trace_b[bid * 4096 + 2056 + (slot)] = clock64(); } } while (0)
#else
#define TRG(slot)
#define TRT(slot, w)
#endif

__device__ __forceinline__ void ldsm4(uint32_t (&r)[4], uint32_t a) {
  asm volatile("ldmatrix.sync.aligned.m8n8.x4.shared.b16 {%0,%1,%2,%3}, [%4];" : "=r"(r[0]), "=r"(r[1]), "=r"(r[2]), "=r"(r[3]) : "r"(a) : "memory");
}
__device__ __forceinline__ void ldsm4t(uint32_t (&r)[4], uint32_t a) {
  asm volatile("ldmatrix.sync.aligned.m8n8.x4.trans.shared.b16 {%0,%1,%2,%3}, [%4];" : "=r"(r[0]), "=r"(r[1]), "=r"(r[2]), "=r"(r[3]) : "r"(a) : "memory");
}
__device__ __forceinline__ void stsm4t(uint32_t a, uint32_t r0, uint32_t r1, uint32_t r2, uint32_t r3) {
  asm volatile("stmatrix.sync.aligned.m8n8.x4.trans.shared.b16 [%0], {%1,%2,%3,%4};" ::"r"(a), "r"(r0), "r"(r1), "r"(r2), "r"(r3) : "memory");
}
__device__ __forceinline__ void stsm2t(uint32_t a, uint32_t r0, uint32_t r1) {
  asm volatile("stmatrix.sync.aligned.m8n8.x2.trans.shared.b16 [%0], {%1,%2};" ::"r"(a), "r"(r0), "r"(r1) : "memory");
}
__device__ __forceinline__ void mma16816(float (&c)[4], const uint32_t (&a)[4], uint32_t b0, uint32_t b1) {
  asm volatile("mma.sync.aligned.m16n8k16.row.col.f32.bf16.bf16.f32 {%0,%1,%2,%3}, {%4,%5,%6,%7}, {%8,%9}, {%0,%1,%2,%3};"
               : "+f"(c[0]), "+f"(c[1]), "+f"(c[2]), "+f"(c[3])
               : "r"(a[0]), "r"(a[1]), "r"(a[2]), "r"(a[3]), "r"(b0), "r"(b1));
}
__device__ __forceinline__ void sts32(uint32_t a, uint32_t v) { asm volatile("st.shared.b32 [%0], %1;" ::"r"(a), "r"(v) : "memory"); }
__device__ __forceinline__ uint2 lds64(uint32_t a) {
  uint2 v;
  asm volatile("ld.shared.v2.b32 {%0,%1}, [%2];" : "=r"(v.x), "=r"(v.y) : "r"(a) : "memory");
  return v;
}
__device__ __forceinline__ float4 lds128f(uint32_t a) {
  float4 v;
  asm volatile("ld.shared.v4.f32 {%0,%1,%2,%3}, [%4];" : "=f"(v.x), "=f"(v.y), "=f"(v.z), "=f"(v.w) : "r"(a) : "memory");
  return v;
}
__device__ __forceinline__ uint4 ld_relaxed128(const uint32_t* p) {
  uint4 v;
  asm volatile("ld.relaxed.gpu.global.v4.u32 {%0,%1,%2,%3}, [%4];" : "=r"(v.x), "=r"(v.y), "=r"(v.z), "=r"(v.w) : "l"(p) : "memory");
  return v;
}
__device__ __forceinline__ void st_relaxed32(uint32_t* p, uint32_t v) { asm volatile("st.relaxed.gpu.global.u32 [%0], %1;" ::"l"(p), "r"(v) : "memory"); }

__device__ __forceinline__ void mma1688(float (&c)[4], uint32_t a0, uint32_t a1, uint32_t b0) {
  asm volatile("mma.sync.aligned.m16n8k8.row.col.f32.bf16.bf16.f32 {%0,%1,%2,%3}, {%4,%5}, {%6}, {%0,%1,%2,%3};"
               : "+f"(c[0]), "+f"(c[1]), "+f"(c[2]), "+f"(c[3])
               : "r"(a0), "r"(a1), "r"(b0));
}
__device__ __forceinline__ uint2 ld_relaxed64(const uint32_t* p) {
  uint2 v;
  asm volatile("{.reg .b64 t; ld.relaxed.gpu.global.b64 t, [%2]; mov.b64 {%0,%1}, t;}" : "=r"(v.x), "=r"(v.y) : "l"(p) : "memory");
  return v;
}
__device__ __forceinline__ void st_relaxed64(uint32_t* p, uint32_t a, uint32_t b) { asm volatile("{.reg .b64 t; mov.b64 t, {%1,%2}; st.relaxed.gpu.global.b64 [%0], t;}" ::"l"(p), "r"(a), "r"(b) : "memory"); }

__device__ __forceinline__ void mma16816z(float (&c)[4], const uint32_t (&a)[4], uint32_t b0, uint32_t b1) {
  asm volatile("mma.sync.aligned.m16n8k16.row.col.f32.bf16.bf16.f32 {%0,%1,%2,%3}, {%4,%5,%6,%7}, {%8,%9}, {0f00000000,0f00000000,0f00000000,0f00000000};"
               : "=f"(c[0]), "=f"(c[1]), "=f"(c[2]), "=f"(c[3])
               : "r"(a[0]), "r"(a[1]), "r"(a[2]), "r"(a[3]), "r"(b0), "r"(b1));
}
template <int NB> __device__ __forceinline__ uint2 xch_reduce(uint32_t a, int key, uint32_t* dst, uint32_t tag) {
  uint32_t m[NB][4];
  float c[2][4];
#pragma unroll
  for (int j = 0; j < NB; j++) ldsm4t(m[j], a ^ (j << 5));
#pragma unroll
  for (int j = 0; j < NB; j++) {
    const uint32_t one = key == j ? 0x3f803f80u : 0u;
    if (j < 2) mma16816z(c[j], m[j], one, one);
    else mma16816(c[j & 1], m[j], one, one);
  }
  const uint2 o = make_uint2((__float_as_uint(c[0][0] + c[1][0]) & ~1u) | tag, __float_as_uint(c[0][2] + c[1][2]));
  st_relaxed64(dst, o.x, o.y);
  return o;
}
__device__ __forceinline__ uint32_t xch_sum(const uint2 (&v)[4]) {
  return pack_bf16((__uint_as_float(v[0].x) + __uint_as_float(v[1].x)) + (__uint_as_float(v[2].x) + __uint_as_float(v[3].x)),
                   (__uint_as_float(v[0].y) + __uint_as_float(v[1].y)) + (__uint_as_float(v[2].y) + __uint_as_float(v[3].y)));
}
__device__ __forceinline__ void xch_probe(uint2 (&v)[4], const uint32_t* x, int cl) {
#pragma unroll
  for (int c = 0; c < 4; c++)
    asm volatile("{.reg .pred p; .reg .b64 t; setp.ne.s32 p, %3, %4; mov.b64 t, {%0,%1}; @p ld.relaxed.gpu.global.b64 t, [%2]; mov.b64 {%0,%1}, t;}"
                 : "+r"(v[c].x), "+r"(v[c].y) : "l"(x + c * XCH_CL), "r"(cl), "r"(c) : "memory");
}
__device__ __forceinline__ uint32_t xch_bad(const uint2 (&v)[4]) {
  uint32_t bad;
  asm("{.reg .b32 t; lop3.b32 t, %1, %2, %3, 0x7e; lop3.b32 %0, t, %4, %3, 0xf6;}" : "=r"(bad) : "r"(v[0].x), "r"(v[1].x), "r"(v[2].x), "r"(v[3].x));
  return bad;
}
template <bool TWO> __device__ __forceinline__ uint32_t xch_poll(const uint32_t* x, int cl, uint2 o, const uint32_t* x2, uint2 o2, uint32_t& r2) {
  uint2 v[4] = {o, o, o, o}, w[4] = {o2, o2, o2, o2};
  uint32_t r;
#pragma unroll 1
  for (int it = 0;; it++) {
    xch_probe(v, x, cl);
    if (TWO) xch_probe(w, x2, cl);
    if (it > (1 << 20)) __trap();
    uint32_t bad = xch_bad(v);
    if (TWO) { bad |= xch_bad(w); r2 = xch_sum(w); }
    r = xch_sum(v);
    if (!__any_sync(0xffffffffu, bad & 1)) break;
  }
  return r;
}
constexpr uint32_t CTA1 = 1u << 24;
template <int NSEND, int NPRE> struct XSend {
  uint32_t d[NPRE], b[NPRE];
  static __device__ constexpr uint32_t off(int i) { return ((2 * i + 2 * i / NSEND) & (NSEND - 1)) * CTA1; }
  __device__ __forceinline__ XSend(uint32_t dst, uint32_t bar) {
#pragma unroll
    for (int i = 0; i < NPRE; i++) { d[i] = dst ^ off(i); b[i] = bar ^ off(i); }
    fence_regs(d);
    fence_regs(b);
  }
  __device__ __forceinline__ void send(uint32_t v) {
    asm volatile("" : "+r"(d[0]), "+r"(b[0]));
#pragma unroll
    for (int i = 0; i < NSEND; i++) st_async32(i < NPRE ? d[i] : d[0] ^ off(i), v, i < NPRE ? b[i] : b[0] ^ off(i));
  }
};
__device__ __forceinline__ uint32_t mbar_try_addr(uint32_t bar, uint32_t par, uint32_t good) {
  uint32_t r;
  asm volatile("{.reg .pred p; .reg .b32 t; mbarrier.try_wait.parity.shared::cta.b64 p, [%1], %2; xor.b32 t, %3, 16; selp.b32 %0, %3, t, p;}" : "=r"(r) : "r"(bar), "r"(par), "r"(good) : "memory");
  return r;
}

#ifdef DEV_TRACE
__device__ __noinline__ void trace_sync() {
  if (threadIdx.x == 0) {
    uint32_t g0, g1, c_;
    asm volatile("mov.u32 %0, %%globaltimer_lo;" : "=r"(g0));
    do { asm volatile("mov.u32 %0, %%globaltimer_lo;" : "=r"(g1)); asm volatile("mov.u32 %0, %%clock;" : "=r"(c_)); } while ((g1 >> 10) == (g0 >> 10));
    g_trace_b[(int)blockIdx.x * 4096 + 2160] = g1; g_trace_b[(int)blockIdx.x * 4096 + 2161] = c_;
  }
}
#endif
template <bool MASK>
__device__ __forceinline__ void rmt_softmax_row(const float (&d)[20], int u, int lim, uint32_t pax, uint32_t pam) {
  constexpr float C = 0.08838834764831845f * 1.4426950408889634f;
  float v[10];
#pragma unroll
  for (int j = 0; j < 5; j++) {
    v[2 * j] = (!MASK || j == 4 || 2 * j <= lim) ? d[4 * j + 2 * u] : -INFINITY;
    v[2 * j + 1] = (!MASK || j == 4 || 2 * j + 1 <= lim) ? d[4 * j + 2 * u + 1] : -INFINITY;
  }
  float m = fmaxf(fmaxf(fmaxf(v[0], v[1]), fmaxf(v[2], v[3])), fmaxf(fmaxf(fmaxf(v[4], v[5]), fmaxf(v[6], v[7])), fmaxf(v[8], v[9])));
  m = fmaxf(m, __shfl_xor_sync(0xffffffffu, m, 1));
  m = fmaxf(m, __shfl_xor_sync(0xffffffffu, m, 2));
  const float mc = -m * C;
#pragma unroll
  for (int i = 0; i < 10; i++) v[i] = ex2(fmaf(v[i], C, mc));
  float l = ((v[0] + v[1]) + (v[2] + v[3])) + (((v[4] + v[5]) + (v[6] + v[7])) + (v[8] + v[9]));
  l += __shfl_xor_sync(0xffffffffu, l, 1);
  l += __shfl_xor_sync(0xffffffffu, l, 2);
  const float inv = rcp(l);
  sts128(pax, pack_bf16(v[0] * inv, v[1] * inv), pack_bf16(v[2] * inv, v[3] * inv), pack_bf16(v[4] * inv, v[5] * inv), pack_bf16(v[6] * inv, v[7] * inv));
  sts32(pam, pack_bf16(v[8] * inv, v[9] * inv));
}

__global__ void __launch_bounds__(256, 1) rmt_kernel(const __grid_constant__ RmtParams P) {
  extern __shared__ __align__(1024) uint8_t smem_rmt[];
  const uint32_t sb = (uint32_t)__cvta_generic_to_shared(smem_rmt);
  const int warp = __shfl_sync(0xffffffffu, threadIdx.x >> 5, 0);
  const int lane = __shfl_sync(0xffffffffu, threadIdx.x & 31, threadIdx.x & 31);
  const int w4 = warp & 3, g = lane >> 2, t4 = lane & 3, rho = lane & 7, li = lane >> 3;
  uint32_t rank;
  asm("mov.u32 %0, %%cluster_ctarank;" : "=r"(rank));
  constexpr int ST_O = R_WV, ST_Q = ST_O + 73728, ST_K = ST_Q + R_KR * 2048, ST_V0 = R_OS, ST_V1 = ST_K + R_KR * 2048 - 6 * 2048;
  static_assert(ST_V0 + 6 * 2048 <= R_H && ST_V0 + 6 * 2048 <= ST_Q && ST_V1 + R_VR * 2048 <= R_BAR, "staging");

#ifdef DEV_SYNC
  trace_sync();
#endif
  if (threadIdx.x == 0) {
    if ((sb & 1023) || mapa(sb, 15) != (mapa(sb, 0) ^ (15 * CTA1))) __trap();
    for (int i = 0; i < 6; i++) mbar_init(sb + RB_MEM + 8 * i, 1);
    mbar_init(sb + RB_QK, 5); mbar_init(sb + RB_XF, 1); mbar_init(sb + RB_XF + 8, 1); mbar_init(sb + RB_QXL, 4); mbar_init(sb + RB_W, 1); mbar_init(sb + RB_W + 8, 1);
    for (int i = 0; i < 4; i++) { mbar_init(sb + RB_TF + 8 * i, 1); mbar_init(sb + RB_TE + 8 * i, 4); }
    mbar_init(sb + RB_TR, 1);
    asm volatile("fence.mbarrier_init.release.cluster;" ::: "memory");
    mbar_expect(sb + RB_TR, 49152);
    mbar_expect(sb + RB_W, 2 * 73728);
    mbar_expect(sb + RB_W + 8, 73728);
  }
  if (threadIdx.x == 32) TRE(blockIdx.x);
  asm volatile("griddepcontrol.launch_dependents;");
  const int cl = blockIdx.x >> 4;
  __syncthreads();
  const int bid = cl * 16 + rank, c0 = bid * 64;
  if (warp == 0) TRG(0);
  auto prefetch_main = [&]() {
    asm volatile("cp.async.bulk.prefetch.L2.global [%0], 4096;" ::"l"(P.ckv + (bid * 8 + warp) * 2048) : "memory");
    asm volatile("cp.async.bulk.prefetch.L2.global [%0], 1280;" ::"l"(P.wuk + (bid * 8 + warp) * HDALL) : "memory");
    asm volatile("cp.async.bulk.prefetch.L2.global [%0], 1280;" ::"l"(P.wuv + (bid * 8 + warp) * HDALL) : "memory");
  };
  if (PF_MAIN == 1 && elect()) prefetch_main();
  __syncwarp();
  if (B_DELAY > 0) __nanosleep(B_DELAY);
  if (elect()) {
    for (int i = warp; i < 9; i += 8) tma2d(sb + ST_O + i * 8192, &P.wo, i * 64, c0, sb + RB_W + 8);
    if (warp == 1 && bid < 27) asm volatile("cp.async.bulk.prefetch.tensor.2d.L2.global [%0, {%1,%2}];" ::"l"(bid < 18 ? &P.x : &P.mem), "r"(bid % 9 * 64), "r"(bid / 9 % 2 * 32) : "memory");
    for (int k = warp; k < 36; k += 8) {
      const int o = qk_slot(k) * 2048;
      tma2d(sb + (qk_in_reg(k) ? ST_Q : R_WQ) + o, &P.wq, c0, k * 16, sb + RB_W);
      tma2d(sb + (qk_in_reg(k) ? ST_K : R_WK) + o, &P.wk, c0, k * 16, sb + RB_W);
    }
    if (PF_V) for (int i = warp; i < 36; i += 8) asm volatile("cp.async.bulk.prefetch.tensor.2d.L2.global [%0, {%1,%2}];" ::"l"(&P.wv), "r"(c0), "r"(i * 16) : "memory");
    if (PF_MAIN == 2) prefetch_main();
  }
  __syncwarp();
  uint32_t wa = sb + ((li >> 1) * 8 + rho) * 128 + (((2 * w4 + (li & 1)) ^ rho) << 4);
  uint32_t la = sb + rho * 128 + ((li ^ rho) << 4);
  int ln = lane;
  if (warp == 0) TRG(1);
  mbar_wait(sb + RB_W + 8 * (warp >> 2), 0);
  if (warp == 0) TRG(2);

  if (warp < 4) {
    uint32_t wq[R_KR][4], wk[R_KR][4];
#pragma unroll
    for (int k = 0; k < R_KR; k++) { ldsm4t(wq[k], wa + ST_Q + k * 2048); ldsm4t(wk[k], wa + ST_K + k * 2048); }
    fence_async_smem();
    bar_sync(NB_P3, 256);
    asm volatile("barrier.cluster.arrive.relaxed.aligned;" ::: "memory");
    if (w4 < 2 && elect()) {
      mbar_expect(sb + RB_XF + 8 * w4, 9 * 4096);
      for (int i = 0; i < 9; i++) tma2d(sb + R_H + hoff(i) + w4 * 5120, &P.x, i * 64, w4 * 32, sb + RB_XF + 8 * w4);
    }
    if (w4 == 3 && elect()) {
      mbar_expect(sb + RB_QK, QK_TX);
      for (int i = 0; i < 5; i++) mbar_expect(sb + RB_MEM + 8 * i, i < 4 ? 2048 : 1024);
      for (int i = 0; i < 9; i++) tma2d(sb + R_HM + hoff(i), &P.mem, i * 64, 0, sb + RB_MEM + 8 * (i >> 1));
    }
    if (w4 == 2) sts128(sb + R_PS + (8 + lane) * 128 + ((5 ^ rho) << 4), 0u, 0u, 0u, 0u);
    __syncwarp();
    uint32_t qm = __shfl_sync(0xffffffffu, sb + R_QS + (rank & 1) * R_HS + (w4 * 16 + g) * 16 + t4 * 4, lane);
    const uint32_t peer = mapa(sb, rank ^ 1) - sb;

    uint32_t aq[P1_PRE][4], ak[P1_PRE][4];
    auto preload = [&]() {
#pragma unroll
      for (int i = 0; i < P1_PRE; i++) { ldsm4t(aq[i], wa + R_WQ + i * 2048); ldsm4t(ak[i], wa + R_WK + i * 2048); }
    };
    auto chain = [&](int s) {
      const bool LAST = s == 63;
      float cq[2][4], ck[2][4];
      for (;;) {
        uint32_t b[3][4];
        if (!PRE_EARLY) preload();
        mbar_wait(sb + RB_MEM, s & 1);
        TRB(0);
        uint32_t lb = la, bad = 0;
        ldsm4(b[0], lb + R_HM + hoff(0));
        ldsm4(b[1], (lb ^ 64) + R_HM + hoff(0));
#pragma unroll
        for (int hc = 0; hc < 18; hc++) {
          if (hc + 2 < 18) {
            if ((hc & 3) == 2) { lb = mbar_try_addr(sb + RB_MEM + 8 * ((hc + 2) >> 2), s & 1, la); bad |= lb ^ la; }
            ldsm4(b[(hc + 2) % 3], ((hc & 1) ? (lb ^ 64) : lb) + R_HM + hoff((hc + 2) >> 1));
          }
#pragma unroll
          for (int j = 0; j < 2; j++) {
            const int k = 2 * hc + j, sl = qk_slot(k);
            if (qk_in_reg(k)) {
              mma16816(cq[j], wq[sl], b[hc % 3][2 * j], b[hc % 3][2 * j + 1]);
              mma16816(ck[j], wk[sl], b[hc % 3][2 * j], b[hc % 3][2 * j + 1]);
            } else {
              static_assert(nsm(0) == 2, "first two steps come from shared memory");
              if (hc == 0) {
                mma16816z(cq[j], aq[j], b[0][2 * j], b[0][2 * j + 1]);
                mma16816z(ck[j], ak[j], b[0][2 * j], b[0][2 * j + 1]);
              } else {
                mma16816(cq[j], aq[sl % P1_PRE], b[hc % 3][2 * j], b[hc % 3][2 * j + 1]);
                mma16816(ck[j], ak[sl % P1_PRE], b[hc % 3][2 * j], b[hc % 3][2 * j + 1]);
              }
              if (sl + P1_PRE < R_NS) { ldsm4t(aq[sl % P1_PRE], wa + R_WQ + (sl + P1_PRE) * 2048); ldsm4t(ak[sl % P1_PRE], wa + R_WK + (sl + P1_PRE) * 2048); }
            }
          }
        }
        if (!__any_sync(0xffffffffu, bad)) break;
#pragma unroll 1
        for (int i = 1; i < 5; i++) mbar_wait(sb + RB_MEM + 8 * i, s & 1);
        if (PRE_EARLY) preload();
      }
      const uint32_t q0 = pack_bf16(cq[0][0] + cq[1][0], cq[0][1] + cq[1][1]), q1 = pack_bf16(cq[0][2] + cq[1][2], cq[0][3] + cq[1][3]);
      const uint32_t k0 = pack_bf16(ck[0][0] + ck[1][0], ck[0][1] + ck[1][1]), k1 = pack_bf16(ck[0][2] + ck[1][2], ck[0][3] + ck[1][3]);
      const uint32_t qp = qm + peer, bp = sb + RB_QK + peer;
      st_async32(qp, q0, bp);
      st_async32(qp + 128, q1, bp);
      st_async32(qp + 10 * R_GS, k0, bp);
      st_async32(qp + 10 * R_GS + 128, k1, bp);
      sts32(qm, q0);
      sts32(qm + 128, q1);
      sts32(qm + 10 * R_GS, k0);
      sts32(qm + 10 * R_GS + 128, k1);
      bar_arrive(NB_P1, 256);
      fence_async_smem();
      __syncwarp();
      arrive_elect(sb + RB_QK);
      TRB(1);
      float d[20];
#pragma unroll
      for (int i = 0; i < 20; i++) d[i] = 0.f;
      constexpr uint32_t HI = R_GS >> 4;
      const uint32_t qd = desc_lo(sb + R_QS, 128);
      mbar_wait(sb + RB_QK, s & 1);
      TRB(16);
      wg_fence();
#pragma unroll
      for (int k = 0; k < 8; k++) wgmma_ss_n40_a1b1(d, mk_desc(qd + (k >> 2) * (R_HS >> 4) + (k & 3) * 16, HI), mk_desc(qd + (k >> 2) * (R_HS >> 4) + (k & 3) * 16 + 6 * HI, HI), k != 0);
      wg_commit();
      bar_arrive(NB_S, 256);
      if (LAST) asm volatile("barrier.cluster.arrive.relaxed.aligned;" ::: "memory");
      const int ln = (qm >> 2) & 31, tt = ln & 3;
      if (w4 == 0) {
        const int gg = ln >> 2;
        const uint32_t pa = sb + R_PS + gg * 128;
        const uint32_t pax = pa + ((tt ^ gg) << 4), pam = pa + ((4 ^ gg) << 4) + tt * 4;
        wg_wait<0>();
        fence_regs(d);
        TRB(17);
        rmt_softmax_row<false>(d, 0, 0, pax, pam);
        bar_arrive(NB_PM, 160);
        TRB(18);
      } else if (w4 < 3) {
        const int tq = (ln & 24) + 4 * (w4 - 1) + ((ln >> 2) & 1), r7 = tq & 7;
        const uint32_t pa = sb + R_PS + (8 + tq) * 128;
        wg_wait<0>();
        fence_regs(d);
        rmt_softmax_row<true>(d, 0, tq - 8 * tt, pa + ((tt ^ r7) << 4), pa + ((4 ^ r7) << 4) + tt * 4);
        rmt_softmax_row<true>(d, 1, tq + 2 - 8 * tt, pa + 256 + ((tt ^ r7 ^ 2) << 4), pa + 256 + ((6 ^ r7) << 4) + tt * 4);
        fence_async_smem();
        bar_arrive(NB_PX, 192);
        TRW(15, 1);
      } else {
        if (!LAST) {
          if (ln < 7) mbar_expect(sb + RB_MEM + 8 * ln, ln == 6 ? QK_TX : ln == 5 ? 9216 : ln == 4 ? 1024 : 2048);
          if (ln == 11 && s < 62) mbar_expect(sb + RB_XF + 8 * (s & 1), 9 * 4096);
          __syncwarp();
        }
        wg_wait<0>();
        fence_regs(d);
      }
    };
    auto bulk = [&](int s) {
      const bool FIRST = s < 0;
      float dq[16], dk[16];
#pragma unroll
      for (int i = 0; i < 16; i++) dq[i] = dk[i] = 0.f;
      mbar_wait(sb + RB_XF + 8 * ((s + 1) & 1), ((s + 1) >> 1) & 1);
      const uint32_t hd = desc_lo(sb + R_H + ((s + 1) & 1) * 5120, 16), wd = desc_lo(sb + R_WQ, 16);
      auto bdesc = [&](int k) { return mk_desc(hd + (hoff(k >> 2) >> 4) + (k & 3) * 2, DHI_SW128); };
      const uint32_t qx = qm + 2 * R_GS + (qm & 12) * (R_GS / 4 - 1);
      if (!FIRST) bar_sync(NB_P3, 256);
      TRB(2);
      wg_fence();
      static_for<0, 73>([&](auto i_) {
        constexpr int i = decltype(i_)::value;
        constexpr char c = B_SEQ[i];
        constexpr int r = seq_count(c, i), nq = seq_count('q', i) + seq_count('Q', i), nk = seq_count('k', i) + seq_count('K', i);
        if constexpr (c == 'q') wgmma_rs_n32_b0(dq, wq[r][0], wq[r][1], wq[r][2], wq[r][3], bdesc(qk_step(r, true)), nq != 0);
        if constexpr (c == 'k') wgmma_rs_n32_b0(dk, wk[r][0], wk[r][1], wk[r][2], wk[r][3], bdesc(qk_step(r, true)), nk != 0);
        if constexpr (c == 'Q') wgmma_ss_n32_a1b0(dq, mk_desc(wd + r * 128, DHI_SW128), bdesc(qk_step(r, false)), nq != 0);
        if constexpr (c == 'K') wgmma_ss_n32_a1b0(dk, mk_desc(wd + (R_NS + r) * 128, DHI_SW128), bdesc(qk_step(r, false)), nk != 0);
        if constexpr (c == '|') {
          if (!FIRST) bar_sync(NB_RD, 256);
          TRB(6);
        }
      });
      wg_commit();
      if (FIRST) asm volatile("barrier.cluster.wait.aligned;" ::: "memory");
      if (PRE_EARLY) preload();
      wg_wait<0>();
      fence_regs(dq);
      fence_regs(dk);
      TRB(3);
#pragma unroll
      for (int r = 0; r < 2; r++) {
        sts128(qx + r * 128, pack_bf16(dq[2 * r], dq[2 * r + 1]), pack_bf16(dq[4 + 2 * r], dq[5 + 2 * r]), pack_bf16(dq[8 + 2 * r], dq[9 + 2 * r]), pack_bf16(dq[12 + 2 * r], dq[13 + 2 * r]));
        sts128(qx + 4 * R_GS + r * 128, pack_bf16(dk[2 * r], dk[2 * r + 1]), pack_bf16(dk[4 + 2 * r], dk[5 + 2 * r]), pack_bf16(dk[8 + 2 * r], dk[9 + 2 * r]), pack_bf16(dk[12 + 2 * r], dk[13 + 2 * r]));
      }
      __syncwarp();
      arrive_elect(sb + RB_QXL);
      TRB(4);
    };
    TRG(3);
#pragma unroll 1
    for (int s = -1; s < 63;) {
      asm volatile("" : "+r"(wa), "+r"(la), "+r"(qm));
      bulk(s);
      s++;
#ifdef DEV_TRS
      TRG(16 + s);
#endif
      chain(s);
    }
#ifdef DEV_TRACE
    bar_sync(NB_S, 256);
    for (int i = threadIdx.x; i < 16 * 32; i += 128) g_trace_b[bid * 4096 + i] = lds32(sb + R_QS + R_GS + ((i >> 8) ^ 1) * R_HS + (i & 255) * 4);
#endif
  } else {
    uint32_t wo[9][4][4], wv[R_VR][4];
#pragma unroll
    for (int i = 0; i < 9; i++) {
      const int T = i < 8 ? 8 * (i >> 1) + 2 * w4 + (i & 1) : 32 + 2 * (w4 & 1) + (w4 >> 1);
      const int quad = i < 8 ? (g >> 2) * 2 + (g & 1) : g & 3, odd = i < 8 ? (g >> 1) & 1 : g >> 2;
      const uint32_t a = sb + ST_O + (T >> 2) * 8192 + t4 * 256 + (quad & 1) * 8;
      const uint32_t ch = (T & 3) * 2 + (quad >> 1), sel = odd ? 0x7632 : 0x5410;
      const uint32_t a0 = a + ((ch ^ (2 * t4)) << 4), a1 = a + 128 + ((ch ^ (2 * t4 + 1)) << 4);
#pragma unroll
      for (int k = 0; k < 8; k++) {
        const uint2 x = lds64(a0 + k * 1024), y = lds64(a1 + k * 1024);
        wo[i][k >> 1][(k & 1) * 2] = __byte_perm(x.x, y.x, sel);
        wo[i][k >> 1][(k & 1) * 2 + 1] = __byte_perm(x.y, y.y, sel);
      }
    }
    fence_async_smem();
    bar_arrive(NB_P3, 256);
    bar_sync(NB_O, 128);
    if (w4 == 0 && elect()) mbar_expect(sb + RB_W + 8, 73728);
    if (elect())
      for (int k = w4; k < 36; k += 4) {
        const int sl = v_slot(k);
        tma2d(sb + (v_in_reg(k) ? (sl < 6 ? ST_V0 : ST_V1) : R_WV) + sl * 2048, &P.wv, c0, k * 16, sb + RB_W + 8);
      }
    __syncwarp();
    mbar_wait(sb + RB_W + 8, 1);
#pragma unroll
    for (int r = 0; r < R_VR; r++) ldsm4t(wv[r], wa + (r < 6 ? ST_V0 : ST_V1) + r * 2048);
    fence_async_smem();
    asm volatile("barrier.cluster.arrive.relaxed.aligned;" ::: "memory");
    const uint32_t sb0 = mapa(sb, 0), tok = rank & 7;
    uint32_t rsb = mapa(sb + RB_RS, (w4 & 1) * 8 + 2 * t4);
    const uint32_t rrow = rank ^ ((t4 & 1) << 3) ^ (t4 & 2), nrow = rank ^ ((t4 & 1) << 2);
    uint32_t rsA = rsb + (R_RS - RB_RS) + rrow * 128 + (((w4 >> 1) * 64 + g * 8) ^ ((rrow & 7) << 4));
    uint32_t rsN = rsb + (R_RS + 8192 - RB_RS) + nrow * 64 + (((w4 >> 1) * 32 + g * 4) ^ (((nrow >> 1) & 3) << 4));
    const uint32_t cp = 16 * (t4 >> 1) + 8 * ((g >> 1) & 1) + 4 * (t4 & 1) + 2 * (g >> 2) + (g & 1);
    uint32_t agd = sb0 + R_HM + tok * 128 + hoff(2 * w4 + (cp >> 4)) + ((((rank >> 3) * 4 + ((cp & 15) >> 2)) ^ tok) << 4) + (cp & 3) * 4;
    uint32_t* xb = g_xch + rank * 288 + w4 * 64 + lane * 2;
    uint32_t vx[8];
#pragma unroll
    for (int i = 0; i < 8; i++) vx[i] = 0;

    auto step = [&](int s) {
      const bool FIRST = s < 0, LAST = s == 63, MID = !FIRST && !LAST;
      const int par = (s + 1) & 1;
      float d[20];
#pragma unroll
      for (int i = 0; i < 20; i++) d[i] = 0.f;
      if (!LAST) mbar_wait(sb + RB_XF + 8 * par, ((s + 1) >> 1) & 1);
      const uint32_t hd = desc_lo(sb + R_H + par * 4096, 16), vd = desc_lo(sb + R_WV, 16);
      if (!FIRST) {
        if (w4 == 0) {
          mbar_wait(sb + RB_QXL, s & 1);
          mbar_wait(sb + RB_MEM + QX_AFTER * 8, s & 1);
          fence_async_smem();
          if (elect()) {
            const uint32_t src = sb + R_QS + (rank & 1) * R_HS + 2 * R_GS, dst = mapa(src, rank ^ 1), bar = mapa(sb + RB_QK, rank ^ 1), cut = 256 + rank * 512;
            asm volatile("cp.async.bulk.shared::cluster.shared::cta.mbarrier::complete_tx::bytes [%0], [%1], %2, [%3];" ::"r"(dst + cut), "r"(src + cut), "r"(8 * R_GS - cut), "r"(bar) : "memory");
            asm volatile("cp.async.bulk.shared::cluster.shared::cta.mbarrier::complete_tx::bytes [%0], [%1], %2, [%3];" ::"r"(dst), "r"(src), "r"(cut), "r"(bar) : "memory");
          }
          __syncwarp();
          TRW(7, 0);
        }
#pragma unroll
        for (int i = 0; i < 5; i++) { mbar_wait(sb + RB_MEM + 8 * i, s & 1); if (i == 4) TRW(30, 2); }
        fence_async_smem();
        bar_sync(NB_P1, 256);
      }
      wg_fence();
#pragma unroll
      for (int k = 0; k < 36; k++) {
        if (k == V_N1 && !FIRST) bar_sync(NB_S, 256);
        const uint64_t db = mk_desc(hd + (hoff(k >> 2) >> 4) + (k & 3) * 2, DHI_SW128);
        if (v_in_reg(k)) wgmma_rs_n40_b0(d, wv[v_slot(k)][0], wv[v_slot(k)][1], wv[v_slot(k)][2], wv[v_slot(k)][3], db, 1);
        else wgmma_ss_n40_a1b0(d, mk_desc(vd + v_slot(k) * 128, DHI_SW128), db, k != 0);
      }
      wg_commit();
      TRB(8);
      uint32_t vm0, vm1, vn[8];
      auto pack_v = [&]() {
#pragma unroll
        for (int i = 0; i < 8; i++) vn[i] = par ? pack_bf16(d[2 * i + 4], d[2 * i + 5]) : pack_bf16(d[2 * i], d[2 * i + 1]);
      };
      if (MID) {
        float o[4] = {0.f, 0.f, 0.f, 0.f};
        uint32_t b0[4], b1[4];
        bar_sync(NB_PM, 160);
        ldsm4(b0, la + R_PS);
        ldsm4(b1, (la ^ 64) + R_PS);
        {
          const uint32_t x0[4] = {vx[0], vx[1], vx[2], vx[3]}, x1[4] = {vx[4], vx[5], vx[6], vx[7]};
          float o2[4] = {0.f, 0.f, 0.f, 0.f};
          wg_wait<0>();
          fence_regs(d);
          TRB(9);
          mma16816(o, x0, b0[0], b0[1]);
          mma16816(o2, x1, b0[2], b0[3]);
          vm0 = par ? pack_bf16(d[0], d[1]) : pack_bf16(d[16], d[17]);
          vm1 = par ? pack_bf16(d[2], d[3]) : pack_bf16(d[18], d[19]);
          float o3[4] = {0.f, 0.f, 0.f, 0.f};
          mma1688(o3, vm0, vm1, b1[0]);
          stsm2t(wa + R_OS, pack_bf16(o[0] + o2[0] + o3[0], o[1] + o2[1] + o3[1]), pack_bf16(o[2] + o2[2] + o3[2], o[3] + o2[3] + o3[3]));
        }
        bar_sync(NB_O, 128);
        TRB(11);
        ldsm4(b0, la + R_OS);
        ldsm4(b1, (la ^ 64) + R_OS);
        auto send = [&](int j, const float (&c0_)[4], const float (&c1_)[4]) {
          st_async64(rsA + j * 2048, pack_bf16(c0_[0], c0_[2]), pack_bf16(c1_[0], c1_[2]), rsb);
          st_async64(rsA + j * 2048 + CTA1, pack_bf16(c0_[1], c0_[3]), pack_bf16(c1_[1], c1_[3]), rsb + CTA1);
        };
        auto tile = [&](float (&c)[4], int i, int k) {
          if (k == 0) mma16816z(c, wo[i][0], b0[0], b0[1]);
          else mma16816(c, wo[i][k], k < 2 ? b0[2 * k] : b1[2 * k - 4], k < 2 ? b0[2 * k + 1] : b1[2 * k - 3]);
        };
        {
          float c[4][4];
          mma16816z(c[0], wo[0][0], b0[0], b0[1]);
          mma16816z(c[1], wo[1][0], b0[0], b0[1]);
          mma16816z(c[2], wo[0][2], b1[0], b1[1]);
          mma16816z(c[3], wo[1][2], b1[0], b1[1]);
          mma16816(c[0], wo[0][1], b0[2], b0[3]);
          mma16816(c[1], wo[1][1], b0[2], b0[3]);
          mma16816(c[2], wo[0][3], b1[2], b1[3]);
          mma16816(c[3], wo[1][3], b1[2], b1[3]);
          pack_v();
#pragma unroll
          for (int i = 0; i < 4; i++) { c[0][i] += c[2][i]; c[1][i] += c[3][i]; }
          send(0, c[0], c[1]);
          fence_regs(vn);
        }
        sched_fence(rsb);
        TRB(13);
        {
          float c[3][4];
#pragma unroll
          for (int k = 0; k < 4; k++) { tile(c[0], 8, k); tile(c[1], 2, k); tile(c[2], 3, k); }
          st_async32(rsN, pack_bf16(c[0][0], c[0][2]), rsb);
          st_async32(rsN + CTA1, pack_bf16(c[0][1], c[0][3]), rsb + CTA1);
          send(1, c[1], c[2]);
        }
        sched_fence(la);
        {
          float c[4][4];
#pragma unroll
          for (int k = 0; k < 4; k++)
#pragma unroll
            for (int i = 0; i < 4; i++) tile(c[i], 4 + i, k);
          if (P3_EARLY == 1) { sched_fence(rsA); bar_arrive(NB_P3, 256); }
          send(2, c[0], c[1]);
          send(3, c[2], c[3]);
          if (P3_EARLY == 2) bar_arrive(NB_P3, 256);
        }
        TRB(12);
      } else {
        if (LAST) bar_sync(NB_PM, 160);
        wg_wait<0>();
        fence_regs(d);
        if (LAST) asm volatile("barrier.cluster.arrive.relaxed.aligned;" ::: "memory");
        vm0 = pack_bf16(d[16], d[17]);
        vm1 = pack_bf16(d[18], d[19]);
        pack_v();
      }
      if (FIRST) {
        asm volatile("barrier.cluster.wait.aligned;" ::: "memory");
        TRG(7);
      } else {
        float e[16];
#pragma unroll
        for (int i = 0; i < 16; i++) e[i] = 0.f;
        uint32_t z0 = 0, z1 = 0;
        asm volatile("" : "+r"(z0), "+r"(z1), "+r"(vm0), "+r"(vm1));
        const uint32_t pd = desc_lo(sb + R_PS + 1024, 16);
        fence_regs(vx);
        bar_sync(NB_PX, 192);
        wg_fence();
        wgmma_rs_n32_b0(e, vx[0], vx[1], vx[2], vx[3], mk_desc(pd, DHI_SW128), 0);
        wgmma_rs_n32_b0(e, vx[4], vx[5], vx[6], vx[7], mk_desc(pd + 2, DHI_SW128), 1);
        wgmma_rs_n32_b0(e, vm0, vm1, z0, z1, mk_desc(pd + 4, DHI_SW128), 1);
        wg_commit();
        if (!P3_EARLY && !LAST) bar_arrive(NB_P3, 256);
        wg_wait<0>();
        fence_regs(e);
        fence_regs(vx);
        bar_sync(NB_O, 128);
        stsm4t(wa + R_PS + 1024, pack_bf16(e[0], e[1]), pack_bf16(e[2], e[3]), pack_bf16(e[4], e[5]), pack_bf16(e[6], e[7]));
        stsm4t(wa + R_PS + 3072, pack_bf16(e[8], e[9]), pack_bf16(e[10], e[11]), pack_bf16(e[12], e[13]), pack_bf16(e[14], e[15]));
        TRB(14);
      }
      auto store_x = [&]() {
        fence_async_smem();
        if (w4 == 2) bar_sync(NB_O2, 128); else bar_arrive(NB_O2, 128);
        if (w4 == 2 && elect()) {
          asm volatile("cp.async.bulk.tensor.2d.global.shared::cta.bulk_group [%0, {%1,%2}], [%3];" ::"l"(&P.ox), "r"(c0), "r"(3 * SEQ + s * 32), "r"(sb + R_PS + 1024) : "memory");
          asm volatile("cp.async.bulk.commit_group;" ::: "memory");
        }
        __syncwarp();
      };
      if (MID) {
        const uint32_t tag = ((s >> 1) & 1) ^ 1;
        uint32_t* x = xb + (s & 1) * XCH_SLOT;
        uint32_t* xw = x + cl * XCH_CL;
        const int src = (ln & 7) + (ln >> 4) * 8, hf = (ln >> 3) & 1;
        const uint32_t ra = sb + R_RS + w4 * 2048 + src * 128 + ((hf ^ (ln & 7)) << 4);
        auto delay = [&](uint32_t t0) {
          while ((uint32_t)clock() - t0 < POLL_DELAY + w4 * POLL_STAG) {}
        };
        uint32_t rn;
        const uint32_t agb = sb0 + RB_MEM + 8 * w4 + (uint32_t)(ln >> 5);
        if (w4 == 3) {
          const int cn = 8 * (ln & 1) + (ln >> 2), no = 64 + 2 * (cn - ln);
          const uint32_t rb = sb + R_RS + 8192 + src * 64 + ((hf ^ ((ln >> 1) & 3)) << 4);
          mbar_wait(sb + RB_RS, s & 1);
          const uint2 o = xch_reduce<4>(ra, ln >> 3, xw, tag);
          const uint2 on = xch_reduce<2>(rb, hf, xw + no, tag);
          const uint32_t t0 = clock();
          bar_arrive(NB_RD, 256);
          TRW(27, 3);
          store_x();
          const uint32_t off = (ln & 2) * 4 * CTA1;
          const uint32_t agn = sb0 + R_HM + tok * 128 + hoff(8) + ((((rank >> 3) * 4 + (cn >> 2)) ^ tok) << 4) + (cn & 3) * 4;
          XSend<16, 6> xs(agd, agb);
          delay(t0);
          const uint32_t r = xch_poll<true>(x, cl, o, x + no, on, rn);
          TRW(28, 3);
          xs.send(r);
          XSend<8, 1>(agn ^ off, (agb + 8) ^ off).send(rn);
          TRW(22, 3);
        } else {
          mbar_wait(sb + RB_RS, s & 1);
          TRB(19);
          const uint2 o = xch_reduce<4>(ra, ln >> 3, xw, tag);
          const uint32_t t0 = clock();
          bar_arrive(NB_RD, 256);
          TRB(25);
          store_x();
          if (w4 == 1 && rank < 9 && s < 62 && elect()) {
            tma2d_mc(sb + R_H + hoff(rank) + (s & 1) * 5120, &P.x, rank * 64, (s + 2) * 32, sb + RB_XF + 8 * (s & 1), 0xffff);
            asm volatile("cp.async.bulk.prefetch.tensor.2d.L2.global [%0, {%1,%2}];" ::"l"(&P.x), "r"(rank * 64), "r"(min(s + 3 + cl, 63) * 32) : "memory");
          }
          __syncwarp();
          XSend<16, 12> xs(agd, agb);
          delay(t0);
          asm volatile("cp.async.bulk.wait_group.read 0;" ::: "memory");
          const uint32_t r = xch_poll<false>(x, cl, o, x, o, rn);
          TRB(26); TRW(10, 1); TRW(20, 2);
          xs.send(r);
          TRB(21); TRW(23, 1); TRW(24, 2);
          if (w4 == 2 && (s & 3) == 3) {
            asm volatile("cp.async.bulk.wait_group 0;" ::: "memory");
#if PUB_REL
            asm volatile("{.reg .pred q; elect.sync _|q, 0xffffffff; @q red.release.gpu.global.add.u32 [%0], 1;}" ::"l"(&g_sync[SY_OX + (s >> 2)]) : "memory");
#else
            asm volatile("{.reg .pred q; elect.sync _|q, 0xffffffff; @q red.relaxed.gpu.global.add.u32 [%0], 1;}" ::"l"(&g_sync[SY_OX + (s >> 2)]) : "memory");
#endif
          }
        }
      }
#pragma unroll
      for (int i = 0; i < 8; i++) vx[i] = vn[i];
    };
    TRG(5);
#pragma unroll 1
    for (int s = -1; s < 64; s++) {
      asm volatile("" : "+r"(wa), "+r"(la), "+r"(rsb), "+r"(rsA), "+r"(rsN), "+r"(agd), "+r"(ln), "+l"(xb));
      step(s);
    }
    if (threadIdx.x == 128) TRE(64 + blockIdx.x);
    fence_async_smem();
    bar_sync(NB_O2, 128);
    if (w4 == 2) {
      if (elect()) {
        asm volatile("cp.async.bulk.tensor.2d.global.shared::cta.bulk_group [%0, {%1,%2}], [%3];" ::"l"(&P.ox), "r"(c0), "r"(3 * SEQ + 63 * 32), "r"(sb + R_PS + 1024) : "memory");
        asm volatile("cp.async.bulk.commit_group;" ::: "memory");
        asm volatile("cp.async.bulk.wait_group 0;" ::: "memory");
#if PUB_REL
        asm volatile("red.release.gpu.global.add.u32 [%0], 1;" ::"l"(&g_sync[SY_OX + 15]) : "memory");
#else
        asm volatile("red.relaxed.gpu.global.add.u32 [%0], 1;" ::"l"(&g_sync[SY_OX + 15]) : "memory");
#endif
      }
      __syncwarp();
    } else {
      uint32_t* z = g_xch + XCH_SLOT + cl * XCH_CL + rank * 288 + (w4 == 3 ? 64 : w4 * 32) + ln;
      st_relaxed32(z, 0u); st_relaxed32(z + 96, 0u); st_relaxed32(z + 192, 0u);
    }
#ifdef DEV_TRACE
    bar_sync(NB_S, 256);
#endif
  }
  asm volatile("barrier.cluster.wait.aligned;\nbarrier.cluster.arrive.relaxed.aligned;" ::: "memory");
  {
    uint32_t rank, cl;
    asm volatile("mov.u32 %0, %%cluster_ctarank;" : "=r"(rank));
    asm volatile("mov.u32 %0, %%clusterid.x;" : "=r"(cl));
    const int lane = threadIdx.x & 31, wg = warp >> 2, u = rank >> 1, blk = cl == 3 ? 12 + (rank & 1) : 14 + (rank & 1), nn = min(cl, 2u);
    constexpr int T_E = 40960, T_R = 4 * T_E;
    auto load_w = [&](int kb) {
      const uint32_t fb = sb + RB_TF + 8 * (kb & 3);
      mbar_expect(fb, T_E);
      tma3d_mc(sb + (kb & 3) * T_E + 16384 + (rank & 1) * 12288, &P.wo3, 0, u * 512 + kb * 64 + (rank & 1) * 32, nn * 3, fb, 3 << (rank & 14));
    };
    auto load_a = [&](int kb) { tma2d(sb + (kb & 3) * T_E, &P.ox128, u * 512 + kb * 64, 3 * SEQ + blk * 128, sb + RB_TF + 8 * (kb & 3)); };
    TRT(0, 0);
    if (warp == 0 && elect()) {
#pragma unroll 1
      for (int kb = 0; kb < 4; kb++) load_w(kb);
      for (int it = 0; ld_acquire(g_sync + SY_OX + blk) < OX_TARGET; it++)
        if (it > (1 << 22)) __trap();
#pragma unroll 1
      for (int kb = 0; kb < 4; kb++) load_a(kb);
    }
    __syncwarp();
    TRT(1, 0);
    float acc[96];
#pragma unroll
    for (int i = 0; i < 96; i++) acc[i] = 0.f;
    const uint32_t te = mapa(sb + RB_TE, (rank & 14) + (lane & 1));
#pragma unroll 1
    for (int kb = 0; kb < 8; kb++) {
      const uint32_t st = sb + (kb & 3) * T_E, a = desc_lo(st + wg * 8192, 16), b = desc_lo(st + 16384, 4096);
      mbar_wait(sb + RB_TF + 8 * (kb & 3), kb >> 2);
      if (kb == 0) TRT(2, 0);
      wg_fence();
#pragma unroll
      for (int kk = 0; kk < 4; kk++) wgmma_ss_n192_a0b1(acc, mk_desc(a + kk * 2, DHI_SW128), mk_desc(b + (kk >> 1) * 768 + (kk & 1) * 128, DHI_SW128), 1);
      wg_commit();
      wg_wait<1>();
      if (kb >= 1 && kb <= 4) {
        if (w4 == 0 && lane < 2) mbar_arrive_cl(te + 8 * (kb - 1));
        if (warp == 0) {
          mbar_wait(sb + RB_TE + 8 * (kb - 1), 0);
          if (elect()) { load_w(kb + 3); load_a(kb + 3); }
        }
        __syncwarp();
      }
    }
    asm volatile("barrier.cluster.wait.aligned;" ::: "memory");
    wg_wait<0>();
    fence_regs(acc);
    TRT(3, 0);
    const uint32_t ra = mapa(sb + T_R + u * 6144 + ((lane ^ u) << 4), 2 * warp + (rank & 1)), rb = mapa(sb + RB_TR, 2 * warp + (rank & 1));
#pragma unroll
    for (int j = 0; j < 12; j++) {
      const int o = 16 * (j >> 1) + (j & 1);
      st_async128(ra + j * 512, pack_bf16(acc[o], acc[o + 2]), pack_bf16(acc[o + 4], acc[o + 6]), pack_bf16(acc[o + 8], acc[o + 10]), pack_bf16(acc[o + 12], acc[o + 14]), rb);
    }
    TRT(4, 0);
    const int r = lane & 7, m = lane >> 3, g = lane >> 2;
    const uint32_t la = sb + T_R + r * 6144 + wg * 3072 + (m >> 1) * 512;
    uint32_t* out = P.out + (blk * 128 + u * 16 + 2 * w4 + 8 * (g & 1)) * DM + DM / 2 + nn * 96 + wg * 48 + (g >> 1) * 4 + (lane & 3);
    mbar_wait(sb + RB_TR, 0);
    TRT(5, 0);
    asm volatile("barrier.cluster.arrive.relaxed.aligned;" ::: "memory");
#pragma unroll 1
    for (int J = 0; J < 3; J++) {
      float c[2][4];
      uint32_t v[4][4];
#pragma unroll
      for (int j = 0; j < 4; j++) ldsm4t(v[j], la + J * 1024 + (((8 * w4 + 4 * (m & 1) + j) ^ r) << 4));
#pragma unroll
      for (int j = 0; j < 4; j++) {
        const uint32_t b0 = g == 2 * j ? 0x3f803f80u : 0u, b1 = g == 2 * j + 1 ? 0x3f803f80u : 0u;
        if (j < 2) mma16816z(c[j], v[j], b0, b1);
        else mma16816(c[j & 1], v[j], b0, b1);
      }
      out[J * 16] = pack_bf16(c[0][0] + c[1][0], c[0][1] + c[1][1]);
      out[J * 16 + DM] = pack_bf16(c[0][2] + c[1][2], c[0][3] + c[1][3]);
    }
    TRT(6, 0);
    if (warp == 0) TRG(6);
    asm volatile("barrier.cluster.wait.aligned;" ::: "memory");
  }
  if (threadIdx.x == 96) TRE(128 + blockIdx.x);
}

void rmt_setup() {
  cudaFuncSetAttribute(rmt_kernel, cudaFuncAttributeMaxDynamicSharedMemorySize, R_SMEM);
  cudaFuncSetAttribute(rmt_kernel, cudaFuncAttributeNonPortableClusterSizeAllowed, 1);
}
void rmt_launch(EncodeFn enc, void* const* d_in, void* scr, void* out) {
  RmtParams R;
  map2d(enc, &R.wq, d_in[8], DM, HDALL, 16);
  map2d(enc, &R.wk, d_in[9], DM, HDALL, 16);
  map2d(enc, &R.wv, d_in[10], DM, HDALL, 16);
  map2d(enc, &R.wo, d_in[11], HDALL, DM, 64);
  map2d(enc, &R.x, d_in[6], SEQ, DM, 32);
  map2d(enc, &R.mem, d_in[7], 8, DM, 8);
  map2d(enc, &R.ox, scr, 4 * SEQ, HDALL, 32);
  cudaLaunchConfig_t cfg = {};
  map2d(enc, &R.ox128, scr, 4 * SEQ, HDALL, 128);
  map3d(enc, &R.wo3, d_in[11], HDALL, DM, 32, 3);
  R.out = (uint32_t*)out;
  R.ckv = (const __nv_bfloat16*)d_in[1]; R.wuk = (const __nv_bfloat16*)d_in[3]; R.wuv = (const __nv_bfloat16*)d_in[4];
  cfg.gridDim = dim3(64);
  cfg.blockDim = dim3(256);
  cfg.dynamicSmemBytes = R_SMEM;
  cfg.stream = cudaStreamPerThread;
  cudaLaunchAttribute at[1];
  at[0].id = cudaLaunchAttributeClusterDimension;
  at[0].val.clusterDim.x = 16;
  at[0].val.clusterDim.y = 1;
  at[0].val.clusterDim.z = 1;
  cfg.attrs = at;
  cfg.numAttrs = 1;
  cudaLaunchKernelEx(&cfg, rmt_kernel, R);
}


const uint16_t h_order[] = {
    4096, 4097, 34, 35, 36, 37, 38, 39, 40, 41, 42, 43, 44, 45, 46, 47, 48, 49, 50, 51,
    52, 53, 54, 55, 56, 57, 58, 59, 60, 61, 62, 63, 64, 65, 66, 67, 68, 69, 70, 71,
    72, 73, 74, 75, 76, 77, 78, 79, 80, 81, 82, 83, 84, 85, 86, 87, 88, 89, 90, 91,
    92, 93, 94, 95, 96, 97, 98, 99, 100, 101, 102, 103, 4103, 4102, 4101, 4100, 4099, 4098, 104, 105,
    106, 107, 108, 109, 110, 111, 4111, 4110, 4109, 4108, 4107, 4106, 112, 113, 114, 115, 116, 117, 118, 119,
    4119, 4118, 4117, 4116, 4115, 4114, 120, 121, 122, 123, 124, 125, 126, 127, 4127, 4126, 4125, 4124, 4123, 4122,
    128, 129, 130, 131, 132, 133, 134, 135, 4135, 4134, 4133, 4132, 4131, 4130, 136, 137, 138, 139, 140, 141,
    142, 143, 4143, 4142, 4141, 4140, 4139, 4138, 144, 145, 146, 147, 148, 149, 150, 151, 4151, 4150, 4149, 4148,
    4147, 4146, 152, 12288, 12544, 12800, 153, 154, 155, 156, 157, 158, 159, 4159, 4158, 4157, 4156, 4155, 4154, 160,
    161, 162, 163, 164, 165, 166, 167, 4167, 4166, 4165, 4164, 4163, 4162, 168, 169, 170, 171, 172, 173, 174,
    175, 4175, 4174, 4173, 4172, 4171, 4170, 176, 177, 178, 179, 180, 181, 182, 183, 4183, 4182, 4181, 4180, 4179,
    4178, 184, 185, 186, 187, 188, 189, 190, 191, 4191, 4190, 4189, 4188, 4187, 4186, 192, 193, 194, 195, 196,
    197, 198, 199, 4199, 4198, 4197, 4196, 4195, 4194, 200, 201, 202, 203, 12289, 12545, 12801, 204, 205, 206, 207,
    4207, 4206, 4205, 4204, 4203, 4202, 208, 209, 210, 211, 212, 213, 214, 215, 4215, 4214, 4213, 4212, 4211, 4210,
    216, 217, 218, 219, 220, 221, 222, 223, 4223, 4222, 4221, 4220, 4219, 12290, 12546, 12802, 4218, 224, 225, 226,
    227, 228, 229, 230, 231, 4231, 4230, 4229, 4228, 4227, 4226, 232, 233, 234, 235, 236, 237, 238, 239, 4239,
    4238, 4237, 4236, 4235, 4234, 240, 241, 242, 243, 244, 245, 246, 247, 4247, 4246, 4245, 4244, 4243, 4242, 248,
    249, 250, 251, 252, 253, 254, 255, 4255, 4254, 12291, 12547, 12803, 4253, 4252, 4251, 4250, 4263, 4262, 4261, 4260,
    4259, 4258, 4271, 4270, 4269, 4268, 4267, 4266, 4279, 4278, 4277, 4276, 4275, 4274, 4287, 4286, 4285, 4284, 4283, 4282,
    4295, 4294, 4293, 4292, 4291, 4290, 4303, 4302, 4301, 4300, 4299, 4298, 4311, 12292, 12548, 12804, 4310, 4309, 4308, 4307,
    4306, 4319, 4318, 4317, 4316, 4315, 4314, 4327, 4326, 4325, 4324, 4323, 4322, 4335, 4334, 4333, 4332, 4331, 4330, 4343,
    4342, 4341, 4340, 4339, 4338, 4351, 4350, 4349, 4348, 4347, 4346, 4105, 4104, 4113, 8199, 8455, 8711, 4112, 4121, 4120,
    4129, 4128, 8194, 8450, 8706, 4137, 4136, 4145, 4144, 4153, 4152, 4161, 4160, 4169, 4168, 4177, 4176, 4185, 4184, 4193,
    4192, 4201, 4200, 4209, 4208, 4217, 4216, 4225, 4224, 4233, 12294, 12550, 4232, 4241, 4240, 4249, 8192, 8448, 8704, 8197,
    8453, 8709, 8198, 8454, 8710, 4248, 4257, 8193, 8449, 8705, 8195, 8451, 8707, 8196, 8452, 8708, 12293, 12549, 12805, 4256,
    4265, 4264, 4273, 4272, 4281, 4280, 4289, 4288, 4297, 4296, 4305, 4304, 4313, 4312, 4321, 4320, 4329, 4328, 4337, 4336,
    4345, 4344,
};
int build_tasks(uint16_t* t) {
  int n = 0;
#ifdef DEV_ORDER
  if (const char* fn = getenv("ORDER")) {
    FILE* f = fopen(fn, "r");
    int v;
    while (fscanf(f, "%d", &v) == 1) t[n++] = v;
    fclose(f);
    return n;
  }
#endif
  static_assert(sizeof(h_order) / 2 <= MAXTASK, "tasks");
  for (; n < (int)(sizeof(h_order) / 2); n++) t[n] = h_order[n];
  return n;
}

}

extern "C" void kernel_launch(void* const* d_in, const int* in_sizes, int n_in, void* d_out, int out_size) {
  (void)in_sizes; (void)n_in; (void)out_size;
  static EncodeFn enc = nullptr;
  static void* scr = nullptr;
  if (!enc) {
    cudaDriverEntryPointQueryResult q;
    cudaGetDriverEntryPoint("cuTensorMapEncodeTiled", (void**)&enc, cudaEnableDefault, &q);
    cudaGetSymbolAddress(&scr, g_scr);
    cudaFuncSetAttribute(main_kernel, cudaFuncAttributeMaxDynamicSharedMemorySize, M_SMEM);
    rmt_setup();
  }
  rmt_launch(enc, d_in, scr, d_out);

  MainParams P;
  map2d(enc, &P.ckv, d_in[1], SEQ, 512, 128);
  map3d(enc, &P.wuk, d_in[3], 512, HDALL, 64, 2);
  map3d(enc, &P.wuv, d_in[4], 512, HDALL, 64, 2);
  map2d(enc, &P.ax, d_in[0], SEQ, DM, 64);
  map2d(enc, &P.wq, d_in[2], DM, HDALL, 64);
  map2d(enc, &P.scr, scr, 4 * SEQ, HDALL, 128);
  map3d(enc, &P.woa, d_in[5], HDALL, DM, 32, 3);
  map3d(enc, &P.wob, d_in[11], HDALL, DM, 32, 3);
  map2d(enc, &P.scr_st, scr, 4 * SEQ, HDALL, ST_ROWS);
  map2d(enc, &P.out_st, d_out, SEQ, 2 * DM, ST_ROWS);
  map3d(enc, &P.woa2, d_in[5], HDALL, DM, 32, 2);
  map3d(enc, &P.wob2, d_in[11], HDALL, DM, 32, 2);
  P.ntask = build_tasks(P.tasks);

  cudaLaunchConfig_t cfg = {};
  cfg.gridDim = dim3(2 * NCL);
  cfg.blockDim = dim3(384);
  cfg.dynamicSmemBytes = M_SMEM;
  cfg.stream = cudaStreamPerThread;
  cudaLaunchAttribute at[1];
  at[0].id = cudaLaunchAttributeProgrammaticStreamSerialization;
  at[0].val.programmaticStreamSerializationAllowed = 1;
  cfg.attrs = at;
  cfg.numAttrs = 1;
#ifdef DEV_SERIAL
  cfg.numAttrs = 0;
#endif
  cudaLaunchKernelEx(&cfg, main_kernel, P);
}
```

```cpp
#include <cuda_runtime.h>
#include <cuda_bf16.h>
#include <cuda.h>
#include <stdint.h>
#ifdef DEV_ORDER
#include <stdio.h>
#include <stdlib.h>
#endif

namespace {

constexpr int SEQ = 2048, DM = 576, HDALL = 4096;

__device__ __nv_bfloat16 g_scr[4ull * SEQ * HDALL];
constexpr int SY_Q = 0, SY_EXIT = 16, SY_KV = 32, SY_CTX = 32 + 256, SY_OX = 32 + 512, SY_N = 32 + 512 + 32;
__device__ unsigned g_sync[SY_N];

#ifdef DEV_END
__device__ long long g_end[512];
#define TRE(i) do { long long c_; asm volatile("mov.u64 %0, %%globaltimer;" : "=l"(c_)); g_end[i] = c_; } while (0)
#else
#define TRE(i)
#endif
#ifdef DEV_TRACE
__device__ long long g_trace[132 * 4096];
#ifdef DEV_TRF
#define TRF(slot) do { if (w4 == 0 && ti < 60) { uint32_t c_; asm volatile("mov.u32 %0, %%clock;" : "=r"(c_)::"memory"); if (elect()) g_trace[blockIdx.x * 4096 + 2048 + ti * 32 + wg * 16 + (slot)] = c_; __syncwarp(); } } while (0)
#else
#define TRF(slot)
#endif
#define TRM(slot) do { if ((threadIdx.x & 31) == 0) { long long c_; asm volatile("mov.u64 %0, %%globaltimer;" : "=l"(c_)); g_trace[blockIdx.x * 4096 + 4080 + (slot)] = c_; } } while (0)
#else
#define TRM(slot)
#define TRF(slot)
#endif

__device__ __forceinline__ void wgmma_ss_n256_a0b1(float (&d)[128], uint64_t da, uint64_t db, int sc) {
  asm volatile("{.reg .pred p; setp.ne.b32 p, %130, 0; wgmma.mma_async.sync.aligned.m64n256k16.f32.bf16.bf16 {%0,%1,%2,%3,%4,%5,%6,%7,%8,%9,%10,%11,%12,%13,%14,%15,%16,%17,%18,%19,%20,%21,%22,%23,%24,%25,%26,%27,%28,%29,%30,%31,%32,%33,%34,%35,%36,%37,%38,%39,%40,%41,%42,%43,%44,%45,%46,%47,%48,%49,%50,%51,%52,%53,%54,%55,%56,%57,%58,%59,%60,%61,%62,%63,%64,%65,%66,%67,%68,%69,%70,%71,%72,%73,%74,%75,%76,%77,%78,%79,%80,%81,%82,%83,%84,%85,%86,%87,%88,%89,%90,%91,%92,%93,%94,%95,%96,%97,%98,%99,%100,%101,%102,%103,%104,%105,%106,%107,%108,%109,%110,%111,%112,%113,%114,%115,%116,%117,%118,%119,%120,%121,%122,%123,%124,%125,%126,%127}, %128, %129, p, 1, 1, 0, 1;}"
    : "+f"(d[0]),"+f"(d[1]),"+f"(d[2]),"+f"(d[3]),"+f"(d[4]),"+f"(d[5]),"+f"(d[6]),"+f"(d[7]),"+f"(d[8]),"+f"(d[9]),"+f"(d[10]),"+f"(d[11]),"+f"(d[12]),"+f"(d[13]),"+f"(d[14]),"+f"(d[15]),"+f"(d[16]),"+f"(d[17]),"+f"(d[18]),"+f"(d[19]),"+f"(d[20]),"+f"(d[21]),"+f"(d[22]),"+f"(d[23]),"+f"(d[24]),"+f"(d[25]),"+f"(d[26]),"+f"(d[27]),"+f"(d[28]),"+f"(d[29]),"+f"(d[30]),"+f"(d[31]),"+f"(d[32]),"+f"(d[33]),"+f"(d[34]),"+f"(d[35]),"+f"(d[36]),"+f"(d[37]),"+f"(d[38]),"+f"(d[39]),"+f"(d[40]),"+f"(d[41]),"+f"(d[42]),"+f"(d[43]),"+f"(d[44]),"+f"(d[45]),"+f"(d[46]),"+f"(d[47]),"+f"(d[48]),"+f"(d[49]),"+f"(d[50]),"+f"(d[51]),"+f"(d[52]),"+f"(d[53]),"+f"(d[54]),"+f"(d[55]),"+f"(d[56]),"+f"(d[57]),"+f"(d[58]),"+f"(d[59]),"+f"(d[60]),"+f"(d[61]),"+f"(d[62]),"+f"(d[63]),"+f"(d[64]),"+f"(d[65]),"+f"(d[66]),"+f"(d[67]),"+f"(d[68]),"+f"(d[69]),"+f"(d[70]),"+f"(d[71]),"+f"(d[72]),"+f"(d[73]),"+f"(d[74]),"+f"(d[75]),"+f"(d[76]),"+f"(d[77]),"+f"(d[78]),"+f"(d[79]),"+f"(d[80]),"+f"(d[81]),"+f"(d[82]),"+f"(d[83]),"+f"(d[84]),"+f"(d[85]),"+f"(d[86]),"+f"(d[87]),"+f"(d[88]),"+f"(d[89]),"+f"(d[90]),"+f"(d[91]),"+f"(d[92]),"+f"(d[93]),"+f"(d[94]),"+f"(d[95]),"+f"(d[96]),"+f"(d[97]),"+f"(d[98]),"+f"(d[99]),"+f"(d[100]),"+f"(d[101]),"+f"(d[102]),"+f"(d[103]),"+f"(d[104]),"+f"(d[105]),"+f"(d[106]),"+f"(d[107]),"+f"(d[108]),"+f"(d[109]),"+f"(d[110]),"+f"(d[111]),"+f"(d[112]),"+f"(d[113]),"+f"(d[114]),"+f"(d[115]),"+f"(d[116]),"+f"(d[117]),"+f"(d[118]),"+f"(d[119]),"+f"(d[120]),"+f"(d[121]),"+f"(d[122]),"+f"(d[123]),"+f"(d[124]),"+f"(d[125]),"+f"(d[126]),"+f"(d[127])
    : "l"(da), "l"(db), "r"(sc));
}
__device__ __forceinline__ void wgmma_ss_n192_a0b1(float (&d)[96], uint64_t da, uint64_t db, int sc) {
  asm volatile("{.reg .pred p; setp.ne.b32 p, %98, 0; wgmma.mma_async.sync.aligned.m64n192k16.f32.bf16.bf16 {%0,%1,%2,%3,%4,%5,%6,%7,%8,%9,%10,%11,%12,%13,%14,%15,%16,%17,%18,%19,%20,%21,%22,%23,%24,%25,%26,%27,%28,%29,%30,%31,%32,%33,%34,%35,%36,%37,%38,%39,%40,%41,%42,%43,%44,%45,%46,%47,%48,%49,%50,%51,%52,%53,%54,%55,%56,%57,%58,%59,%60,%61,%62,%63,%64,%65,%66,%67,%68,%69,%70,%71,%72,%73,%74,%75,%76,%77,%78,%79,%80,%81,%82,%83,%84,%85,%86,%87,%88,%89,%90,%91,%92,%93,%94,%95}, %96, %97, p, 1, 1, 0, 1;}"
    : "+f"(d[0]),"+f"(d[1]),"+f"(d[2]),"+f"(d[3]),"+f"(d[4]),"+f"(d[5]),"+f"(d[6]),"+f"(d[7]),"+f"(d[8]),"+f"(d[9]),"+f"(d[10]),"+f"(d[11]),"+f"(d[12]),"+f"(d[13]),"+f"(d[14]),"+f"(d[15]),"+f"(d[16]),"+f"(d[17]),"+f"(d[18]),"+f"(d[19]),"+f"(d[20]),"+f"(d[21]),"+f"(d[22]),"+f"(d[23]),"+f"(d[24]),"+f"(d[25]),"+f"(d[26]),"+f"(d[27]),"+f"(d[28]),"+f"(d[29]),"+f"(d[30]),"+f"(d[31]),"+f"(d[32]),"+f"(d[33]),"+f"(d[34]),"+f"(d[35]),"+f"(d[36]),"+f"(d[37]),"+f"(d[38]),"+f"(d[39]),"+f"(d[40]),"+f"(d[41]),"+f"(d[42]),"+f"(d[43]),"+f"(d[44]),"+f"(d[45]),"+f"(d[46]),"+f"(d[47]),"+f"(d[48]),"+f"(d[49]),"+f"(d[50]),"+f"(d[51]),"+f"(d[52]),"+f"(d[53]),"+f"(d[54]),"+f"(d[55]),"+f"(d[56]),"+f"(d[57]),"+f"(d[58]),"+f"(d[59]),"+f"(d[60]),"+f"(d[61]),"+f"(d[62]),"+f"(d[63]),"+f"(d[64]),"+f"(d[65]),"+f"(d[66]),"+f"(d[67]),"+f"(d[68]),"+f"(d[69]),"+f"(d[70]),"+f"(d[71]),"+f"(d[72]),"+f"(d[73]),"+f"(d[74]),"+f"(d[75]),"+f"(d[76]),"+f"(d[77]),"+f"(d[78]),"+f"(d[79]),"+f"(d[80]),"+f"(d[81]),"+f"(d[82]),"+f"(d[83]),"+f"(d[84]),"+f"(d[85]),"+f"(d[86]),"+f"(d[87]),"+f"(d[88]),"+f"(d[89]),"+f"(d[90]),"+f"(d[91]),"+f"(d[92]),"+f"(d[93]),"+f"(d[94]),"+f"(d[95])
    : "l"(da), "l"(db), "r"(sc));
}
__device__ __forceinline__ void wgmma_rs_n64_b0(float (&d)[32], uint32_t a0, uint32_t a1, uint32_t a2, uint32_t a3, uint64_t db, int sc) {
  asm volatile("{.reg .pred p; setp.ne.b32 p, %37, 0; wgmma.mma_async.sync.aligned.m64n64k16.f32.bf16.bf16 {%0,%1,%2,%3,%4,%5,%6,%7,%8,%9,%10,%11,%12,%13,%14,%15,%16,%17,%18,%19,%20,%21,%22,%23,%24,%25,%26,%27,%28,%29,%30,%31}, {%32,%33,%34,%35}, %36, p, 1, 1, 0;}"
    : "+f"(d[0]),"+f"(d[1]),"+f"(d[2]),"+f"(d[3]),"+f"(d[4]),"+f"(d[5]),"+f"(d[6]),"+f"(d[7]),"+f"(d[8]),"+f"(d[9]),"+f"(d[10]),"+f"(d[11]),"+f"(d[12]),"+f"(d[13]),"+f"(d[14]),"+f"(d[15]),"+f"(d[16]),"+f"(d[17]),"+f"(d[18]),"+f"(d[19]),"+f"(d[20]),"+f"(d[21]),"+f"(d[22]),"+f"(d[23]),"+f"(d[24]),"+f"(d[25]),"+f"(d[26]),"+f"(d[27]),"+f"(d[28]),"+f"(d[29]),"+f"(d[30]),"+f"(d[31])
    : "r"(a0), "r"(a1), "r"(a2), "r"(a3), "l"(db), "r"(sc));
}
__device__ __forceinline__ void wgmma_ss_n128_a0b1(float (&d)[64], uint64_t da, uint64_t db, int sc) {
  asm volatile("{.reg .pred p; setp.ne.b32 p, %66, 0; wgmma.mma_async.sync.aligned.m64n128k16.f32.bf16.bf16 {%0,%1,%2,%3,%4,%5,%6,%7,%8,%9,%10,%11,%12,%13,%14,%15,%16,%17,%18,%19,%20,%21,%22,%23,%24,%25,%26,%27,%28,%29,%30,%31,%32,%33,%34,%35,%36,%37,%38,%39,%40,%41,%42,%43,%44,%45,%46,%47,%48,%49,%50,%51,%52,%53,%54,%55,%56,%57,%58,%59,%60,%61,%62,%63}, %64, %65, p, 1, 1, 0, 1;}"
    : "+f"(d[0]),"+f"(d[1]),"+f"(d[2]),"+f"(d[3]),"+f"(d[4]),"+f"(d[5]),"+f"(d[6]),"+f"(d[7]),"+f"(d[8]),"+f"(d[9]),"+f"(d[10]),"+f"(d[11]),"+f"(d[12]),"+f"(d[13]),"+f"(d[14]),"+f"(d[15]),"+f"(d[16]),"+f"(d[17]),"+f"(d[18]),"+f"(d[19]),"+f"(d[20]),"+f"(d[21]),"+f"(d[22]),"+f"(d[23]),"+f"(d[24]),"+f"(d[25]),"+f"(d[26]),"+f"(d[27]),"+f"(d[28]),"+f"(d[29]),"+f"(d[30]),"+f"(d[31]),"+f"(d[32]),"+f"(d[33]),"+f"(d[34]),"+f"(d[35]),"+f"(d[36]),"+f"(d[37]),"+f"(d[38]),"+f"(d[39]),"+f"(d[40]),"+f"(d[41]),"+f"(d[42]),"+f"(d[43]),"+f"(d[44]),"+f"(d[45]),"+f"(d[46]),"+f"(d[47]),"+f"(d[48]),"+f"(d[49]),"+f"(d[50]),"+f"(d[51]),"+f"(d[52]),"+f"(d[53]),"+f"(d[54]),"+f"(d[55]),"+f"(d[56]),"+f"(d[57]),"+f"(d[58]),"+f"(d[59]),"+f"(d[60]),"+f"(d[61]),"+f"(d[62]),"+f"(d[63])
    : "l"(da), "l"(db), "r"(sc));
}
__device__ __forceinline__ void wgmma_rs_n128_b0(float (&d)[64], uint32_t a0, uint32_t a1, uint32_t a2, uint32_t a3, uint64_t db, int sc) {
  asm volatile("{.reg .pred p; setp.ne.b32 p, %69, 0; wgmma.mma_async.sync.aligned.m64n128k16.f32.bf16.bf16 {%0,%1,%2,%3,%4,%5,%6,%7,%8,%9,%10,%11,%12,%13,%14,%15,%16,%17,%18,%19,%20,%21,%22,%23,%24,%25,%26,%27,%28,%29,%30,%31,%32,%33,%34,%35,%36,%37,%38,%39,%40,%41,%42,%43,%44,%45,%46,%47,%48,%49,%50,%51,%52,%53,%54,%55,%56,%57,%58,%59,%60,%61,%62,%63}, {%64,%65,%66,%67}, %68, p, 1, 1, 0;}"
    : "+f"(d[0]),"+f"(d[1]),"+f"(d[2]),"+f"(d[3]),"+f"(d[4]),"+f"(d[5]),"+f"(d[6]),"+f"(d[7]),"+f"(d[8]),"+f"(d[9]),"+f"(d[10]),"+f"(d[11]),"+f"(d[12]),"+f"(d[13]),"+f"(d[14]),"+f"(d[15]),"+f"(d[16]),"+f"(d[17]),"+f"(d[18]),"+f"(d[19]),"+f"(d[20]),"+f"(d[21]),"+f"(d[22]),"+f"(d[23]),"+f"(d[24]),"+f"(d[25]),"+f"(d[26]),"+f"(d[27]),"+f"(d[28]),"+f"(d[29]),"+f"(d[30]),"+f"(d[31]),"+f"(d[32]),"+f"(d[33]),"+f"(d[34]),"+f"(d[35]),"+f"(d[36]),"+f"(d[37]),"+f"(d[38]),"+f"(d[39]),"+f"(d[40]),"+f"(d[41]),"+f"(d[42]),"+f"(d[43]),"+f"(d[44]),"+f"(d[45]),"+f"(d[46]),"+f"(d[47]),"+f"(d[48]),"+f"(d[49]),"+f"(d[50]),"+f"(d[51]),"+f"(d[52]),"+f"(d[53]),"+f"(d[54]),"+f"(d[55]),"+f"(d[56]),"+f"(d[57]),"+f"(d[58]),"+f"(d[59]),"+f"(d[60]),"+f"(d[61]),"+f"(d[62]),"+f"(d[63])
    : "r"(a0), "r"(a1), "r"(a2), "r"(a3), "l"(db), "r"(sc));
}
__device__ __forceinline__ void wgmma_rs_n128_b1(float (&d)[64], uint32_t a0, uint32_t a1, uint32_t a2, uint32_t a3, uint64_t db, int sc) {
  asm volatile("{.reg .pred p; setp.ne.b32 p, %69, 0; wgmma.mma_async.sync.aligned.m64n128k16.f32.bf16.bf16 {%0,%1,%2,%3,%4,%5,%6,%7,%8,%9,%10,%11,%12,%13,%14,%15,%16,%17,%18,%19,%20,%21,%22,%23,%24,%25,%26,%27,%28,%29,%30,%31,%32,%33,%34,%35,%36,%37,%38,%39,%40,%41,%42,%43,%44,%45,%46,%47,%48,%49,%50,%51,%52,%53,%54,%55,%56,%57,%58,%59,%60,%61,%62,%63}, {%64,%65,%66,%67}, %68, p, 1, 1, 1;}"
    : "+f"(d[0]),"+f"(d[1]),"+f"(d[2]),"+f"(d[3]),"+f"(d[4]),"+f"(d[5]),"+f"(d[6]),"+f"(d[7]),"+f"(d[8]),"+f"(d[9]),"+f"(d[10]),"+f"(d[11]),"+f"(d[12]),"+f"(d[13]),"+f"(d[14]),"+f"(d[15]),"+f"(d[16]),"+f"(d[17]),"+f"(d[18]),"+f"(d[19]),"+f"(d[20]),"+f"(d[21]),"+f"(d[22]),"+f"(d[23]),"+f"(d[24]),"+f"(d[25]),"+f"(d[26]),"+f"(d[27]),"+f"(d[28]),"+f"(d[29]),"+f"(d[30]),"+f"(d[31]),"+f"(d[32]),"+f"(d[33]),"+f"(d[34]),"+f"(d[35]),"+f"(d[36]),"+f"(d[37]),"+f"(d[38]),"+f"(d[39]),"+f"(d[40]),"+f"(d[41]),"+f"(d[42]),"+f"(d[43]),"+f"(d[44]),"+f"(d[45]),"+f"(d[46]),"+f"(d[47]),"+f"(d[48]),"+f"(d[49]),"+f"(d[50]),"+f"(d[51]),"+f"(d[52]),"+f"(d[53]),"+f"(d[54]),"+f"(d[55]),"+f"(d[56]),"+f"(d[57]),"+f"(d[58]),"+f"(d[59]),"+f"(d[60]),"+f"(d[61]),"+f"(d[62]),"+f"(d[63])
    : "r"(a0), "r"(a1), "r"(a2), "r"(a3), "l"(db), "r"(sc));
}
__device__ __forceinline__ void wgmma_rs_n32_b0(float (&d)[16], uint32_t a0, uint32_t a1, uint32_t a2, uint32_t a3, uint64_t db, int sc) {
  asm volatile("{.reg .pred p; setp.ne.b32 p, %21, 0; wgmma.mma_async.sync.aligned.m64n32k16.f32.bf16.bf16 {%0,%1,%2,%3,%4,%5,%6,%7,%8,%9,%10,%11,%12,%13,%14,%15}, {%16,%17,%18,%19}, %20, p, 1, 1, 0;}"
    : "+f"(d[0]),"+f"(d[1]),"+f"(d[2]),"+f"(d[3]),"+f"(d[4]),"+f"(d[5]),"+f"(d[6]),"+f"(d[7]),"+f"(d[8]),"+f"(d[9]),"+f"(d[10]),"+f"(d[11]),"+f"(d[12]),"+f"(d[13]),"+f"(d[14]),"+f"(d[15])
    : "r"(a0), "r"(a1), "r"(a2), "r"(a3), "l"(db), "r"(sc));
}
__device__ __forceinline__ void wgmma_ss_n32_a1b0(float (&d)[16], uint64_t da, uint64_t db, int sc) {
  asm volatile("{.reg .pred p; setp.ne.b32 p, %18, 0; wgmma.mma_async.sync.aligned.m64n32k16.f32.bf16.bf16 {%0,%1,%2,%3,%4,%5,%6,%7,%8,%9,%10,%11,%12,%13,%14,%15}, %16, %17, p, 1, 1, 1, 0;}"
    : "+f"(d[0]),"+f"(d[1]),"+f"(d[2]),"+f"(d[3]),"+f"(d[4]),"+f"(d[5]),"+f"(d[6]),"+f"(d[7]),"+f"(d[8]),"+f"(d[9]),"+f"(d[10]),"+f"(d[11]),"+f"(d[12]),"+f"(d[13]),"+f"(d[14]),"+f"(d[15])
    : "l"(da), "l"(db), "r"(sc));
}
__device__ __forceinline__ void wgmma_ss_n40_a1b0(float (&d)[20], uint64_t da, uint64_t db, int sc) {
  asm volatile("{.reg .pred p; setp.ne.b32 p, %22, 0; wgmma.mma_async.sync.aligned.m64n40k16.f32.bf16.bf16 {%0,%1,%2,%3,%4,%5,%6,%7,%8,%9,%10,%11,%12,%13,%14,%15,%16,%17,%18,%19}, %20, %21, p, 1, 1, 1, 0;}"
    : "+f"(d[0]),"+f"(d[1]),"+f"(d[2]),"+f"(d[3]),"+f"(d[4]),"+f"(d[5]),"+f"(d[6]),"+f"(d[7]),"+f"(d[8]),"+f"(d[9]),"+f"(d[10]),"+f"(d[11]),"+f"(d[12]),"+f"(d[13]),"+f"(d[14]),"+f"(d[15]),"+f"(d[16]),"+f"(d[17]),"+f"(d[18]),"+f"(d[19])
    : "l"(da), "l"(db), "r"(sc));
}
__device__ __forceinline__ void wgmma_ss_n40_a1b1(float (&d)[20], uint64_t da, uint64_t db, int sc) {
  asm volatile("{.reg .pred p; setp.ne.b32 p, %22, 0; wgmma.mma_async.sync.aligned.m64n40k16.f32.bf16.bf16 {%0,%1,%2,%3,%4,%5,%6,%7,%8,%9,%10,%11,%12,%13,%14,%15,%16,%17,%18,%19}, %20, %21, p, 1, 1, 1, 1;}"
    : "+f"(d[0]),"+f"(d[1]),"+f"(d[2]),"+f"(d[3]),"+f"(d[4]),"+f"(d[5]),"+f"(d[6]),"+f"(d[7]),"+f"(d[8]),"+f"(d[9]),"+f"(d[10]),"+f"(d[11]),"+f"(d[12]),"+f"(d[13]),"+f"(d[14]),"+f"(d[15]),"+f"(d[16]),"+f"(d[17]),"+f"(d[18]),"+f"(d[19])
    : "l"(da), "l"(db), "r"(sc));
}
__device__ __forceinline__ void wgmma_rs_n40_b0(float (&d)[20], uint32_t a0, uint32_t a1, uint32_t a2, uint32_t a3, uint64_t db, int sc) {
  asm volatile("{.reg .pred p; setp.ne.b32 p, %25, 0; wgmma.mma_async.sync.aligned.m64n40k16.f32.bf16.bf16 {%0,%1,%2,%3,%4,%5,%6,%7,%8,%9,%10,%11,%12,%13,%14,%15,%16,%17,%18,%19}, {%20,%21,%22,%23}, %24, p, 1, 1, 0;}"
    : "+f"(d[0]),"+f"(d[1]),"+f"(d[2]),"+f"(d[3]),"+f"(d[4]),"+f"(d[5]),"+f"(d[6]),"+f"(d[7]),"+f"(d[8]),"+f"(d[9]),"+f"(d[10]),"+f"(d[11]),"+f"(d[12]),"+f"(d[13]),"+f"(d[14]),"+f"(d[15]),"+f"(d[16]),"+f"(d[17]),"+f"(d[18]),"+f"(d[19])
    : "r"(a0), "r"(a1), "r"(a2), "r"(a3), "l"(db), "r"(sc));
}
__device__ __forceinline__ void wgmma_ssz_n256_a0b1(float (&d)[128], uint64_t da, uint64_t db) {
  asm volatile("{.reg .pred p; setp.ne.b32 p, 0, 0; wgmma.mma_async.sync.aligned.m64n256k16.f32.bf16.bf16 {%0,%1,%2,%3,%4,%5,%6,%7,%8,%9,%10,%11,%12,%13,%14,%15,%16,%17,%18,%19,%20,%21,%22,%23,%24,%25,%26,%27,%28,%29,%30,%31,%32,%33,%34,%35,%36,%37,%38,%39,%40,%41,%42,%43,%44,%45,%46,%47,%48,%49,%50,%51,%52,%53,%54,%55,%56,%57,%58,%59,%60,%61,%62,%63,%64,%65,%66,%67,%68,%69,%70,%71,%72,%73,%74,%75,%76,%77,%78,%79,%80,%81,%82,%83,%84,%85,%86,%87,%88,%89,%90,%91,%92,%93,%94,%95,%96,%97,%98,%99,%100,%101,%102,%103,%104,%105,%106,%107,%108,%109,%110,%111,%112,%113,%114,%115,%116,%117,%118,%119,%120,%121,%122,%123,%124,%125,%126,%127}, %128, %129, p, 1, 1, 0, 1;}"
    : "=f"(d[0]),"=f"(d[1]),"=f"(d[2]),"=f"(d[3]),"=f"(d[4]),"=f"(d[5]),"=f"(d[6]),"=f"(d[7]),"=f"(d[8]),"=f"(d[9]),"=f"(d[10]),"=f"(d[11]),"=f"(d[12]),"=f"(d[13]),"=f"(d[14]),"=f"(d[15]),"=f"(d[16]),"=f"(d[17]),"=f"(d[18]),"=f"(d[19]),"=f"(d[20]),"=f"(d[21]),"=f"(d[22]),"=f"(d[23]),"=f"(d[24]),"=f"(d[25]),"=f"(d[26]),"=f"(d[27]),"=f"(d[28]),"=f"(d[29]),"=f"(d[30]),"=f"(d[31]),"=f"(d[32]),"=f"(d[33]),"=f"(d[34]),"=f"(d[35]),"=f"(d[36]),"=f"(d[37]),"=f"(d[38]),"=f"(d[39]),"=f"(d[40]),"=f"(d[41]),"=f"(d[42]),"=f"(d[43]),"=f"(d[44]),"=f"(d[45]),"=f"(d[46]),"=f"(d[47]),"=f"(d[48]),"=f"(d[49]),"=f"(d[50]),"=f"(d[51]),"=f"(d[52]),"=f"(d[53]),"=f"(d[54]),"=f"(d[55]),"=f"(d[56]),"=f"(d[57]),"=f"(d[58]),"=f"(d[59]),"=f"(d[60]),"=f"(d[61]),"=f"(d[62]),"=f"(d[63]),"=f"(d[64]),"=f"(d[65]),"=f"(d[66]),"=f"(d[67]),"=f"(d[68]),"=f"(d[69]),"=f"(d[70]),"=f"(d[71]),"=f"(d[72]),"=f"(d[73]),"=f"(d[74]),"=f"(d[75]),"=f"(d[76]),"=f"(d[77]),"=f"(d[78]),"=f"(d[79]),"=f"(d[80]),"=f"(d[81]),"=f"(d[82]),"=f"(d[83]),"=f"(d[84]),"=f"(d[85]),"=f"(d[86]),"=f"(d[87]),"=f"(d[88]),"=f"(d[89]),"=f"(d[90]),"=f"(d[91]),"=f"(d[92]),"=f"(d[93]),"=f"(d[94]),"=f"(d[95]),"=f"(d[96]),"=f"(d[97]),"=f"(d[98]),"=f"(d[99]),"=f"(d[100]),"=f"(d[101]),"=f"(d[102]),"=f"(d[103]),"=f"(d[104]),"=f"(d[105]),"=f"(d[106]),"=f"(d[107]),"=f"(d[108]),"=f"(d[109]),"=f"(d[110]),"=f"(d[111]),"=f"(d[112]),"=f"(d[113]),"=f"(d[114]),"=f"(d[115]),"=f"(d[116]),"=f"(d[117]),"=f"(d[118]),"=f"(d[119]),"=f"(d[120]),"=f"(d[121]),"=f"(d[122]),"=f"(d[123]),"=f"(d[124]),"=f"(d[125]),"=f"(d[126]),"=f"(d[127])
    : "l"(da), "l"(db));
}
__device__ __forceinline__ void wgmma_ssz_n128_a0b1(float (&d)[64], uint64_t da, uint64_t db) {
  asm volatile("{.reg .pred p; setp.ne.b32 p, 0, 0; wgmma.mma_async.sync.aligned.m64n128k16.f32.bf16.bf16 {%0,%1,%2,%3,%4,%5,%6,%7,%8,%9,%10,%11,%12,%13,%14,%15,%16,%17,%18,%19,%20,%21,%22,%23,%24,%25,%26,%27,%28,%29,%30,%31,%32,%33,%34,%35,%36,%37,%38,%39,%40,%41,%42,%43,%44,%45,%46,%47,%48,%49,%50,%51,%52,%53,%54,%55,%56,%57,%58,%59,%60,%61,%62,%63}, %64, %65, p, 1, 1, 0, 1;}"
    : "=f"(d[0]),"=f"(d[1]),"=f"(d[2]),"=f"(d[3]),"=f"(d[4]),"=f"(d[5]),"=f"(d[6]),"=f"(d[7]),"=f"(d[8]),"=f"(d[9]),"=f"(d[10]),"=f"(d[11]),"=f"(d[12]),"=f"(d[13]),"=f"(d[14]),"=f"(d[15]),"=f"(d[16]),"=f"(d[17]),"=f"(d[18]),"=f"(d[19]),"=f"(d[20]),"=f"(d[21]),"=f"(d[22]),"=f"(d[23]),"=f"(d[24]),"=f"(d[25]),"=f"(d[26]),"=f"(d[27]),"=f"(d[28]),"=f"(d[29]),"=f"(d[30]),"=f"(d[31]),"=f"(d[32]),"=f"(d[33]),"=f"(d[34]),"=f"(d[35]),"=f"(d[36]),"=f"(d[37]),"=f"(d[38]),"=f"(d[39]),"=f"(d[40]),"=f"(d[41]),"=f"(d[42]),"=f"(d[43]),"=f"(d[44]),"=f"(d[45]),"=f"(d[46]),"=f"(d[47]),"=f"(d[48]),"=f"(d[49]),"=f"(d[50]),"=f"(d[51]),"=f"(d[52]),"=f"(d[53]),"=f"(d[54]),"=f"(d[55]),"=f"(d[56]),"=f"(d[57]),"=f"(d[58]),"=f"(d[59]),"=f"(d[60]),"=f"(d[61]),"=f"(d[62]),"=f"(d[63])
    : "l"(da), "l"(db));
}


__device__ __forceinline__ void wg_fence() { asm volatile("wgmma.fence.sync.aligned;" ::: "memory"); }
__device__ __forceinline__ void wg_commit() { asm volatile("wgmma.commit_group.sync.aligned;" ::: "memory"); }
template <int N> __device__ __forceinline__ void wg_wait() { asm volatile("wgmma.wait_group.sync.aligned %0;" ::"n"(N) : "memory"); }
template <int N> __device__ __forceinline__ void fence_regs(float (&d)[N]) {
#pragma unroll
  for (int i = 0; i < N; i++) asm volatile("" : "+f"(d[i])::"memory");
}
template <int N> __device__ __forceinline__ void fence_regs(uint32_t (&d)[N]) {
#pragma unroll
  for (int i = 0; i < N; i++) asm volatile("" : "+r"(d[i])::"memory");
}
__device__ __forceinline__ uint64_t mk_desc(uint32_t lo, uint32_t hi) {
  uint64_t d;
  asm("mov.b64 %0, {%1,%2};" : "=l"(d) : "r"(lo), "r"(hi));
  return d;
}
constexpr uint32_t DHI_SW128 = (1024u >> 4) | (1u << 30);
__device__ __forceinline__ uint32_t desc_lo(uint32_t addr, uint32_t lbo) { return ((addr & 0x3FFFF) >> 4) | ((lbo >> 4) << 16); }

__device__ __forceinline__ void mbar_init(uint32_t bar, uint32_t cnt) { asm volatile("mbarrier.init.shared::cta.b64 [%0], %1;" ::"r"(bar), "r"(cnt) : "memory"); }
__device__ __forceinline__ uint32_t mbar_try(uint32_t bar, uint32_t par) {
  uint32_t ok;
  asm volatile("{.reg .pred p; mbarrier.try_wait.parity.shared::cta.b64 p, [%1], %2; selp.u32 %0, 1, 0, p;}" : "=r"(ok) : "r"(bar), "r"(par) : "memory");
  return ok;
}
__device__ __noinline__ void mbar_wait_slow(uint32_t bar, uint32_t par) {
  for (int i = 0; i < (1 << 22); i++)
    if (mbar_try(bar, par)) return;
  __trap();
}
__device__ __forceinline__ void mbar_wait(uint32_t bar, uint32_t par) {
  asm volatile(
      "{\n.reg .pred p;\n.reg .u32 c;\n"
      "mbarrier.try_wait.parity.shared::cta.b64 p, [%0], %1;\n"
      "@p bra DONE;\n"
      "mov.u32 c, 0;\n"
      "LOOP:\n"
      "mbarrier.try_wait.parity.shared::cta.b64 p, [%0], %1;\n"
      "@p bra DONE;\n"
      "add.u32 c, c, 1;\n"
      "setp.lt.u32 p, c, 4000000;\n"
      "@p bra LOOP;\n"
      "trap;\n"
      "DONE:\n}" ::"r"(bar), "r"(par) : "memory");
}
__device__ __forceinline__ void mbar_wait2(uint32_t b0, uint32_t p0, uint32_t b1, uint32_t p1) {
  asm volatile(
      "{\n.reg .pred p, q;\n.reg .u32 c;\n"
      "mov.u32 c, 0;\n"
      "LOOP:\n"
      "mbarrier.try_wait.parity.shared::cta.b64 p, [%0], %1;\n"
      "mbarrier.try_wait.parity.shared::cta.b64 q, [%2], %3;\n"
      "and.pred p, p, q;\n"
      "@p bra DONE;\n"
      "add.u32 c, c, 1;\n"
      "setp.lt.u32 p, c, 4000000;\n"
      "@p bra LOOP;\n"
      "trap;\n"
      "DONE:\n}" ::"r"(b0), "r"(p0), "r"(b1), "r"(p1) : "memory");
}
__device__ __forceinline__ void mbar_wait_cl(uint32_t bar, uint32_t par) {
  asm volatile(
      "{\n.reg .pred p;\n.reg .u32 c;\n"
      "mbarrier.try_wait.parity.acquire.cluster.shared::cta.b64 p, [%0], %1;\n"
      "@p bra DONE;\n"
      "mov.u32 c, 0;\n"
      "LOOP:\n"
      "mbarrier.try_wait.parity.acquire.cluster.shared::cta.b64 p, [%0], %1;\n"
      "@p bra DONE;\n"
      "add.u32 c, c, 1;\n"
      "setp.lt.u32 p, c, 4000000;\n"
      "@p bra LOOP;\n"
      "trap;\n"
      "DONE:\n}" ::"r"(bar), "r"(par) : "memory");
}
__device__ __forceinline__ void mbar_arrive(uint32_t bar) { asm volatile("mbarrier.arrive.shared::cta.b64 _, [%0];" ::"r"(bar) : "memory"); }
__device__ __forceinline__ void mbar_arrive_cl(uint32_t bar) { asm volatile("mbarrier.arrive.shared::cluster.b64 _, [%0];" ::"r"(bar) : "memory"); }
__device__ __forceinline__ void mbar_expect(uint32_t bar, uint32_t bytes) { asm volatile("mbarrier.arrive.expect_tx.shared::cta.b64 _, [%0], %1;" ::"r"(bar), "r"(bytes) : "memory"); }
__device__ __forceinline__ void mbar_expect_cl(uint32_t bar, uint32_t bytes) { asm volatile("mbarrier.arrive.expect_tx.shared::cluster.b64 _, [%0], %1;" ::"r"(bar), "r"(bytes) : "memory"); }
__device__ __forceinline__ uint32_t mapa(uint32_t addr, uint32_t rank) {
  uint32_t r;
  asm("mapa.shared::cluster.u32 %0, %1, %2;" : "=r"(r) : "r"(addr), "r"(rank));
  return r;
}
__device__ __forceinline__ void st_async32(uint32_t addr, uint32_t v, uint32_t bar) {
  asm volatile("st.async.shared::cluster.mbarrier::complete_tx::bytes.b32 [%0], %1, [%2];" ::"r"(addr), "r"(v), "r"(bar) : "memory");
}
__device__ __forceinline__ void st_async64(uint32_t addr, uint32_t a, uint32_t b, uint32_t bar) {
  asm volatile("st.async.shared::cluster.mbarrier::complete_tx::bytes.v2.b32 [%0], {%1,%2}, [%3];" ::"r"(addr), "r"(a), "r"(b), "r"(bar) : "memory");
}
__device__ __forceinline__ void st_async128(uint32_t addr, uint32_t a, uint32_t b, uint32_t c, uint32_t d, uint32_t bar) {
  asm volatile("st.async.shared::cluster.mbarrier::complete_tx::bytes.v4.b32 [%0], {%1,%2,%3,%4}, [%5];" ::"r"(addr), "r"(a), "r"(b), "r"(c), "r"(d), "r"(bar) : "memory");
}
__device__ __forceinline__ void bar_sync(int id, int n) { asm volatile("bar.sync %0, %1;" ::"r"(id), "r"(n) : "memory"); }
__device__ __forceinline__ void bar_arrive(int id, int n) { asm volatile("bar.arrive %0, %1;" ::"r"(id), "r"(n) : "memory"); }
__device__ __forceinline__ void cluster_sync() { asm volatile("barrier.cluster.arrive.aligned;\nbarrier.cluster.wait.aligned;" ::: "memory"); }
__device__ __forceinline__ bool elect() {
  uint32_t p;
  asm volatile("{.reg .pred q; elect.sync _|q, 0xffffffff; selp.u32 %0, 1, 0, q;}" : "=r"(p));
  return p != 0;
}
__device__ __forceinline__ void fence_async_smem() { asm volatile("fence.proxy.async.shared::cta;" ::: "memory"); }
__device__ __forceinline__ void fence_async_all() { asm volatile("fence.proxy.async;" ::: "memory"); }
__device__ __forceinline__ void tma2d(uint32_t dst, const CUtensorMap* m, int c0, int c1, uint32_t bar) {
  asm volatile("cp.async.bulk.tensor.2d.shared::cluster.global.mbarrier::complete_tx::bytes [%0], [%1, {%2,%3}], [%4];" ::"r"(dst), "l"(m), "r"(c0), "r"(c1), "r"(bar) : "memory");
}
__device__ __forceinline__ void tma2d_mc(uint32_t dst, const CUtensorMap* m, int c0, int c1, uint32_t bar, uint16_t mask) {
  asm volatile("cp.async.bulk.tensor.2d.shared::cluster.global.mbarrier::complete_tx::bytes.multicast::cluster [%0], [%1, {%2,%3}], [%4], %5;" ::"r"(dst), "l"(m), "r"(c0), "r"(c1), "r"(bar), "h"(mask) : "memory");
}
__device__ __forceinline__ void tma3d(uint32_t dst, const CUtensorMap* m, int c0, int c1, int c2, uint32_t bar) {
  asm volatile("cp.async.bulk.tensor.3d.shared::cluster.global.mbarrier::complete_tx::bytes [%0], [%1, {%2,%3,%4}], [%5];" ::"r"(dst), "l"(m), "r"(c0), "r"(c1), "r"(c2), "r"(bar) : "memory");
}
__device__ __forceinline__ void tma3d_mc(uint32_t dst, const CUtensorMap* m, int c0, int c1, int c2, uint32_t bar, uint16_t mask) {
  asm volatile("cp.async.bulk.tensor.3d.shared::cluster.global.mbarrier::complete_tx::bytes.multicast::cluster [%0], [%1, {%2,%3,%4}], [%5], %6;" ::"r"(dst), "l"(m), "r"(c0), "r"(c1), "r"(c2), "r"(bar), "h"(mask) : "memory");
}
__device__ __forceinline__ uint32_t ld_acquire(const unsigned* p) {
  uint32_t v;
  asm volatile("ld.acquire.gpu.global.u32 %0, [%1];" : "=r"(v) : "l"(p) : "memory");
  return v;
}
__device__ __forceinline__ uint32_t pack_bf16(float lo, float hi) {
  uint32_t r;
  asm("cvt.rn.bf16x2.f32 %0, %1, %2;" : "=r"(r) : "f"(hi), "f"(lo));
  return r;
}
__device__ __forceinline__ float ex2(float x) {
  float y;
  asm("ex2.approx.ftz.f32 %0, %1;" : "=f"(y) : "f"(x));
  return y;
}
__device__ __forceinline__ float rcp(float x) {
  float y;
  asm("rcp.approx.ftz.f32 %0, %1;" : "=f"(y) : "f"(x));
  return y;
}
__device__ __forceinline__ void stg128(void* p, uint32_t a, uint32_t b, uint32_t c, uint32_t d) {
  asm volatile("st.global.v4.b32 [%0], {%1,%2,%3,%4};" ::"l"(p), "r"(a), "r"(b), "r"(c), "r"(d) : "memory");
}
__device__ __forceinline__ void sts128(uint32_t a, uint32_t x, uint32_t y, uint32_t z, uint32_t w) {
  asm volatile("st.shared.v4.b32 [%0], {%1,%2,%3,%4};" ::"r"(a), "r"(x), "r"(y), "r"(z), "r"(w) : "memory");
}
__device__ __forceinline__ void stsm4(uint32_t a, uint32_t r0, uint32_t r1, uint32_t r2, uint32_t r3) {
  asm volatile("stmatrix.sync.aligned.m8n8.x4.shared.b16 [%0], {%1,%2,%3,%4};" ::"r"(a), "r"(r0), "r"(r1), "r"(r2), "r"(r3) : "memory");
}
__device__ __forceinline__ void arrive_elect(uint32_t bar) {
  asm volatile("{.reg .pred q; elect.sync _|q, 0xffffffff; @q mbarrier.arrive.shared::cta.b64 _, [%0];}" ::"r"(bar) : "memory");
}
__device__ __forceinline__ void sched_fence(uint32_t v) { asm volatile("{.reg .pred p; setp.eq.u32 p, %0, 0; @p trap;}" ::"r"(v) : "memory"); }
template <int V> struct IC { static constexpr int value = V; };
template <int A, int B, class F> __device__ __forceinline__ void static_for(F&& f) {
  if constexpr (A < B) {
    f(IC<A>());
    static_for<A + 1, B>(f);
  }
}
__device__ __forceinline__ uint32_t lds32(uint32_t a) {
  uint32_t v;
  asm volatile("ld.shared.b32 %0, [%1];" : "=r"(v) : "r"(a) : "memory");
  return v;
}

constexpr int MAXTASK = 256 + 256 + 200;
constexpr int T_KV = 0, T_FA = 1, T_OA = 2, T_OB = 3, T_MA = 4, T_MB = 5;
constexpr uint32_t TASK_END = 0xFFFF;
constexpr int NCL = 34;
struct MainParams {
  CUtensorMap ckv, wuk, wuv, ax, wq, scr, woa, wob, scr_st, out_st, woa2, wob2;
  uint32_t ntask;
  uint16_t tasks[MAXTASK];
};

constexpr int M_GR = 16384, M_NG = 12;
constexpr int M_STG = M_GR * M_NG;
constexpr int M_BAR = M_STG + 32768;
constexpr int M_FULL = M_BAR, M_EMPTY = M_BAR + 64, M_TFULL = M_BAR + 128, M_TEMPTY = M_BAR + 160, M_EPI = M_BAR + 192, M_SFREE = M_BAR + 224, M_GO = M_BAR + 240,
              M_TSLOT = M_BAR + 256;
constexpr int M_SMEM = M_BAR + 512 + 1024;
constexpr int OX_TARGET = 64;

#ifndef PF_ON
#define PF_ON 0
#endif
#ifndef ST_ROWS
#define ST_ROWS 16
#endif
#ifndef ST_DEPTH
#define ST_DEPTH 1
#endif
#ifndef KV_SKEW
#define KV_SKEW 7
#endif
#ifndef FM_NJ
#define FM_NJ 2
#endif
#ifndef Q_SKEW
#define Q_SKEW 6
#endif
struct Ring {
  uint32_t e, g;
  __device__ __forceinline__ uint32_t take(int z) {
    if (g + z > M_NG) g = 0;
    const uint32_t r = g;
    g += z;
    return r;
  }
  __device__ __forceinline__ uint32_t bar() const { return (e & 7) * 8; }
  __device__ __forceinline__ uint32_t par() const { return (e >> 3) & 1; }
};
__device__ __forceinline__ int task_entries(int type, int p) { return type == T_KV ? 9 : type == T_FA ? 9 + 2 * (2 * p + 2) : 65; }
__device__ __forceinline__ int entry_size(int type, int it) { return type == T_FA || (type == T_KV && it == 8) || type >= T_MA ? 2 : 3; }

__device__ __forceinline__ void need_flag(uint32_t& v, int bit, const unsigned* flag, unsigned target) {
  for (int it = 0; !((__ballot_sync(0xffffffffu, v >= target) >> bit) & 1); it++) {
    if (it > (1 << 21)) __trap();
    if (it) __nanosleep(40);
    v = ld_acquire(flag);
  }
}

constexpr float SM_C = 0.08838834764831845f * 1.4426950408889634f;
template <int NJ> __device__ __forceinline__ void softmax_max(const float (&s)[64], float& m0, float& m1, float& a0, float& a1, float& c0, float& c1) {
  float x0 = fmaxf(s[0], s[4]), y0 = fmaxf(s[1], s[5]), x1 = fmaxf(s[2], s[6]), y1 = fmaxf(s[3], s[7]);
#pragma unroll
  for (int j = 2; j < NJ; j++) {
    x0 = fmaxf(x0, s[4 * j]);
    y0 = fmaxf(y0, s[4 * j + 1]);
    x1 = fmaxf(x1, s[4 * j + 2]);
    y1 = fmaxf(y1, s[4 * j + 3]);
  }
  x0 = fmaxf(x0, y0);
  x1 = fmaxf(x1, y1);
  x0 = fmaxf(x0, __shfl_xor_sync(0xffffffffu, x0, 1));
  x1 = fmaxf(x1, __shfl_xor_sync(0xffffffffu, x1, 1));
  x0 = fmaxf(x0, __shfl_xor_sync(0xffffffffu, x0, 2));
  x1 = fmaxf(x1, __shfl_xor_sync(0xffffffffu, x1, 2));
  const float n0 = fmaxf(m0, x0), n1 = fmaxf(m1, x1);
  a0 = ex2((m0 - n0) * SM_C);
  a1 = ex2((m1 - n1) * SM_C);
  m0 = n0;
  m1 = n1;
  c0 = -n0 * SM_C;
  c1 = -n1 * SM_C;
}
template <int J0, int J1> __device__ __forceinline__ void softmax_exp(const float (&s)[64], uint32_t (&p)[32], float c0, float c1, float (&t)[4]) {
#pragma unroll
  for (int j = J0; j < J1; j++) {
    const float e0 = ex2(fmaf(s[4 * j], SM_C, c0)), e1 = ex2(fmaf(s[4 * j + 1], SM_C, c0));
    const float e2 = ex2(fmaf(s[4 * j + 2], SM_C, c1)), e3 = ex2(fmaf(s[4 * j + 3], SM_C, c1));
    p[2 * j] = pack_bf16(e0, e1);
    p[2 * j + 1] = pack_bf16(e2, e3);
    if (j == 0) { t[0] = e0; t[1] = e1; t[2] = e2; t[3] = e3; }
    else { t[0] += e0; t[1] += e1; t[2] += e2; t[3] += e3; }
  }
}
template <int I0, int I1> __device__ __forceinline__ void fence_part(uint32_t (&d)[32]) {
#pragma unroll
  for (int i = I0; i < I1; i++) asm volatile("" : "+r"(d[i])::"memory");
}
template <int J0, int J1, int N> __device__ __forceinline__ void stage_tile(const float (&d)[N], uint32_t a, float f0, float f1) {
#pragma unroll
  for (int j = J0; j < J1; j += 2)
    stsm4((a ^ (((j - J0) & 7) << 4)) + ((j - J0) >> 3) * 8192, pack_bf16(d[4 * j] * f0, d[4 * j + 1] * f0), pack_bf16(d[4 * j + 2] * f1, d[4 * j + 3] * f1),
          pack_bf16(d[4 * j + 4] * f0, d[4 * j + 5] * f0), pack_bf16(d[4 * j + 6] * f1, d[4 * j + 7] * f1));
}
template <int J0, int J1> __device__ __forceinline__ void causal_mask(float (&s)[64], int lim0) {
#pragma unroll
  for (int j = J0; j < J1; j++) {
    if (8 * j > lim0) s[4 * j] = -INFINITY;
    if (8 * j + 1 > lim0) s[4 * j + 1] = -INFINITY;
    if (8 * j > lim0 + 8) s[4 * j + 2] = -INFINITY;
    if (8 * j + 1 > lim0 + 8) s[4 * j + 3] = -INFINITY;
  }
}

__global__ void __cluster_dims__(2, 1, 1) __launch_bounds__(384, 1) main_kernel(const __grid_constant__ MainParams P) {
  extern __shared__ uint8_t smem_raw[];
  const uint32_t sb = ((uint32_t)__cvta_generic_to_shared(smem_raw) + 1023u) & ~1023u;
  const int warp = __shfl_sync(0xffffffffu, threadIdx.x >> 5, 0), lane = threadIdx.x & 31;
  uint32_t rank;
  asm("mov.u32 %0, %%cluster_ctarank;" : "=r"(rank));
  rank = __shfl_sync(0xffffffffu, rank, 0);
#ifdef DEV_TRACE
  if (threadIdx.x == 0) { long long c; asm volatile("mov.u64 %0, %%globaltimer;" : "=l"(c)); g_trace[blockIdx.x * 4096 + 4090] = c; }
#endif
  const uint32_t cluster = blockIdx.x >> 1;
  static_assert(M_EMPTY == M_FULL + 64 && M_TFULL == M_FULL + 128 && M_TEMPTY == M_FULL + 160 && M_EPI == M_FULL + 192 && M_SFREE == M_FULL + 224, "barriers");
  if (warp == 8 && elect()) {
#pragma unroll 1
    for (int i = 0; i < 4; i++) {
      const uint32_t st = sb + i * 3 * M_GR, fb = sb + M_FULL + 8 * i;
      mbar_init(fb, 1);
      mbar_expect(fb, 49152);
      tma2d(st, &P.ckv, i * 64, (cluster & 7) * 256 + rank * 128, fb);
      tma3d(st + 16384, &P.wuk, 0, i * 64, (cluster >> 3) * 2, fb);
      tma3d(st + 32768, &P.wuv, 0, i * 64, (cluster >> 3) * 2, fb);
    }
    asm volatile("fence.mbarrier_init.release.cluster;" ::: "memory");
  }
  const uint32_t task0 = cluster;
  if (warp >= 1 && warp < 8 && elect()) {
    const uint32_t b = sb + M_FULL + 32 * warp, cnt = (warp & 14) == 2 ? 16 : warp == 5 ? 22 : warp == 6 ? 4 : 1;
#pragma unroll
    for (int i = 0; i < 4; i++) mbar_init(b + 8 * i, cnt);
    asm volatile("fence.mbarrier_init.release.cluster;" ::: "memory");
  }
  __syncwarp();
  if (warp == 8) TRM(5);
  asm volatile("barrier.cluster.arrive.relaxed.aligned;" ::: "memory");
  auto started = [&]() { asm volatile("barrier.cluster.wait.aligned;" ::: "memory"); };
  const uint32_t tempty0 = mapa(sb + M_TEMPTY, 0);
  auto read_task = [&](int ti) -> uint32_t {
    if (ti == 0) return task0;
    mbar_wait(sb + M_TFULL + 8 * ((ti - 1) & 3), ((ti - 1) >> 2) & 1);
    return __shfl_sync(0xffffffffu, lds32(sb + M_TSLOT + 4 * ((ti - 1) & 3)), 0);
  };
  auto free_task = [&](int ti) {
    if (ti > 0 && lane == 0) mbar_arrive_cl(tempty0 + 8 * ((ti - 1) & 3));
  };

  if (warp >= 8) {
    asm volatile("setmaxnreg.dec.sync.aligned.u32 40;");
    if (warp == 8) {
      if (lane >= 3 && lane < 12) asm volatile("prefetch.tensormap [%0];" ::"l"(&P.ckv + lane) : "memory");
      __syncwarp();
      started();
      TRM(4);
      Ring r{0, 0};
      uint32_t lin = 0;
      uint32_t mypos = 0, mypar = 2;
      const uint32_t myempty = sb + M_EMPTY + 8 * (lane & 7);
      auto alloc = [&](int z, uint32_t& fb) -> uint32_t {
        if (r.g + z > M_NG) lin += M_NG - r.g;
        const uint32_t st = sb + r.take(z) * M_GR;
        const uint32_t need = mypar < 2 && lin + z - mypos > M_NG;
        for (int it = 0;; it++) {
          uint32_t ok;
          asm volatile("{.reg .pred p, q; setp.eq.u32 q, %3, 0; mov.pred p, q; @!q mbarrier.try_wait.parity.shared::cta.b64 p, [%1], %2; selp.u32 %0, 1, 0, p;}"
                       : "=r"(ok) : "r"(myempty), "r"(mypar), "r"(need) : "memory");
          if (__all_sync(0xffffffffu, ok)) break;
          if (it > 4000000) __trap();
        }
        mypar = need ? 2 : mypar;
        if (lane == (r.e & 7)) { mypos = lin; mypar = r.par(); }
        lin += z;
        fb = sb + M_FULL + r.bar();
        r.e++;
        return st;
      };
      auto go = [&]() { if (rank == 0) arrive_elect(sb + M_GO); };
      for (int ti = 0;; ti++) {
        const uint32_t task = read_task(ti);
        free_task(ti);
        if (task == TASK_END) break;
        const int type = task >> 12, nn = (task >> 8) & 15, h = (task >> 3) & 31, p = task & 7;
        uint32_t fb, fv = 0;
        if (type == T_KV) {
          const CUtensorMap* w = rank ? &P.wuv : &P.wuk;
          const int row = p * 256 + rank * 128;
#pragma unroll 1
          for (int k = 0; k < 512; k += 64) {
            const uint32_t st = alloc(3, fb);
            if ((ti > 0 || k >= 256) && elect()) {
              mbar_expect(fb, 49152);
              tma2d(st, &P.ckv, k, row, fb);
              tma3d_mc(st + 16384 + rank * 16384, w, 0, k, h * 2, fb, 3);
            }
            if (k == 384) go();
            if (PF_ON && ti == 0 && h < 4 && k == 192 && elect()) {
              asm volatile("cp.async.bulk.prefetch.tensor.3d.L2.global [%0, {0,%1,%2}];" ::"l"(w), "r"(p * 64), "r"((h + 4) * 2) : "memory");
              if (h == 0) asm volatile("cp.async.bulk.prefetch.tensor.3d.L2.global [%0, {0,%1,%2}];" ::"l"(w), "r"(p * 64), "r"(16) : "memory");
            }
            if (PF_ON && ti == 1 && h < 8 && k >= 192 && elect()) {
              const int c = (k - 192) / 32 + rank;
              if (c < 9) asm volatile("cp.async.bulk.prefetch.tensor.2d.L2.global [%0, {%1,%2}];" ::"l"(&P.ax), "r"(c * 64), "r"(p * 256 + (h & 3) * 64) : "memory");
              if (k == 192) asm volatile("cp.async.bulk.prefetch.tensor.2d.L2.global [%0, {%1,%2}];" ::"l"(&P.wq), "r"((h & 3) * 128 + rank * 64), "r"(p * 64) : "memory");
            }
            __syncwarp();
          }
          alloc(2, fb);
          arrive_elect(fb);
        } else if (type == T_FA) {
          const unsigned* flag = g_sync + SY_KV + h * 8 + (lane & 7);
          asm volatile("ld.relaxed.gpu.global.u32 %0, [%1];" : "=r"(fv) : "l"(flag) : "memory");
          const int r0 = p * 256 + rank * 64, r1 = p * 256 + 192 - rank * 64, col = h * 128 + rank * 64;
#pragma unroll 1
          for (int k = 0; k < 576; k += 64) {
            const uint32_t st = alloc(2, fb);
            if (elect()) {
              mbar_expect(fb, 32768);
              tma2d(st, &P.ax, k, r0, fb);
              tma2d(st + 8192, &P.ax, k, r1, fb);
              tma2d_mc(st + 16384 + rank * 8192, &P.wq, col, k, fb, 3);
            }
          }
          auto kv = [&](int row) {
            const uint32_t st = alloc(2, fb);
            if (elect()) {
              mbar_expect(fb, 32768);
              tma2d_mc(st + rank * 16384, &P.scr, col, row, fb, 3);
            }
          };
          need_flag(fv, p, flag, 4);
          kv((2 * p + 1) * 128);
#pragma unroll 1
          for (int j = 2 * p; j >= 0; j--) {
            need_flag(fv, j >> 1, flag, 4);
            if (j == 0) go();
            kv(j * 128);
            kv(SEQ + (j + 1) * 128);
          }
          kv(SEQ);
        } else {
          const int part = type & 1;
          const unsigned* flag = g_sync + (part ? SY_OX + 2 * p + 1 : SY_CTX + p * 32 + lane);
          const unsigned target = part ? OX_TARGET : 4;
          const int row = (2 + part) * SEQ + p * 256 + rank * 128;
          const int nch = type >= T_MA ? 2 : 3;
          const CUtensorMap* w = &P.woa + part + (type >= T_MA ? 4 : 0);
#pragma unroll 1
          for (int k = 0; k < HDALL; k += 64) {
            need_flag(fv, k >> 7, flag, target);
            const uint32_t st = alloc(nch, fb);
            if (elect()) {
              mbar_expect(fb, 16384 + nch * 8192);
              tma2d(st, &P.scr, k, row, fb);
              tma3d_mc(st + 16384 + rank * nch * 4096, w, 0, k + rank * 32, nn * nch, fb, 3);
            }
            if (k == HDALL - 192) go();
          }
          alloc(nch, fb);
          arrive_elect(fb);
        }
      }
    } else if (warp == 9) {
      started();
      TRM(0);
      if (rank == 0) {
        for (int ti = 0;; ti++) {
          uint32_t q = 0;
          mbar_wait(sb + M_GO, ti & 1);
          if (lane == 0) q = atomicAdd(&g_sync[SY_Q], 1u);
          q = __shfl_sync(0xffffffffu, q, 0);
          if (ti == 0 && q < 100000) TRM(1);
          const uint32_t t = q < P.ntask ? (uint32_t)P.tasks[q] : TASK_END;
          if (ti == 0 && t < 100000) TRM(2);
          mbar_wait(sb + M_TEMPTY + 8 * (ti & 3), ((ti >> 2) & 1) ^ 1);
          if (lane < 2) {
            const uint32_t b = mapa(sb + M_TFULL + 8 * (ti & 3), lane);
            mbar_expect_cl(b, 4);
            st_async32(mapa(sb + M_TSLOT + 4 * (ti & 3), lane), t, b);
          }
          __syncwarp();
          if (t == TASK_END) break;
        }
      }
    } else {
      const int wg = warp - 10;
      const uint32_t emptyx = mapa(sb + M_EMPTY, lane & 1);
      Ring r{0, 0};
      int lead = wg;
      started();
      for (int ti = 0;; ti++) {
        const int sl = ti & 1;
        const uint32_t task = read_task(ti);
        const int type = task >> 12, nn = (task >> 8) & 15, h = (task >> 3) & 31, p = task & 7;
        if (task != TASK_END) {
          const int nit = task_entries(type, p);
          uint32_t st = 0;
          for (int it = 0; it < nit; it++) st = r.take(entry_size(type, it));
          r.e += nit - 1;
          int row = p * 256 + rank * 128 + wg * 64;
          if (type == T_FA) {
            row = 2 * SEQ + p * 256 + (lead ? 3 - (int)rank : (int)rank) * 64;
            lead ^= 1;
          }
          mbar_wait(sb + M_EPI + 8 * (sl * 2 + wg), (ti >> 1) & 1);
          auto store = [&](const CUtensorMap* m, uint32_t src, int r0, int c0, int n32, bool fast = true) {
            if (lane == 0) {
#pragma unroll 1
              for (int i = 0; i < n32 * (32 / ST_ROWS); i++) {
                asm volatile("cp.async.bulk.tensor.2d.global.shared::cta.bulk_group [%0, {%1,%2}], [%3];" ::"l"(m), "r"((c0 + i / (64 / ST_ROWS)) * 64), "r"(r0 + i % (64 / ST_ROWS) * ST_ROWS), "r"(src + i * ST_ROWS * 128) : "memory");
                asm volatile("cp.async.bulk.commit_group;" ::: "memory");
                if (fast) asm volatile("cp.async.bulk.wait_group.read %0;" ::"n"(ST_DEPTH) : "memory");
                else asm volatile("cp.async.bulk.wait_group.read 0;" ::: "memory");
              }
              asm volatile("cp.async.bulk.wait_group.read 0;" ::: "memory");
            }
            __syncwarp();
          };
          if (type != T_FA) {
            if (type == T_KV) store(&P.scr_st, sb + st * M_GR + wg * 16384, SEQ + row, h * 2, 4);
            else if (type < T_MA) store(&P.out_st, sb + st * M_GR + wg * 24576, row, (type & 1) * 9 + nn * 3, 6);
            else store(&P.out_st, sb + st * M_GR + wg * 16384, row, (type & 1) * 9 + nn * 2, 4);
            if (lane < 2) asm volatile("mbarrier.arrive.shared::cluster.b64 _, [%0], 4;" ::"r"(emptyx + r.bar()) : "memory");
          }
          r.e++;
          if (type <= T_FA) store(&P.scr_st, sb + M_STG + wg * 16384, row, h * 2, 4, false);
          if (lane == 0) mbar_arrive(sb + M_SFREE + 8 * wg);
          if (lane == 0) {
            asm volatile("cp.async.bulk.wait_group 0;" ::: "memory");
            if (type <= T_FA) {
              __threadfence();
              atomicAdd(type == T_KV ? &g_sync[SY_KV + h * 8 + p] : &g_sync[SY_CTX + p * 32 + h], 1u);
            }
          }
        }
        __syncwarp();
        free_task(ti);
        if (task == TASK_END) break;
      }
    }
    __syncwarp();
    cluster_sync();
    if (threadIdx.x == 288) TRE(256 + blockIdx.x);
    if (warp == 9) {
      uint32_t old = 0;
      if (lane == 0) {
        __threadfence();
        old = atomicAdd(&g_sync[SY_EXIT], 1u);
        __threadfence();
      }
      if (__shfl_sync(0xffffffffu, old, 0) == gridDim.x - 1) {
        asm volatile("griddepcontrol.wait;" ::: "memory");
        for (int i = lane; i < SY_N; i += 32) g_sync[i] = 0;
      }
    }
  } else {
    asm volatile("setmaxnreg.inc.sync.aligned.u32 232;");
    if (warp == 0) TRM(3);
    const int wg = warp >> 2, w4 = warp & 3, g = lane >> 2, t4 = lane & 3;
    const uint32_t emptyx = mapa(sb + M_EMPTY, lane & 1);
    Ring r{0, 0};
    int lead = wg;
    auto release = [&](uint32_t bar) {
      if (lane < 2) mbar_arrive_cl(emptyx + bar);
    };
    auto acquire = [&](int z, uint32_t& bar) -> uint32_t {
      bar = r.bar();
      mbar_wait(sb + M_FULL + bar, r.par());
      r.e++;
      return sb + r.take(z) * M_GR;
    };
    const uint32_t sa = (w4 * 16 + ((lane >> 3) & 1) * 8 + (lane & 7)) * 128 + (((lane >> 4) ^ (lane & 7)) << 4);
    uint32_t ntask = task0;
    started();
    for (int ti = 0;; ti++) {
      const int sl = ti & 1;
      const uint32_t task = ntask;
      if (task == TASK_END) break;
      auto next_task = [&]() { ntask = read_task(ti + 1); free_task(ti + 1); };
      const int type = task >> 12, p = task & 7;
#ifdef DEV_TRACE
      if (w4 == 0 && lane == 0 && ti < 250) { long long c; asm volatile("mov.u64 %0, %%globaltimer;" : "=l"(c)); g_trace[blockIdx.x * 4096 + ti * 8 + wg * 4] = c; g_trace[blockIdx.x * 4096 + ti * 8 + wg * 4 + 2] = task; g_trace[blockIdx.x * 4096 + ti * 8 + wg * 4 + 3] = clock64(); }
#endif
      if (type == T_KV) {
        float acc[128];
        uint32_t prev;
        {
          const uint32_t st = acquire(3, prev);
          if (ti == 0 && warp == 0) TRM(6);
          const uint32_t a = desc_lo(st + wg * 8192, 16), b = desc_lo(st + 16384, 8192);
          wg_fence();
          wgmma_ssz_n256_a0b1(acc, mk_desc(a, DHI_SW128), mk_desc(b, DHI_SW128));
#pragma unroll
          for (int kk = 1; kk < 4; kk++) wgmma_ss_n256_a0b1(acc, mk_desc(a + kk * 2, DHI_SW128), mk_desc(b + kk * 128, DHI_SW128), 1);
          wg_commit();
        }
#pragma unroll 1
        for (int kb = 1; kb < 8; kb++) {
          uint32_t bar;
          const uint32_t st = acquire(3, bar);
          const uint32_t a = desc_lo(st + wg * 8192, 16), b = desc_lo(st + 16384, 8192);
          if (KV_SKEW < 8 && kb == KV_SKEW && !lead) {
            wg_wait<0>();
            release(prev);
            bar_sync(5, 256);
          }
          wg_fence();
#pragma unroll
          for (int kk = 0; kk < 4; kk++) wgmma_ss_n256_a0b1(acc, mk_desc(a + kk * 2, DHI_SW128), mk_desc(b + kk * 128, DHI_SW128), 1);
          wg_commit();
          if (KV_SKEW < 8 && kb == 7 && lead) bar_arrive(5, 256);
          if (KV_SKEW < 8 && kb == KV_SKEW && !lead) { prev = bar; continue; }
          wg_wait<1>();
          release(prev);
          prev = bar;
        }
        if (ti == 0 && warp == 0) TRM(7);
        next_task();
        uint32_t bar;
        const uint32_t st = acquire(2, bar);
        mbar_wait(sb + M_SFREE + 8 * wg, (ti & 1) ^ 1);
        wg_wait<0>();
        release(prev);
        fence_regs(acc);
        stage_tile<16, 32>(acc, st + wg * 16384 + sa, 1.f, 1.f);
        stage_tile<0, 16>(acc, sb + M_STG + wg * 16384 + sa, 1.f, 1.f);
        fence_async_smem();
        __syncwarp();
        arrive_elect(sb + M_EPI + 8 * (sl * 2 + wg));
      } else if (type == T_FA) {
        const int lng = lead;
        lead ^= 1;
        const int grp = lng ? 3 - (int)rank : (int)rank;
        const int n = 2 * p + 1 + lng;
        float s[64], o[64];
        uint32_t pr[32], q[32];
        TRF(0);
        {
          uint32_t prev;
          {
            const uint32_t st = acquire(2, prev);
            const uint32_t a = desc_lo(st + lng * 8192, 16), b = desc_lo(st + 16384, 8192);
            wg_fence();
            wgmma_ssz_n128_a0b1(s, mk_desc(a, DHI_SW128), mk_desc(b, DHI_SW128));
#pragma unroll
            for (int kk = 1; kk < 4; kk++) wgmma_ss_n128_a0b1(s, mk_desc(a + kk * 2, DHI_SW128), mk_desc(b + kk * 128, DHI_SW128), 1);
            wg_commit();
          }
#pragma unroll 1
          for (int kb = 1; kb < 9; kb++) {
            uint32_t bar;
            if (kb == 1) TRF(8);
            if (kb == 5) TRF(9);
            const uint32_t st = acquire(2, bar);
            const uint32_t a = desc_lo(st + lng * 8192, 16), b = desc_lo(st + 16384, 8192);
            const bool hold = kb == Q_SKEW && !lng;
            if (hold) {
              wg_wait<0>();
              release(prev);
              bar_sync(5, 256);
            }
            wg_fence();
#pragma unroll
            for (int kk = 0; kk < 4; kk++) wgmma_ss_n128_a0b1(s, mk_desc(a + kk * 2, DHI_SW128), mk_desc(b + kk * 128, DHI_SW128), 1);
            wg_commit();
            if (Q_SKEW < 9 && kb == 8 && lng) bar_arrive(5, 256);
            if (hold) { prev = bar; continue; }
            wg_wait<1>();
            release(prev);
            prev = bar;
          }
#pragma unroll
          for (int i = 0; i < 64; i++) o[i] = 0.f;
          wg_wait<0>();
          release(prev);
          fence_regs(s);
#pragma unroll
          for (int i = 0; i < 32; i++) q[i] = pack_bf16(s[2 * i], s[2 * i + 1]);
        }
        TRF(1);
        const int lim0 = (grp & 1) * 64 + w4 * 16 + g - 2 * t4;
        float m0 = -INFINITY, m1 = -INFINITY, l0 = 0.f, l1 = 0.f;
        auto issue_s = [&](uint32_t st) {
          const uint32_t b = desc_lo(st, 16);
#pragma unroll
          for (int kk = 0; kk < 8; kk++) wgmma_rs_n128_b0(s, q[4 * kk], q[4 * kk + 1], q[4 * kk + 2], q[4 * kk + 3], mk_desc(b + (kk >> 2) * 1024 + (kk & 3) * 2, DHI_SW128), kk);
          wg_commit();
        };
        auto issue_pv = [&](uint32_t st) {
          const uint32_t b = desc_lo(st, 16384);
#pragma unroll
          for (int kk = 0; kk < 8; kk++) {
            wgmma_rs_n128_b1(o, pr[4 * kk], pr[4 * kk + 1], pr[4 * kk + 2], pr[4 * kk + 3], mk_desc(b + kk * 128, DHI_SW128), 1);
            if (kk == 1 || kk == 3 || kk == 7) wg_commit();
          }
        };
        auto skip = [&]() {
          uint32_t bar;
          acquire(2, bar);
          release(bar);
        };
        const bool half = !(grp & 1);
        float t[4];
        auto first = [&]() {
          float a0, a1, c0, c1;
          uint32_t kb;
          const uint32_t kst = acquire(2, kb);
          if (!lng) bar_sync(1 + wg, 256);
          fence_regs(q);
          fence_regs(s);
          if (half) {
            const uint32_t b = desc_lo(kst, 16);
            wg_fence();
#pragma unroll
            for (int kk = 0; kk < 8; kk++) wgmma_rs_n64_b0(reinterpret_cast<float(&)[32]>(s), q[4 * kk], q[4 * kk + 1], q[4 * kk + 2], q[4 * kk + 3], mk_desc(b + (kk >> 2) * 1024 + (kk & 3) * 2, DHI_SW128), kk);
            wg_commit();
            bar_arrive(2 - wg, 256);
            wg_wait<0>();
            fence_regs(s);
            causal_mask<0, 8>(s, lim0);
          } else {
            wg_fence();
            issue_s(kst);
            bar_arrive(2 - wg, 256);
            wg_wait<0>();
            fence_regs(s);
            causal_mask<8, 16>(s, lim0);
          }
          release(kb);
          TRF(2);
          softmax_max<FM_NJ>(s, m0, m1, a0, a1, c0, c1);
          softmax_exp<0, 8>(s, pr, c0, c1, t);
          if (half) {
#pragma unroll
            for (int i = 16; i < 32; i++) pr[i] = 0;
          } else {
            softmax_exp<8, 16>(s, pr, c0, c1, t);
          }
        };
        auto block = [&]() {
          const uint32_t kb = r.bar(), kp = r.par(), kst = sb + r.take(2) * M_GR;
          r.e++;
          const uint32_t vb = r.bar(), vp = r.par(), vst = sb + r.take(2) * M_GR;
          r.e++;
          mbar_wait2(sb + M_FULL + kb, kp, sb + M_FULL + vb, vp);
          fence_regs(o);
          fence_regs(pr);
          fence_regs(s);
          bar_sync(1 + wg, 256);
          wg_fence();
          issue_s(kst);
          issue_pv(vst);
          bar_arrive(2 - wg, 256);
          wg_wait<3>();
          release(kb);
          fence_regs(s);
          const float d0 = -m0 * SM_C, d1 = -m1 * SM_C;
          wg_wait<2>();
          fence_part<0, 8>(pr);
          softmax_exp<0, 4>(s, pr, d0, d1, t);
          fence_part<0, 8>(pr);
          sched_fence(kst);
          wg_wait<1>();
          fence_part<8, 16>(pr);
          softmax_exp<4, 8>(s, pr, d0, d1, t);
          fence_part<8, 16>(pr);
          sched_fence(vst);
          wg_wait<0>();
          release(vb);
          fence_regs(o);
          fence_part<16, 32>(pr);
          softmax_exp<8, 16>(s, pr, d0, d1, t);
        };
        auto check = [&](bool hlf) {
          if (__builtin_expect(__any_sync(0xffffffffu, !((t[0] + t[1]) + (t[2] + t[3]) < 1.8446744e19f)), 0)) {
            float a0, a1, c0, c1;
            if (hlf) {
#pragma unroll
              for (int i = 32; i < 64; i++) s[i] = -INFINITY;
            }
            softmax_max<16>(s, m0, m1, a0, a1, c0, c1);
            l0 *= a0;
            l1 *= a1;
#pragma unroll
            for (int i = 0; i < 16; i++) { o[4 * i] *= a0; o[4 * i + 1] *= a0; o[4 * i + 2] *= a1; o[4 * i + 3] *= a1; }
            softmax_exp<0, 16>(s, pr, c0, c1, t);
          }
          l0 += t[0] + t[1];
          l1 += t[2] + t[3];
        };
        if (!lng) skip();
        first();
        check(half);
        if (!lng) skip();
        TRF(3);
#pragma unroll 1
        for (int j = 1; j < n; j++) {
          if (j == n - 1) TRF(4);
          block();
          check(false);
        }
        TRF(5);
        uint32_t vb;
        const uint32_t vst = acquire(2, vb);
        fence_regs(o);
        fence_regs(pr);
        if (!lng) bar_sync(1 + wg, 256);
        wg_fence();
        issue_pv(vst);
        l0 += __shfl_xor_sync(0xffffffffu, l0, 1);
        l1 += __shfl_xor_sync(0xffffffffu, l1, 1);
        l0 += __shfl_xor_sync(0xffffffffu, l0, 2);
        l1 += __shfl_xor_sync(0xffffffffu, l1, 2);
        const float i0 = rcp(l0), i1 = rcp(l1);
        next_task();
        mbar_wait(sb + M_SFREE + 8 * wg, (ti & 1) ^ 1);
        wg_wait<0>();
        release(vb);
        fence_regs(o);
        fence_regs(pr);
        TRF(6);
        stage_tile<0, 16>(o, sb + M_STG + wg * 16384 + sa, i0, i1);
        fence_async_smem();
        __syncwarp();
        arrive_elect(sb + M_EPI + 8 * (sl * 2 + wg));
        TRF(7);
      } else if (type >= T_MA) {
        float acc[64];
#pragma unroll
        for (int i = 0; i < 64; i++) acc[i] = 0.f;
        uint32_t prev = 0;
        for (int kb = 0; kb < 64; kb++) {
          uint32_t bar;
          const uint32_t st = acquire(2, bar);
          const uint32_t a = desc_lo(st + wg * 8192, 16), b = desc_lo(st + 16384, 4096);
          wg_fence();
#pragma unroll
          for (int kk = 0; kk < 4; kk++) wgmma_ss_n128_a0b1(acc, mk_desc(a + kk * 2, DHI_SW128), mk_desc(b + (kk >> 1) * 512 + (kk & 1) * 128, DHI_SW128), kk | kb);
          wg_commit();
          if (kb > 0) { wg_wait<1>(); release(prev); }
          prev = bar;
        }
        next_task();
        uint32_t bar;
        const uint32_t st = acquire(2, bar);
        mbar_wait(sb + M_SFREE + 8 * wg, (ti & 1) ^ 1);
        wg_wait<0>();
        release(prev);
        fence_regs(acc);
        stage_tile<0, 16>(acc, st + wg * 16384 + sa, 1.f, 1.f);
        fence_async_smem();
        __syncwarp();
        arrive_elect(sb + M_EPI + 8 * (sl * 2 + wg));
      } else {
        float acc[96];
#pragma unroll
        for (int i = 0; i < 96; i++) acc[i] = 0.f;
        uint32_t prev = 0;
        for (int kb = 0; kb < 64; kb++) {
          uint32_t bar;
          const uint32_t st = acquire(3, bar);
          const uint32_t a = desc_lo(st + wg * 8192, 16), b = desc_lo(st + 16384, 4096);
          wg_fence();
#pragma unroll
          for (int kk = 0; kk < 4; kk++) wgmma_ss_n192_a0b1(acc, mk_desc(a + kk * 2, DHI_SW128), mk_desc(b + (kk >> 1) * 768 + (kk & 1) * 128, DHI_SW128), kk | kb);
          wg_commit();
          if (kb > 0) { wg_wait<1>(); release(prev); }
          prev = bar;
        }
        next_task();
        uint32_t bar;
        const uint32_t st = acquire(3, bar);
        mbar_wait(sb + M_SFREE + 8 * wg, (ti & 1) ^ 1);
        wg_wait<0>();
        release(prev);
        fence_regs(acc);
        stage_tile<0, 24>(acc, st + wg * 24576 + sa, 1.f, 1.f);
        fence_async_smem();
        __syncwarp();
        arrive_elect(sb + M_EPI + 8 * (sl * 2 + wg));
      }
#ifdef DEV_TRACE
      if (w4 == 0 && lane == 0 && ti < 250) { long long c; asm volatile("mov.u64 %0, %%globaltimer;" : "=l"(c)); g_trace[blockIdx.x * 4096 + ti * 8 + wg * 4 + 1] = c; }
#endif
    }
    cluster_sync();
  }
}

typedef CUresult (*EncodeFn)(CUtensorMap*, CUtensorMapDataType, cuuint32_t, void*, const cuuint64_t*, const cuuint64_t*, const cuuint32_t*,
                             const cuuint32_t*, CUtensorMapInterleave, CUtensorMapSwizzle, CUtensorMapL2promotion, CUtensorMapFloatOOBfill);

void map2d(EncodeFn enc, CUtensorMap* m, const void* p, int rows, int cols, int boxr) {
  cuuint64_t gd[2] = {(cuuint64_t)cols, (cuuint64_t)rows}, gs[1] = {(cuuint64_t)cols * 2};
  cuuint32_t bx[2] = {64, (cuuint32_t)boxr}, es[2] = {1, 1};
  enc(m, CU_TENSOR_MAP_DATA_TYPE_BFLOAT16, 2, (void*)p, gd, gs, bx, es, CU_TENSOR_MAP_INTERLEAVE_NONE, CU_TENSOR_MAP_SWIZZLE_128B,
      CU_TENSOR_MAP_L2_PROMOTION_L2_256B, CU_TENSOR_MAP_FLOAT_OOB_FILL_NONE);
}
void map3d(EncodeFn enc, CUtensorMap* m, const void* p, int rows, int cols, int boxr, int nch) {
  cuuint64_t gd[3] = {64, (cuuint64_t)rows, (cuuint64_t)cols / 64}, gs[2] = {(cuuint64_t)cols * 2, 128};
  cuuint32_t bx[3] = {64, (cuuint32_t)boxr, (cuuint32_t)nch}, es[3] = {1, 1, 1};
  enc(m, CU_TENSOR_MAP_DATA_TYPE_BFLOAT16, 3, (void*)p, gd, gs, bx, es, CU_TENSOR_MAP_INTERLEAVE_NONE, CU_TENSOR_MAP_SWIZZLE_128B,
      CU_TENSOR_MAP_L2_PROMOTION_L2_256B, CU_TENSOR_MAP_FLOAT_OOB_FILL_NONE);
}

#ifndef R_KR
#define R_KR 24
#endif
#ifndef R_VR
#define R_VR 9
#endif
constexpr int R_NS = 36 - R_KR;
constexpr int R_WQ = 0, R_WK = R_WQ + R_NS * 2048, R_WV = R_WK + R_NS * 2048;
constexpr int R_OS = 102 * 1024;
constexpr int R_RS = 103 * 1024;
static_assert(R_WV + (36 - R_VR) * 2048 <= R_OS, "weights");
constexpr int R_HC = 9216, R_H = 114 * 1024, R_HM = R_H + 4096;
__host__ __device__ constexpr int hoff(int c) { return (c < 8 ? 1 + (c >> 1) + 4 * (c & 1) : 0) * R_HC; }
constexpr int R_PS = R_H + 9 * R_HC;
constexpr int R_GS = 1056, R_HS = 12288, R_QS = 201 * 1024;
static_assert(R_PS + 5120 <= R_QS, "layout");
constexpr int R_BAR = R_QS + 2 * R_HS;
static_assert(3 * 73728 <= R_BAR, "prologue staging");
constexpr int RB_MEM = R_BAR  , RB_RS = R_BAR + 40, RB_QK = R_BAR + 48, RB_XF = R_BAR + 88  , RB_QXL = R_BAR + 104, RB_W = R_BAR + 112  ;
constexpr int RB_TF = R_BAR + 128  , RB_TE = R_BAR + 160  , RB_TR = R_BAR + 192;
constexpr int R_SMEM = R_BAR + 256;
static_assert(R_SMEM <= 232448, "smem");
constexpr int QK_TX = 2048 + 8 * R_GS;
constexpr int NB_P1 = 1, NB_P3 = 2, NB_PM = 3, NB_O = 4, NB_PX = 5, NB_RD = 6, NB_S = 7, NB_O2 = 8;
static_assert(R_NS >= 9 && R_NS <= 18, "R_KR");
__host__ __device__ constexpr int nsm(int c) { return c < R_NS - 9 ? 2 : 1; }
__host__ __device__ constexpr int sm0(int c) { return c < R_NS - 9 ? 2 * c : c + R_NS - 9; }
__host__ __device__ constexpr bool qk_in_reg(int k) { return (k & 3) >= nsm(k >> 2); }
__host__ __device__ constexpr int qk_slot(int k) { return qk_in_reg(k) ? k - sm0((k >> 2) + 1) : sm0(k >> 2) + (k & 3); }
__host__ __device__ constexpr int qk_step(int slot, bool reg) {
  for (int k = 0; k < 36; k++)
    if (qk_in_reg(k) == reg && qk_slot(k) == slot) return k;
  return -1;
}
#ifndef B_SEQ
#define B_SEQ "qkqkqkqkQkqkKqkq|QKQKQKqkQkqKqkQkqKqkQkqKqkQkqKqkQkqKqkQkqKqkQkqKqkQkqKqk"
#endif
__host__ __device__ constexpr int seq_count(char c, int n) {
  int r = 0;
  for (int i = 0; i < n; i++) r += B_SEQ[i] == c;
  return r;
}
static_assert(sizeof(B_SEQ) == 74 && seq_count('q', 73) == R_KR && seq_count('k', 73) == R_KR && seq_count('Q', 73) == R_NS && seq_count('K', 73) == R_NS, "B_SEQ");
#ifndef V_N1
#define V_N1 10
#endif
#ifndef V_PER
#define V_PER 3
#endif
#ifndef V_K0
#define V_K0 11
#endif
#ifndef QX_AFTER
#define QX_AFTER 2
#endif
#ifndef P1_PRE
#define P1_PRE 2
#endif
#ifndef B_DELAY
#define B_DELAY 0
#endif
#ifndef PUB_REL
#define PUB_REL 0
#endif
#ifndef PF_V
#define PF_V 0
#endif
#ifndef PF_MAIN
#define PF_MAIN 0
#endif
#ifndef PRE_EARLY
#define PRE_EARLY 1
#endif
#ifndef P3_EARLY
#define P3_EARLY 0
#endif
#ifndef POLL_STAG
#define POLL_STAG 80
#endif
#ifndef POLL_DELAY
#define POLL_DELAY 240
#endif
__host__ __device__ constexpr bool v_in_reg(int k) { return k >= V_K0 && (k - V_K0) % V_PER == 0 && (k - V_K0) / V_PER < R_VR; }
__host__ __device__ constexpr int v_nreg_before(int k) { return k <= V_K0 ? 0 : ((k - V_K0 + V_PER - 1) / V_PER < R_VR ? (k - V_K0 + V_PER - 1) / V_PER : R_VR); }
__host__ __device__ constexpr int v_slot(int k) { return v_in_reg(k) ? (k - V_K0) / V_PER : k - v_nreg_before(k); }
static_assert(V_K0 + (R_VR - 1) * V_PER < 36, "Wv split");

struct RmtParams {
  CUtensorMap wq, wk, wv, wo, x, mem, ox, ox128, wo3;
  const __nv_bfloat16 *ckv, *wuk, *wuv;
  uint32_t* out;
};
constexpr int XCH_CL = 16 * 288, XCH_SLOT = 4 * XCH_CL;
__device__ uint32_t g_xch[2 * XCH_SLOT];
#ifdef DEV_TRACE
__device__ long long g_trace_b[64 * 4096];
#ifndef TR_S0
#define TR_S0 24
#endif
#ifndef TR_MASK
#define TR_MASK 0xffffffffu
#endif
#define TRW(slot, w) do { if (((TR_MASK >> (slot)) & 1) && w4 == (w) && s >= TR_S0 && s < TR_S0 + 16) { uint32_t c_; asm volatile("mov.u32 %0, %%clock;" : "=r"(c_)::"memory"); sts32(sb + R_QS + R_GS + ((s >> 3) & 1) * R_HS + (s & 7) * 128 + (slot) * 4, c_); } } while (0)
#else
#define TRW(slot, w)
#endif
#define TRB(slot) TRW(slot, 0)
#ifdef DEV_TRACE
#ifndef TRG_MASK
#define TRG_MASK 0x41
#endif
#define TRT(slot, w) do { if (warp == (w) && (threadIdx.x & 31) == 0) { long long c_; asm volatile("mov.u64 %0, %%globaltimer;" : "=l"(c_)); g_trace_b[bid * 4096 + 2200 + (slot)] = c_; } } while (0)
#define TRG(slot) do { if (((slot) >= 16 || ((TRG_MASK >> (slot)) & 1)) && (threadIdx.x & 127) == 0) { long long c_; asm volatile("mov.u64 %0, %%globaltimer;" : "=l"(c_)); g_trace_b[bid * 4096 + 2048 + (slot)] = c_; if ((slot) < 8) g_trace_b[bid * 4096 + 2056 + (slot)] = clock64(); } } while (0)
#else
#define TRG(slot)
#define TRT(slot, w)
#endif

__device__ __forceinline__ void ldsm4(uint32_t (&r)[4], uint32_t a) {
  asm volatile("ldmatrix.sync.aligned.m8n8.x4.shared.b16 {%0,%1,%2,%3}, [%4];" : "=r"(r[0]), "=r"(r[1]), "=r"(r[2]), "=r"(r[3]) : "r"(a) : "memory");
}
__device__ __forceinline__ void ldsm4t(uint32_t (&r)[4], uint32_t a) {
  asm volatile("ldmatrix.sync.aligned.m8n8.x4.trans.shared.b16 {%0,%1,%2,%3}, [%4];" : "=r"(r[0]), "=r"(r[1]), "=r"(r[2]), "=r"(r[3]) : "r"(a) : "memory");
}
__device__ __forceinline__ void stsm4t(uint32_t a, uint32_t r0, uint32_t r1, uint32_t r2, uint32_t r3) {
  asm volatile("stmatrix.sync.aligned.m8n8.x4.trans.shared.b16 [%0], {%1,%2,%3,%4};" ::"r"(a), "r"(r0), "r"(r1), "r"(r2), "r"(r3) : "memory");
}
__device__ __forceinline__ void stsm2t(uint32_t a, uint32_t r0, uint32_t r1) {
  asm volatile("stmatrix.sync.aligned.m8n8.x2.trans.shared.b16 [%0], {%1,%2};" ::"r"(a), "r"(r0), "r"(r1) : "memory");
}
__device__ __forceinline__ void mma16816(float (&c)[4], const uint32_t (&a)[4], uint32_t b0, uint32_t b1) {
  asm volatile("mma.sync.aligned.m16n8k16.row.col.f32.bf16.bf16.f32 {%0,%1,%2,%3}, {%4,%5,%6,%7}, {%8,%9}, {%0,%1,%2,%3};"
               : "+f"(c[0]), "+f"(c[1]), "+f"(c[2]), "+f"(c[3])
               : "r"(a[0]), "r"(a[1]), "r"(a[2]), "r"(a[3]), "r"(b0), "r"(b1));
}
__device__ __forceinline__ void sts32(uint32_t a, uint32_t v) { asm volatile("st.shared.b32 [%0], %1;" ::"r"(a), "r"(v) : "memory"); }
__device__ __forceinline__ uint2 lds64(uint32_t a) {
  uint2 v;
  asm volatile("ld.shared.v2.b32 {%0,%1}, [%2];" : "=r"(v.x), "=r"(v.y) : "r"(a) : "memory");
  return v;
}
__device__ __forceinline__ float4 lds128f(uint32_t a) {
  float4 v;
  asm volatile("ld.shared.v4.f32 {%0,%1,%2,%3}, [%4];" : "=f"(v.x), "=f"(v.y), "=f"(v.z), "=f"(v.w) : "r"(a) : "memory");
  return v;
}
__device__ __forceinline__ uint4 ld_relaxed128(const uint32_t* p) {
  uint4 v;
  asm volatile("ld.relaxed.gpu.global.v4.u32 {%0,%1,%2,%3}, [%4];" : "=r"(v.x), "=r"(v.y), "=r"(v.z), "=r"(v.w) : "l"(p) : "memory");
  return v;
}
__device__ __forceinline__ void st_relaxed32(uint32_t* p, uint32_t v) { asm volatile("st.relaxed.gpu.global.u32 [%0], %1;" ::"l"(p), "r"(v) : "memory"); }

__device__ __forceinline__ void mma1688(float (&c)[4], uint32_t a0, uint32_t a1, uint32_t b0) {
  asm volatile("mma.sync.aligned.m16n8k8.row.col.f32.bf16.bf16.f32 {%0,%1,%2,%3}, {%4,%5}, {%6}, {%0,%1,%2,%3};"
               : "+f"(c[0]), "+f"(c[1]), "+f"(c[2]), "+f"(c[3])
               : "r"(a0), "r"(a1), "r"(b0));
}
__device__ __forceinline__ uint2 ld_relaxed64(const uint32_t* p) {
  uint2 v;
  asm volatile("{.reg .b64 t; ld.relaxed.gpu.global.b64 t, [%2]; mov.b64 {%0,%1}, t;}" : "=r"(v.x), "=r"(v.y) : "l"(p) : "memory");
  return v;
}
__device__ __forceinline__ void st_relaxed64(uint32_t* p, uint32_t a, uint32_t b) { asm volatile("{.reg .b64 t; mov.b64 t, {%1,%2}; st.relaxed.gpu.global.b64 [%0], t;}" ::"l"(p), "r"(a), "r"(b) : "memory"); }

__device__ __forceinline__ void mma16816z(float (&c)[4], const uint32_t (&a)[4], uint32_t b0, uint32_t b1) {
  asm volatile("mma.sync.aligned.m16n8k16.row.col.f32.bf16.bf16.f32 {%0,%1,%2,%3}, {%4,%5,%6,%7}, {%8,%9}, {0f00000000,0f00000000,0f00000000,0f00000000};"
               : "=f"(c[0]), "=f"(c[1]), "=f"(c[2]), "=f"(c[3])
               : "r"(a[0]), "r"(a[1]), "r"(a[2]), "r"(a[3]), "r"(b0), "r"(b1));
}
template <int NB> __device__ __forceinline__ uint2 xch_reduce(uint32_t a, int key, uint32_t* dst, uint32_t tag) {
  uint32_t m[NB][4];
  float c[2][4];
#pragma unroll
  for (int j = 0; j < NB; j++) ldsm4t(m[j], a ^ (j << 5));
#pragma unroll
  for (int j = 0; j < NB; j++) {
    const uint32_t one = key == j ? 0x3f803f80u : 0u;
    if (j < 2) mma16816z(c[j], m[j], one, one);
    else mma16816(c[j & 1], m[j], one, one);
  }
  const uint2 o = make_uint2((__float_as_uint(c[0][0] + c[1][0]) & ~1u) | tag, __float_as_uint(c[0][2] + c[1][2]));
  st_relaxed64(dst, o.x, o.y);
  return o;
}
__device__ __forceinline__ uint32_t xch_sum(const uint2 (&v)[4]) {
  return pack_bf16((__uint_as_float(v[0].x) + __uint_as_float(v[1].x)) + (__uint_as_float(v[2].x) + __uint_as_float(v[3].x)),
                   (__uint_as_float(v[0].y) + __uint_as_float(v[1].y)) + (__uint_as_float(v[2].y) + __uint_as_float(v[3].y)));
}
__device__ __forceinline__ void xch_probe(uint2 (&v)[4], const uint32_t* x, int cl) {
#pragma unroll
  for (int c = 0; c < 4; c++)
    asm volatile("{.reg .pred p; .reg .b64 t; setp.ne.s32 p, %3, %4; mov.b64 t, {%0,%1}; @p ld.relaxed.gpu.global.b64 t, [%2]; mov.b64 {%0,%1}, t;}"
                 : "+r"(v[c].x), "+r"(v[c].y) : "l"(x + c * XCH_CL), "r"(cl), "r"(c) : "memory");
}
__device__ __forceinline__ uint32_t xch_bad(const uint2 (&v)[4]) {
  uint32_t bad;
  asm("{.reg .b32 t; lop3.b32 t, %1, %2, %3, 0x7e; lop3.b32 %0, t, %4, %3, 0xf6;}" : "=r"(bad) : "r"(v[0].x), "r"(v[1].x), "r"(v[2].x), "r"(v[3].x));
  return bad;
}
template <bool TWO> __device__ __forceinline__ uint32_t xch_poll(const uint32_t* x, int cl, uint2 o, const uint32_t* x2, uint2 o2, uint32_t& r2) {
  uint2 v[4] = {o, o, o, o}, w[4] = {o2, o2, o2, o2};
  uint32_t r;
#pragma unroll 1
  for (int it = 0;; it++) {
    xch_probe(v, x, cl);
    if (TWO) xch_probe(w, x2, cl);
    if (it > (1 << 20)) __trap();
    uint32_t bad = xch_bad(v);
    if (TWO) { bad |= xch_bad(w); r2 = xch_sum(w); }
    r = xch_sum(v);
    if (!__any_sync(0xffffffffu, bad & 1)) break;
  }
  return r;
}
constexpr uint32_t CTA1 = 1u << 24;
template <int NSEND, int NPRE> struct XSend {
  uint32_t d[NPRE], b[NPRE];
  static __device__ constexpr uint32_t off(int i) { return ((2 * i + 2 * i / NSEND) & (NSEND - 1)) * CTA1; }
  __device__ __forceinline__ XSend(uint32_t dst, uint32_t bar) {
#pragma unroll
    for (int i = 0; i < NPRE; i++) { d[i] = dst ^ off(i); b[i] = bar ^ off(i); }
    fence_regs(d);
    fence_regs(b);
  }
  __device__ __forceinline__ void send(uint32_t v) {
    asm volatile("" : "+r"(d[0]), "+r"(b[0]));
#pragma unroll
    for (int i = 0; i < NSEND; i++) st_async32(i < NPRE ? d[i] : d[0] ^ off(i), v, i < NPRE ? b[i] : b[0] ^ off(i));
  }
};
__device__ __forceinline__ uint32_t mbar_try_addr(uint32_t bar, uint32_t par, uint32_t good) {
  uint32_t r;
  asm volatile("{.reg .pred p; .reg .b32 t; mbarrier.try_wait.parity.shared::cta.b64 p, [%1], %2; xor.b32 t, %3, 16; selp.b32 %0, %3, t, p;}" : "=r"(r) : "r"(bar), "r"(par), "r"(good) : "memory");
  return r;
}

#ifdef DEV_TRACE
__device__ __noinline__ void trace_sync() {
  if (threadIdx.x == 0) {
    uint32_t g0, g1, c_;
    asm volatile("mov.u32 %0, %%globaltimer_lo;" : "=r"(g0));
    do { asm volatile("mov.u32 %0, %%globaltimer_lo;" : "=r"(g1)); asm volatile("mov.u32 %0, %%clock;" : "=r"(c_)); } while ((g1 >> 10) == (g0 >> 10));
    g_trace_b[(int)blockIdx.x * 4096 + 2160] = g1; g_trace_b[(int)blockIdx.x * 4096 + 2161] = c_;
  }
}
#endif
template <bool MASK>
__device__ __forceinline__ void rmt_softmax_row(const float (&d)[20], int u, int lim, uint32_t pax, uint32_t pam) {
  constexpr float C = 0.08838834764831845f * 1.4426950408889634f;
  float v[10];
#pragma unroll
  for (int j = 0; j < 5; j++) {
    v[2 * j] = (!MASK || j == 4 || 2 * j <= lim) ? d[4 * j + 2 * u] : -INFINITY;
    v[2 * j + 1] = (!MASK || j == 4 || 2 * j + 1 <= lim) ? d[4 * j + 2 * u + 1] : -INFINITY;
  }
  float m = fmaxf(fmaxf(fmaxf(v[0], v[1]), fmaxf(v[2], v[3])), fmaxf(fmaxf(fmaxf(v[4], v[5]), fmaxf(v[6], v[7])), fmaxf(v[8], v[9])));
  m = fmaxf(m, __shfl_xor_sync(0xffffffffu, m, 1));
  m = fmaxf(m, __shfl_xor_sync(0xffffffffu, m, 2));
  const float mc = -m * C;
#pragma unroll
  for (int i = 0; i < 10; i++) v[i] = ex2(fmaf(v[i], C, mc));
  float l = ((v[0] + v[1]) + (v[2] + v[3])) + (((v[4] + v[5]) + (v[6] + v[7])) + (v[8] + v[9]));
  l += __shfl_xor_sync(0xffffffffu, l, 1);
  l += __shfl_xor_sync(0xffffffffu, l, 2);
  const float inv = rcp(l);
  sts128(pax, pack_bf16(v[0] * inv, v[1] * inv), pack_bf16(v[2] * inv, v[3] * inv), pack_bf16(v[4] * inv, v[5] * inv), pack_bf16(v[6] * inv, v[7] * inv));
  sts32(pam, pack_bf16(v[8] * inv, v[9] * inv));
}

__global__ void __launch_bounds__(256, 1) rmt_kernel(const __grid_constant__ RmtParams P) {
  extern __shared__ __align__(1024) uint8_t smem_rmt[];
  const uint32_t sb = (uint32_t)__cvta_generic_to_shared(smem_rmt);
  const int warp = __shfl_sync(0xffffffffu, threadIdx.x >> 5, 0);
  const int lane = __shfl_sync(0xffffffffu, threadIdx.x & 31, threadIdx.x & 31);
  const int w4 = warp & 3, g = lane >> 2, t4 = lane & 3, rho = lane & 7, li = lane >> 3;
  uint32_t rank;
  asm("mov.u32 %0, %%cluster_ctarank;" : "=r"(rank));
  constexpr int ST_O = R_WV, ST_Q = ST_O + 73728, ST_K = ST_Q + R_KR * 2048, ST_V0 = R_OS, ST_V1 = ST_K + R_KR * 2048 - 6 * 2048;
  static_assert(ST_V0 + 6 * 2048 <= R_H && ST_V0 + 6 * 2048 <= ST_Q && ST_V1 + R_VR * 2048 <= R_BAR, "staging");

#ifdef DEV_SYNC
  trace_sync();
#endif
  if (threadIdx.x == 0) {
    if ((sb & 1023) || mapa(sb, 15) != (mapa(sb, 0) ^ (15 * CTA1))) __trap();
    for (int i = 0; i < 6; i++) mbar_init(sb + RB_MEM + 8 * i, 1);
    mbar_init(sb + RB_QK, 5); mbar_init(sb + RB_XF, 1); mbar_init(sb + RB_XF + 8, 1); mbar_init(sb + RB_QXL, 4); mbar_init(sb + RB_W, 1); mbar_init(sb + RB_W + 8, 1);
    for (int i = 0; i < 4; i++) { mbar_init(sb + RB_TF + 8 * i, 1); mbar_init(sb + RB_TE + 8 * i, 4); }
    mbar_init(sb + RB_TR, 1);
    asm volatile("fence.mbarrier_init.release.cluster;" ::: "memory");
    mbar_expect(sb + RB_TR, 49152);
    mbar_expect(sb + RB_W, 2 * 73728);
    mbar_expect(sb + RB_W + 8, 73728);
  }
  if (threadIdx.x == 32) TRE(blockIdx.x);
  asm volatile("griddepcontrol.launch_dependents;");
  const int cl = blockIdx.x >> 4;
  __syncthreads();
  const int bid = cl * 16 + rank, c0 = bid * 64;
  if (warp == 0) TRG(0);
  auto prefetch_main = [&]() {
    asm volatile("cp.async.bulk.prefetch.L2.global [%0], 4096;" ::"l"(P.ckv + (bid * 8 + warp) * 2048) : "memory");
    asm volatile("cp.async.bulk.prefetch.L2.global [%0], 1280;" ::"l"(P.wuk + (bid * 8 + warp) * HDALL) : "memory");
    asm volatile("cp.async.bulk.prefetch.L2.global [%0], 1280;" ::"l"(P.wuv + (bid * 8 + warp) * HDALL) : "memory");
  };
  if (PF_MAIN == 1 && elect()) prefetch_main();
  __syncwarp();
  if (B_DELAY > 0) __nanosleep(B_DELAY);
  if (elect()) {
    for (int i = warp; i < 9; i += 8) tma2d(sb + ST_O + i * 8192, &P.wo, i * 64, c0, sb + RB_W + 8);
    if (warp == 1 && bid < 27) asm volatile("cp.async.bulk.prefetch.tensor.2d.L2.global [%0, {%1,%2}];" ::"l"(bid < 18 ? &P.x : &P.mem), "r"(bid % 9 * 64), "r"(bid / 9 % 2 * 32) : "memory");
    for (int k = warp; k < 36; k += 8) {
      const int o = qk_slot(k) * 2048;
      tma2d(sb + (qk_in_reg(k) ? ST_Q : R_WQ) + o, &P.wq, c0, k * 16, sb + RB_W);
      tma2d(sb + (qk_in_reg(k) ? ST_K : R_WK) + o, &P.wk, c0, k * 16, sb + RB_W);
    }
    if (PF_V) for (int i = warp; i < 36; i += 8) asm volatile("cp.async.bulk.prefetch.tensor.2d.L2.global [%0, {%1,%2}];" ::"l"(&P.wv), "r"(c0), "r"(i * 16) : "memory");
    if (PF_MAIN == 2) prefetch_main();
  }
  __syncwarp();
  uint32_t wa = sb + ((li >> 1) * 8 + rho) * 128 + (((2 * w4 + (li & 1)) ^ rho) << 4);
  uint32_t la = sb + rho * 128 + ((li ^ rho) << 4);
  int ln = lane;
  if (warp == 0) TRG(1);
  mbar_wait(sb + RB_W + 8 * (warp >> 2), 0);
  if (warp == 0) TRG(2);

  if (warp < 4) {
    uint32_t wq[R_KR][4], wk[R_KR][4];
#pragma unroll
    for (int k = 0; k < R_KR; k++) { ldsm4t(wq[k], wa + ST_Q + k * 2048); ldsm4t(wk[k], wa + ST_K + k * 2048); }
    fence_async_smem();
    bar_sync(NB_P3, 256);
    asm volatile("barrier.cluster.arrive.relaxed.aligned;" ::: "memory");
    if (w4 < 2 && elect()) {
      mbar_expect(sb + RB_XF + 8 * w4, 9 * 4096);
      for (int i = 0; i < 9; i++) tma2d(sb + R_H + hoff(i) + w4 * 5120, &P.x, i * 64, w4 * 32, sb + RB_XF + 8 * w4);
    }
    if (w4 == 3 && elect()) {
      mbar_expect(sb + RB_QK, QK_TX);
      for (int i = 0; i < 5; i++) mbar_expect(sb + RB_MEM + 8 * i, i < 4 ? 2048 : 1024);
      for (int i = 0; i < 9; i++) tma2d(sb + R_HM + hoff(i), &P.mem, i * 64, 0, sb + RB_MEM + 8 * (i >> 1));
    }
    if (w4 == 2) sts128(sb + R_PS + (8 + lane) * 128 + ((5 ^ rho) << 4), 0u, 0u, 0u, 0u);
    __syncwarp();
    uint32_t qm = __shfl_sync(0xffffffffu, sb + R_QS + (rank & 1) * R_HS + (w4 * 16 + g) * 16 + t4 * 4, lane);
    const uint32_t peer = mapa(sb, rank ^ 1) - sb;

    uint32_t aq[P1_PRE][4], ak[P1_PRE][4];
    auto preload = [&]() {
#pragma unroll
      for (int i = 0; i < P1_PRE; i++) { ldsm4t(aq[i], wa + R_WQ + i * 2048); ldsm4t(ak[i], wa + R_WK + i * 2048); }
    };
    auto chain = [&](int s) {
      const bool LAST = s == 63;
      float cq[2][4], ck[2][4];
      for (;;) {
        uint32_t b[3][4];
        if (!PRE_EARLY) preload();
        mbar_wait(sb + RB_MEM, s & 1);
        TRB(0);
        uint32_t lb = la, bad = 0;
        ldsm4(b[0], lb + R_HM + hoff(0));
        ldsm4(b[1], (lb ^ 64) + R_HM + hoff(0));
#pragma unroll
        for (int hc = 0; hc < 18; hc++) {
          if (hc + 2 < 18) {
            if ((hc & 3) == 2) { lb = mbar_try_addr(sb + RB_MEM + 8 * ((hc + 2) >> 2), s & 1, la); bad |= lb ^ la; }
            ldsm4(b[(hc + 2) % 3], ((hc & 1) ? (lb ^ 64) : lb) + R_HM + hoff((hc + 2) >> 1));
          }
#pragma unroll
          for (int j = 0; j < 2; j++) {
            const int k = 2 * hc + j, sl = qk_slot(k);
            if (qk_in_reg(k)) {
              mma16816(cq[j], wq[sl], b[hc % 3][2 * j], b[hc % 3][2 * j + 1]);
              mma16816(ck[j], wk[sl], b[hc % 3][2 * j], b[hc % 3][2 * j + 1]);
            } else {
              static_assert(nsm(0) == 2, "first two steps come from shared memory");
              if (hc == 0) {
                mma16816z(cq[j], aq[j], b[0][2 * j], b[0][2 * j + 1]);
                mma16816z(ck[j], ak[j], b[0][2 * j], b[0][2 * j + 1]);
              } else {
                mma16816(cq[j], aq[sl % P1_PRE], b[hc % 3][2 * j], b[hc % 3][2 * j + 1]);
                mma16816(ck[j], ak[sl % P1_PRE], b[hc % 3][2 * j], b[hc % 3][2 * j + 1]);
              }
              if (sl + P1_PRE < R_NS) { ldsm4t(aq[sl % P1_PRE], wa + R_WQ + (sl + P1_PRE) * 2048); ldsm4t(ak[sl % P1_PRE], wa + R_WK + (sl + P1_PRE) * 2048); }
            }
          }
        }
        if (!__any_sync(0xffffffffu, bad)) break;
#pragma unroll 1
        for (int i = 1; i < 5; i++) mbar_wait(sb + RB_MEM + 8 * i, s & 1);
        if (PRE_EARLY) preload();
      }
      const uint32_t q0 = pack_bf16(cq[0][0] + cq[1][0], cq[0][1] + cq[1][1]), q1 = pack_bf16(cq[0][2] + cq[1][2], cq[0][3] + cq[1][3]);
      const uint32_t k0 = pack_bf16(ck[0][0] + ck[1][0], ck[0][1] + ck[1][1]), k1 = pack_bf16(ck[0][2] + ck[1][2], ck[0][3] + ck[1][3]);
      const uint32_t qp = qm + peer, bp = sb + RB_QK + peer;
      st_async32(qp, q0, bp);
      st_async32(qp + 128, q1, bp);
      st_async32(qp + 10 * R_GS, k0, bp);
      st_async32(qp + 10 * R_GS + 128, k1, bp);
      sts32(qm, q0);
      sts32(qm + 128, q1);
      sts32(qm + 10 * R_GS, k0);
      sts32(qm + 10 * R_GS + 128, k1);
      bar_arrive(NB_P1, 256);
      fence_async_smem();
      __syncwarp();
      arrive_elect(sb + RB_QK);
      TRB(1);
      float d[20];
#pragma unroll
      for (int i = 0; i < 20; i++) d[i] = 0.f;
      constexpr uint32_t HI = R_GS >> 4;
      const uint32_t qd = desc_lo(sb + R_QS, 128);
      mbar_wait(sb + RB_QK, s & 1);
      TRB(16);
      wg_fence();
#pragma unroll
      for (int k = 0; k < 8; k++) wgmma_ss_n40_a1b1(d, mk_desc(qd + (k >> 2) * (R_HS >> 4) + (k & 3) * 16, HI), mk_desc(qd + (k >> 2) * (R_HS >> 4) + (k & 3) * 16 + 6 * HI, HI), k != 0);
      wg_commit();
      bar_arrive(NB_S, 256);
      if (LAST) asm volatile("barrier.cluster.arrive.relaxed.aligned;" ::: "memory");
      const int ln = (qm >> 2) & 31, tt = ln & 3;
      if (w4 == 0) {
        const int gg = ln >> 2;
        const uint32_t pa = sb + R_PS + gg * 128;
        const uint32_t pax = pa + ((tt ^ gg) << 4), pam = pa + ((4 ^ gg) << 4) + tt * 4;
        wg_wait<0>();
        fence_regs(d);
        TRB(17);
        rmt_softmax_row<false>(d, 0, 0, pax, pam);
        bar_arrive(NB_PM, 160);
        TRB(18);
      } else if (w4 < 3) {
        const int tq = (ln & 24) + 4 * (w4 - 1) + ((ln >> 2) & 1), r7 = tq & 7;
        const uint32_t pa = sb + R_PS + (8 + tq) * 128;
        wg_wait<0>();
        fence_regs(d);
        rmt_softmax_row<true>(d, 0, tq - 8 * tt, pa + ((tt ^ r7) << 4), pa + ((4 ^ r7) << 4) + tt * 4);
        rmt_softmax_row<true>(d, 1, tq + 2 - 8 * tt, pa + 256 + ((tt ^ r7 ^ 2) << 4), pa + 256 + ((6 ^ r7) << 4) + tt * 4);
        fence_async_smem();
        bar_arrive(NB_PX, 192);
        TRW(15, 1);
      } else {
        if (!LAST) {
          if (ln < 7) mbar_expect(sb + RB_MEM + 8 * ln, ln == 6 ? QK_TX : ln == 5 ? 9216 : ln == 4 ? 1024 : 2048);
          if (ln == 11 && s < 62) mbar_expect(sb + RB_XF + 8 * (s & 1), 9 * 4096);
          __syncwarp();
        }
        wg_wait<0>();
        fence_regs(d);
      }
    };
    auto bulk = [&](int s) {
      const bool FIRST = s < 0;
      float dq[16], dk[16];
#pragma unroll
      for (int i = 0; i < 16; i++) dq[i] = dk[i] = 0.f;
      mbar_wait(sb + RB_XF + 8 * ((s + 1) & 1), ((s + 1) >> 1) & 1);
      const uint32_t hd = desc_lo(sb + R_H + ((s + 1) & 1) * 5120, 16), wd = desc_lo(sb + R_WQ, 16);
      auto bdesc = [&](int k) { return mk_desc(hd + (hoff(k >> 2) >> 4) + (k & 3) * 2, DHI_SW128); };
      const uint32_t qx = qm + 2 * R_GS + (qm & 12) * (R_GS / 4 - 1);
      if (!FIRST) bar_sync(NB_P3, 256);
      TRB(2);
      wg_fence();
      static_for<0, 73>([&](auto i_) {
        constexpr int i = decltype(i_)::value;
        constexpr char c = B_SEQ[i];
        constexpr int r = seq_count(c, i), nq = seq_count('q', i) + seq_count('Q', i), nk = seq_count('k', i) + seq_count('K', i);
        if constexpr (c == 'q') wgmma_rs_n32_b0(dq, wq[r][0], wq[r][1], wq[r][2], wq[r][3], bdesc(qk_step(r, true)), nq != 0);
        if constexpr (c == 'k') wgmma_rs_n32_b0(dk, wk[r][0], wk[r][1], wk[r][2], wk[r][3], bdesc(qk_step(r, true)), nk != 0);
        if constexpr (c == 'Q') wgmma_ss_n32_a1b0(dq, mk_desc(wd + r * 128, DHI_SW128), bdesc(qk_step(r, false)), nq != 0);
        if constexpr (c == 'K') wgmma_ss_n32_a1b0(dk, mk_desc(wd + (R_NS + r) * 128, DHI_SW128), bdesc(qk_step(r, false)), nk != 0);
        if constexpr (c == '|') {
          if (!FIRST) bar_sync(NB_RD, 256);
          TRB(6);
        }
      });
      wg_commit();
      if (FIRST) asm volatile("barrier.cluster.wait.aligned;" ::: "memory");
      if (PRE_EARLY) preload();
      wg_wait<0>();
      fence_regs(dq);
      fence_regs(dk);
      TRB(3);
#pragma unroll
      for (int r = 0; r < 2; r++) {
        sts128(qx + r * 128, pack_bf16(dq[2 * r], dq[2 * r + 1]), pack_bf16(dq[4 + 2 * r], dq[5 + 2 * r]), pack_bf16(dq[8 + 2 * r], dq[9 + 2 * r]), pack_bf16(dq[12 + 2 * r], dq[13 + 2 * r]));
        sts128(qx + 4 * R_GS + r * 128, pack_bf16(dk[2 * r], dk[2 * r + 1]), pack_bf16(dk[4 + 2 * r], dk[5 + 2 * r]), pack_bf16(dk[8 + 2 * r], dk[9 + 2 * r]), pack_bf16(dk[12 + 2 * r], dk[13 + 2 * r]));
      }
      __syncwarp();
      arrive_elect(sb + RB_QXL);
      TRB(4);
    };
    TRG(3);
#pragma unroll 1
    for (int s = -1; s < 63;) {
      asm volatile("" : "+r"(wa), "+r"(la), "+r"(qm));
      bulk(s);
      s++;
#ifdef DEV_TRS
      TRG(16 + s);
#endif
      chain(s);
    }
#ifdef DEV_TRACE
    bar_sync(NB_S, 256);
    for (int i = threadIdx.x; i < 16 * 32; i += 128) g_trace_b[bid * 4096 + i] = lds32(sb + R_QS + R_GS + ((i >> 8) ^ 1) * R_HS + (i & 255) * 4);
#endif
  } else {
    uint32_t wo[9][4][4], wv[R_VR][4];
#pragma unroll
    for (int i = 0; i < 9; i++) {
      const int T = i < 8 ? 8 * (i >> 1) + 2 * w4 + (i & 1) : 32 + 2 * (w4 & 1) + (w4 >> 1);
      const int quad = i < 8 ? (g >> 2) * 2 + (g & 1) : g & 3, odd = i < 8 ? (g >> 1) & 1 : g >> 2;
      const uint32_t a = sb + ST_O + (T >> 2) * 8192 + t4 * 256 + (quad & 1) * 8;
      const uint32_t ch = (T & 3) * 2 + (quad >> 1), sel = odd ? 0x7632 : 0x5410;
      const uint32_t a0 = a + ((ch ^ (2 * t4)) << 4), a1 = a + 128 + ((ch ^ (2 * t4 + 1)) << 4);
#pragma unroll
      for (int k = 0; k < 8; k++) {
        const uint2 x = lds64(a0 + k * 1024), y = lds64(a1 + k * 1024);
        wo[i][k >> 1][(k & 1) * 2] = __byte_perm(x.x, y.x, sel);
        wo[i][k >> 1][(k & 1) * 2 + 1] = __byte_perm(x.y, y.y, sel);
      }
    }
    fence_async_smem();
    bar_arrive(NB_P3, 256);
    bar_sync(NB_O, 128);
    if (w4 == 0 && elect()) mbar_expect(sb + RB_W + 8, 73728);
    if (elect())
      for (int k = w4; k < 36; k += 4) {
        const int sl = v_slot(k);
        tma2d(sb + (v_in_reg(k) ? (sl < 6 ? ST_V0 : ST_V1) : R_WV) + sl * 2048, &P.wv, c0, k * 16, sb + RB_W + 8);
      }
    __syncwarp();
    mbar_wait(sb + RB_W + 8, 1);
#pragma unroll
    for (int r = 0; r < R_VR; r++) ldsm4t(wv[r], wa + (r < 6 ? ST_V0 : ST_V1) + r * 2048);
    fence_async_smem();
    asm volatile("barrier.cluster.arrive.relaxed.aligned;" ::: "memory");
    const uint32_t sb0 = mapa(sb, 0), tok = rank & 7;
    uint32_t rsb = mapa(sb + RB_RS, (w4 & 1) * 8 + 2 * t4);
    const uint32_t rrow = rank ^ ((t4 & 1) << 3) ^ (t4 & 2), nrow = rank ^ ((t4 & 1) << 2);
    uint32_t rsA = rsb + (R_RS - RB_RS) + rrow * 128 + (((w4 >> 1) * 64 + g * 8) ^ ((rrow & 7) << 4));
    uint32_t rsN = rsb + (R_RS + 8192 - RB_RS) + nrow * 64 + (((w4 >> 1) * 32 + g * 4) ^ (((nrow >> 1) & 3) << 4));
    const uint32_t cp = 16 * (t4 >> 1) + 8 * ((g >> 1) & 1) + 4 * (t4 & 1) + 2 * (g >> 2) + (g & 1);
    uint32_t agd = sb0 + R_HM + tok * 128 + hoff(2 * w4 + (cp >> 4)) + ((((rank >> 3) * 4 + ((cp & 15) >> 2)) ^ tok) << 4) + (cp & 3) * 4;
    uint32_t* xb = g_xch + rank * 288 + w4 * 64 + lane * 2;
    uint32_t vx[8];
#pragma unroll
    for (int i = 0; i < 8; i++) vx[i] = 0;

    auto step = [&](int s) {
      const bool FIRST = s < 0, LAST = s == 63, MID = !FIRST && !LAST;
      const int par = (s + 1) & 1;
      float d[20];
#pragma unroll
      for (int i = 0; i < 20; i++) d[i] = 0.f;
      if (!LAST) mbar_wait(sb + RB_XF + 8 * par, ((s + 1) >> 1) & 1);
      const uint32_t hd = desc_lo(sb + R_H + par * 4096, 16), vd = desc_lo(sb + R_WV, 16);
      if (!FIRST) {
        if (w4 == 0) {
          mbar_wait(sb + RB_QXL, s & 1);
          mbar_wait(sb + RB_MEM + QX_AFTER * 8, s & 1);
          fence_async_smem();
          if (elect()) {
            const uint32_t src = sb + R_QS + (rank & 1) * R_HS + 2 * R_GS, dst = mapa(src, rank ^ 1), bar = mapa(sb + RB_QK, rank ^ 1), cut = 256 + rank * 512;
            asm volatile("cp.async.bulk.shared::cluster.shared::cta.mbarrier::complete_tx::bytes [%0], [%1], %2, [%3];" ::"r"(dst + cut), "r"(src + cut), "r"(8 * R_GS - cut), "r"(bar) : "memory");
            asm volatile("cp.async.bulk.shared::cluster.shared::cta.mbarrier::complete_tx::bytes [%0], [%1], %2, [%3];" ::"r"(dst), "r"(src), "r"(cut), "r"(bar) : "memory");
          }
          __syncwarp();
          TRW(7, 0);
        }
#pragma unroll
        for (int i = 0; i < 5; i++) { mbar_wait(sb + RB_MEM + 8 * i, s & 1); if (i == 4) TRW(30, 2); }
        fence_async_smem();
        bar_sync(NB_P1, 256);
      }
      wg_fence();
#pragma unroll
      for (int k = 0; k < 36; k++) {
        if (k == V_N1 && !FIRST) bar_sync(NB_S, 256);
        const uint64_t db = mk_desc(hd + (hoff(k >> 2) >> 4) + (k & 3) * 2, DHI_SW128);
        if (v_in_reg(k)) wgmma_rs_n40_b0(d, wv[v_slot(k)][0], wv[v_slot(k)][1], wv[v_slot(k)][2], wv[v_slot(k)][3], db, 1);
        else wgmma_ss_n40_a1b0(d, mk_desc(vd + v_slot(k) * 128, DHI_SW128), db, k != 0);
      }
      wg_commit();
      TRB(8);
      uint32_t vm0, vm1, vn[8];
      auto pack_v = [&]() {
#pragma unroll
        for (int i = 0; i < 8; i++) vn[i] = par ? pack_bf16(d[2 * i + 4], d[2 * i + 5]) : pack_bf16(d[2 * i], d[2 * i + 1]);
      };
      if (MID) {
        float o[4] = {0.f, 0.f, 0.f, 0.f};
        uint32_t b0[4], b1[4];
        bar_sync(NB_PM, 160);
        ldsm4(b0, la + R_PS);
        ldsm4(b1, (la ^ 64) + R_PS);
        {
          const uint32_t x0[4] = {vx[0], vx[1], vx[2], vx[3]}, x1[4] = {vx[4], vx[5], vx[6], vx[7]};
          float o2[4] = {0.f, 0.f, 0.f, 0.f};
          wg_wait<0>();
          fence_regs(d);
          TRB(9);
          mma16816(o, x0, b0[0], b0[1]);
          mma16816(o2, x1, b0[2], b0[3]);
          vm0 = par ? pack_bf16(d[0], d[1]) : pack_bf16(d[16], d[17]);
          vm1 = par ? pack_bf16(d[2], d[3]) : pack_bf16(d[18], d[19]);
          float o3[4] = {0.f, 0.f, 0.f, 0.f};
          mma1688(o3, vm0, vm1, b1[0]);
          stsm2t(wa + R_OS, pack_bf16(o[0] + o2[0] + o3[0], o[1] + o2[1] + o3[1]), pack_bf16(o[2] + o2[2] + o3[2], o[3] + o2[3] + o3[3]));
        }
        bar_sync(NB_O, 128);
        TRB(11);
        ldsm4(b0, la + R_OS);
        ldsm4(b1, (la ^ 64) + R_OS);
        auto send = [&](int j, const float (&c0_)[4], const float (&c1_)[4]) {
          st_async64(rsA + j * 2048, pack_bf16(c0_[0], c0_[2]), pack_bf16(c1_[0], c1_[2]), rsb);
          st_async64(rsA + j * 2048 + CTA1, pack_bf16(c0_[1], c0_[3]), pack_bf16(c1_[1], c1_[3]), rsb + CTA1);
        };
        auto tile = [&](float (&c)[4], int i, int k) {
          if (k == 0) mma16816z(c, wo[i][0], b0[0], b0[1]);
          else mma16816(c, wo[i][k], k < 2 ? b0[2 * k] : b1[2 * k - 4], k < 2 ? b0[2 * k + 1] : b1[2 * k - 3]);
        };
        {
          float c[4][4];
          mma16816z(c[0], wo[0][0], b0[0], b0[1]);
          mma16816z(c[1], wo[1][0], b0[0], b0[1]);
          mma16816z(c[2], wo[0][2], b1[0], b1[1]);
          mma16816z(c[3], wo[1][2], b1[0], b1[1]);
          mma16816(c[0], wo[0][1], b0[2], b0[3]);
          mma16816(c[1], wo[1][1], b0[2], b0[3]);
          mma16816(c[2], wo[0][3], b1[2], b1[3]);
          mma16816(c[3], wo[1][3], b1[2], b1[3]);
          pack_v();
#pragma unroll
          for (int i = 0; i < 4; i++) { c[0][i] += c[2][i]; c[1][i] += c[3][i]; }
          send(0, c[0], c[1]);
          fence_regs(vn);
        }
        sched_fence(rsb);
        TRB(13);
        {
          float c[3][4];
#pragma unroll
          for (int k = 0; k < 4; k++) { tile(c[0], 8, k); tile(c[1], 2, k); tile(c[2], 3, k); }
          st_async32(rsN, pack_bf16(c[0][0], c[0][2]), rsb);
          st_async32(rsN + CTA1, pack_bf16(c[0][1], c[0][3]), rsb + CTA1);
          send(1, c[1], c[2]);
        }
        sched_fence(la);
        {
          float c[4][4];
#pragma unroll
          for (int k = 0; k < 4; k++)
#pragma unroll
            for (int i = 0; i < 4; i++) tile(c[i], 4 + i, k);
          if (P3_EARLY == 1) { sched_fence(rsA); bar_arrive(NB_P3, 256); }
          send(2, c[0], c[1]);
          send(3, c[2], c[3]);
          if (P3_EARLY == 2) bar_arrive(NB_P3, 256);
        }
        TRB(12);
      } else {
        if (LAST) bar_sync(NB_PM, 160);
        wg_wait<0>();
        fence_regs(d);
        if (LAST) asm volatile("barrier.cluster.arrive.relaxed.aligned;" ::: "memory");
        vm0 = pack_bf16(d[16], d[17]);
        vm1 = pack_bf16(d[18], d[19]);
        pack_v();
      }
      if (FIRST) {
        asm volatile("barrier.cluster.wait.aligned;" ::: "memory");
        TRG(7);
      } else {
        float e[16];
#pragma unroll
        for (int i = 0; i < 16; i++) e[i] = 0.f;
        uint32_t z0 = 0, z1 = 0;
        asm volatile("" : "+r"(z0), "+r"(z1), "+r"(vm0), "+r"(vm1));
        const uint32_t pd = desc_lo(sb + R_PS + 1024, 16);
        fence_regs(vx);
        bar_sync(NB_PX, 192);
        wg_fence();
        wgmma_rs_n32_b0(e, vx[0], vx[1], vx[2], vx[3], mk_desc(pd, DHI_SW128), 0);
        wgmma_rs_n32_b0(e, vx[4], vx[5], vx[6], vx[7], mk_desc(pd + 2, DHI_SW128), 1);
        wgmma_rs_n32_b0(e, vm0, vm1, z0, z1, mk_desc(pd + 4, DHI_SW128), 1);
        wg_commit();
        if (!P3_EARLY && !LAST) bar_arrive(NB_P3, 256);
        wg_wait<0>();
        fence_regs(e);
        fence_regs(vx);
        bar_sync(NB_O, 128);
        stsm4t(wa + R_PS + 1024, pack_bf16(e[0], e[1]), pack_bf16(e[2], e[3]), pack_bf16(e[4], e[5]), pack_bf16(e[6], e[7]));
        stsm4t(wa + R_PS + 3072, pack_bf16(e[8], e[9]), pack_bf16(e[10], e[11]), pack_bf16(e[12], e[13]), pack_bf16(e[14], e[15]));
        TRB(14);
      }
      auto store_x = [&]() {
        fence_async_smem();
        if (w4 == 2) bar_sync(NB_O2, 128); else bar_arrive(NB_O2, 128);
        if (w4 == 2 && elect()) {
          asm volatile("cp.async.bulk.tensor.2d.global.shared::cta.bulk_group [%0, {%1,%2}], [%3];" ::"l"(&P.ox), "r"(c0), "r"(3 * SEQ + s * 32), "r"(sb + R_PS + 1024) : "memory");
          asm volatile("cp.async.bulk.commit_group;" ::: "memory");
        }
        __syncwarp();
      };
      if (MID) {
        const uint32_t tag = ((s >> 1) & 1) ^ 1;
        uint32_t* x = xb + (s & 1) * XCH_SLOT;
        uint32_t* xw = x + cl * XCH_CL;
        const int src = (ln & 7) + (ln >> 4) * 8, hf = (ln >> 3) & 1;
        const uint32_t ra = sb + R_RS + w4 * 2048 + src * 128 + ((hf ^ (ln & 7)) << 4);
        auto delay = [&](uint32_t t0) {
          while ((uint32_t)clock() - t0 < POLL_DELAY + w4 * POLL_STAG) {}
        };
        uint32_t rn;
        const uint32_t agb = sb0 + RB_MEM + 8 * w4 + (uint32_t)(ln >> 5);
        if (w4 == 3) {
          const int cn = 8 * (ln & 1) + (ln >> 2), no = 64 + 2 * (cn - ln);
          const uint32_t rb = sb + R_RS + 8192 + src * 64 + ((hf ^ ((ln >> 1) & 3)) << 4);
          mbar_wait(sb + RB_RS, s & 1);
          const uint2 o = xch_reduce<4>(ra, ln >> 3, xw, tag);
          const uint2 on = xch_reduce<2>(rb, hf, xw + no, tag);
          const uint32_t t0 = clock();
          bar_arrive(NB_RD, 256);
          TRW(27, 3);
          store_x();
          const uint32_t off = (ln & 2) * 4 * CTA1;
          const uint32_t agn = sb0 + R_HM + tok * 128 + hoff(8) + ((((rank >> 3) * 4 + (cn >> 2)) ^ tok) << 4) + (cn & 3) * 4;
          XSend<16, 6> xs(agd, agb);
          delay(t0);
          const uint32_t r = xch_poll<true>(x, cl, o, x + no, on, rn);
          TRW(28, 3);
          xs.send(r);
          XSend<8, 1>(agn ^ off, (agb + 8) ^ off).send(rn);
          TRW(22, 3);
        } else {
          mbar_wait(sb + RB_RS, s & 1);
          TRB(19);
          const uint2 o = xch_reduce<4>(ra, ln >> 3, xw, tag);
          const uint32_t t0 = clock();
          bar_arrive(NB_RD, 256);
          TRB(25);
          store_x();
          if (w4 == 1 && rank < 9 && s < 62 && elect()) {
            tma2d_mc(sb + R_H + hoff(rank) + (s & 1) * 5120, &P.x, rank * 64, (s + 2) * 32, sb + RB_XF + 8 * (s & 1), 0xffff);
            asm volatile("cp.async.bulk.prefetch.tensor.2d.L2.global [%0, {%1,%2}];" ::"l"(&P.x), "r"(rank * 64), "r"(min(s + 3 + cl, 63) * 32) : "memory");
          }
          __syncwarp();
          XSend<16, 12> xs(agd, agb);
          delay(t0);
          asm volatile("cp.async.bulk.wait_group.read 0;" ::: "memory");
          const uint32_t r = xch_poll<false>(x, cl, o, x, o, rn);
          TRB(26); TRW(10, 1); TRW(20, 2);
          xs.send(r);
          TRB(21); TRW(23, 1); TRW(24, 2);
          if (w4 == 2 && (s & 3) == 3) {
            asm volatile("cp.async.bulk.wait_group 0;" ::: "memory");
#if PUB_REL
            asm volatile("{.reg .pred q; elect.sync _|q, 0xffffffff; @q red.release.gpu.global.add.u32 [%0], 1;}" ::"l"(&g_sync[SY_OX + (s >> 2)]) : "memory");
#else
            asm volatile("{.reg .pred q; elect.sync _|q, 0xffffffff; @q red.relaxed.gpu.global.add.u32 [%0], 1;}" ::"l"(&g_sync[SY_OX + (s >> 2)]) : "memory");
#endif
          }
        }
      }
#pragma unroll
      for (int i = 0; i < 8; i++) vx[i] = vn[i];
    };
    TRG(5);
#pragma unroll 1
    for (int s = -1; s < 64; s++) {
      asm volatile("" : "+r"(wa), "+r"(la), "+r"(rsb), "+r"(rsA), "+r"(rsN), "+r"(agd), "+r"(ln), "+l"(xb));
      step(s);
    }
    if (threadIdx.x == 128) TRE(64 + blockIdx.x);
    fence_async_smem();
    bar_sync(NB_O2, 128);
    if (w4 == 2) {
      if (elect()) {
        asm volatile("cp.async.bulk.tensor.2d.global.shared::cta.bulk_group [%0, {%1,%2}], [%3];" ::"l"(&P.ox), "r"(c0), "r"(3 * SEQ + 63 * 32), "r"(sb + R_PS + 1024) : "memory");
        asm volatile("cp.async.bulk.commit_group;" ::: "memory");
        asm volatile("cp.async.bulk.wait_group 0;" ::: "memory");
#if PUB_REL
        asm volatile("red.release.gpu.global.add.u32 [%0], 1;" ::"l"(&g_sync[SY_OX + 15]) : "memory");
#else
        asm volatile("red.relaxed.gpu.global.add.u32 [%0], 1;" ::"l"(&g_sync[SY_OX + 15]) : "memory");
#endif
      }
      __syncwarp();
    } else {
      uint32_t* z = g_xch + XCH_SLOT + cl * XCH_CL + rank * 288 + (w4 == 3 ? 64 : w4 * 32) + ln;
      st_relaxed32(z, 0u); st_relaxed32(z + 96, 0u); st_relaxed32(z + 192, 0u);
    }
#ifdef DEV_TRACE
    bar_sync(NB_S, 256);
#endif
  }
  asm volatile("barrier.cluster.wait.aligned;\nbarrier.cluster.arrive.relaxed.aligned;" ::: "memory");
  {
    uint32_t rank, cl, sb, warp;
    asm volatile("mov.u32 %0, %%cluster_ctarank;" : "=r"(rank));
    asm volatile("{.reg .b32 t; mov.u32 t, %%ctaid.x; shr.u32 %0, t, 4;}" : "=r"(cl));
    asm volatile("{.reg .b64 t; cvta.to.shared.u64 t, %1; cvt.u32.u64 %0, t;}" : "=r"(sb) : "l"(smem_rmt));
    asm volatile("{.reg .b32 t; mov.u32 t, %%tid.x; shr.u32 t, t, 5; shfl.sync.idx.b32 %0, t, 0, 31, -1;}" : "=r"(warp));
    const int w4 = warp & 3;
    const int lane = threadIdx.x & 31, wg = warp >> 2, u = rank >> 1, blk = cl == 3 ? 12 + (rank & 1) : 14 + (rank & 1), nn = min(cl, 2u);
    constexpr int T_E = 40960, T_R = 4 * T_E;
    auto load_w = [&](int kb) {
      const uint32_t fb = sb + RB_TF + 8 * (kb & 3);
      mbar_expect(fb, T_E);
      tma3d_mc(sb + (kb & 3) * T_E + 16384 + (rank & 1) * 12288, &P.wo3, 0, u * 512 + kb * 64 + (rank & 1) * 32, nn * 3, fb, 3 << (rank & 14));
    };
    auto load_a = [&](int kb) { tma2d(sb + (kb & 3) * T_E, &P.ox128, u * 512 + kb * 64, 3 * SEQ + blk * 128, sb + RB_TF + 8 * (kb & 3)); };
    TRT(0, 0);
    if (warp == 0 && elect()) {
#pragma unroll 1
      for (int kb = 0; kb < 4; kb++) load_w(kb);
      for (int it = 0; ld_acquire(g_sync + SY_OX + blk) < OX_TARGET; it++)
        if (it > (1 << 22)) __trap();
#pragma unroll 1
      for (int kb = 0; kb < 4; kb++) load_a(kb);
    }
    __syncwarp();
    TRT(1, 0);
    float acc[96];
#pragma unroll
    for (int i = 0; i < 96; i++) acc[i] = 0.f;
    const uint32_t te = mapa(sb + RB_TE, (rank & 14) + (lane & 1));
#pragma unroll 1
    for (int kb = 0; kb < 8; kb++) {
      const uint32_t st = sb + (kb & 3) * T_E, a = desc_lo(st + wg * 8192, 16), b = desc_lo(st + 16384, 4096);
      mbar_wait(sb + RB_TF + 8 * (kb & 3), kb >> 2);
      if (kb == 0) TRT(2, 0);
      wg_fence();
#pragma unroll
      for (int kk = 0; kk < 4; kk++) wgmma_ss_n192_a0b1(acc, mk_desc(a + kk * 2, DHI_SW128), mk_desc(b + (kk >> 1) * 768 + (kk & 1) * 128, DHI_SW128), 1);
      wg_commit();
      wg_wait<1>();
      if (kb >= 1 && kb <= 4) {
        if (w4 == 0 && lane < 2) mbar_arrive_cl(te + 8 * (kb - 1));
        if (warp == 0) {
          mbar_wait(sb + RB_TE + 8 * (kb - 1), 0);
          if (elect()) { load_w(kb + 3); load_a(kb + 3); }
        }
        __syncwarp();
      }
    }
    asm volatile("barrier.cluster.wait.aligned;" ::: "memory");
    wg_wait<0>();
    fence_regs(acc);
    TRT(3, 0);
    const uint32_t ra = mapa(sb + T_R + u * 6144 + ((lane ^ u) << 4), 2 * warp + (rank & 1)), rb = mapa(sb + RB_TR, 2 * warp + (rank & 1));
#pragma unroll
    for (int j = 0; j < 12; j++) {
      const int o = 16 * (j >> 1) + (j & 1);
      st_async128(ra + j * 512, pack_bf16(acc[o], acc[o + 2]), pack_bf16(acc[o + 4], acc[o + 6]), pack_bf16(acc[o + 8], acc[o + 10]), pack_bf16(acc[o + 12], acc[o + 14]), rb);
    }
    TRT(4, 0);
    const int r = lane & 7, m = lane >> 3, g = lane >> 2;
    const uint32_t la = sb + T_R + r * 6144 + wg * 3072 + (m >> 1) * 512;
    uint32_t* out = P.out + (blk * 128 + u * 16 + 2 * w4 + 8 * (g & 1)) * DM + DM / 2 + nn * 96 + wg * 48 + (g >> 1) * 4 + (lane & 3);
    mbar_wait(sb + RB_TR, 0);
    TRT(5, 0);
    asm volatile("barrier.cluster.arrive.relaxed.aligned;" ::: "memory");
#pragma unroll 1
    for (int J = 0; J < 3; J++) {
      float c[2][4];
      uint32_t v[4][4];
#pragma unroll
      for (int j = 0; j < 4; j++) ldsm4t(v[j], la + J * 1024 + (((8 * w4 + 4 * (m & 1) + j) ^ r) << 4));
#pragma unroll
      for (int j = 0; j < 4; j++) {
        const uint32_t b0 = g == 2 * j ? 0x3f803f80u : 0u, b1 = g == 2 * j + 1 ? 0x3f803f80u : 0u;
        if (j < 2) mma16816z(c[j], v[j], b0, b1);
        else mma16816(c[j & 1], v[j], b0, b1);
      }
      out[J * 16] = pack_bf16(c[0][0] + c[1][0], c[0][1] + c[1][1]);
      out[J * 16 + DM] = pack_bf16(c[0][2] + c[1][2], c[0][3] + c[1][3]);
    }
    TRT(6, 0);
    if (warp == 0) TRG(6);
    asm volatile("barrier.cluster.wait.aligned;" ::: "memory");
  }
  if (threadIdx.x == 96) TRE(128 + blockIdx.x);
}

void rmt_setup() {
  cudaFuncSetAttribute(rmt_kernel, cudaFuncAttributeMaxDynamicSharedMemorySize, R_SMEM);
  cudaFuncSetAttribute(rmt_kernel, cudaFuncAttributeNonPortableClusterSizeAllowed, 1);
}
void rmt_launch(EncodeFn enc, void* const* d_in, void* scr, void* out) {
  RmtParams R;
  map2d(enc, &R.wq, d_in[8], DM, HDALL, 16);
  map2d(enc, &R.wk, d_in[9], DM, HDALL, 16);
  map2d(enc, &R.wv, d_in[10], DM, HDALL, 16);
  map2d(enc, &R.wo, d_in[11], HDALL, DM, 64);
  map2d(enc, &R.x, d_in[6], SEQ, DM, 32);
  map2d(enc, &R.mem, d_in[7], 8, DM, 8);
  map2d(enc, &R.ox, scr, 4 * SEQ, HDALL, 32);
  cudaLaunchConfig_t cfg = {};
  map2d(enc, &R.ox128, scr, 4 * SEQ, HDALL, 128);
  map3d(enc, &R.wo3, d_in[11], HDALL, DM, 32, 3);
  R.out = (uint32_t*)out;
  R.ckv = (const __nv_bfloat16*)d_in[1]; R.wuk = (const __nv_bfloat16*)d_in[3]; R.wuv = (const __nv_bfloat16*)d_in[4];
  cfg.gridDim = dim3(64);
  cfg.blockDim = dim3(256);
  cfg.dynamicSmemBytes = R_SMEM;
  cfg.stream = cudaStreamPerThread;
  cudaLaunchAttribute at[1];
  at[0].id = cudaLaunchAttributeClusterDimension;
  at[0].val.clusterDim.x = 16;
  at[0].val.clusterDim.y = 1;
  at[0].val.clusterDim.z = 1;
  cfg.attrs = at;
  cfg.numAttrs = 1;
  cudaLaunchKernelEx(&cfg, rmt_kernel, R);
}


const uint16_t h_order[] = {
    4096, 4097, 34, 35, 36, 37, 38, 39, 40, 41, 42, 43, 44, 45, 46, 47, 48, 49, 50, 51,
    52, 53, 54, 55, 56, 57, 58, 59, 60, 61, 62, 63, 64, 65, 66, 67, 68, 69, 70, 71,
    4103, 4102, 4101, 4100, 4099, 4098, 72, 73, 74, 75, 76, 77, 78, 79, 4111, 4110, 4109, 4108, 4107, 4106,
    80, 81, 82, 83, 84, 85, 86, 87, 4119, 4118, 4117, 4116, 4115, 4114, 88, 89, 90, 91, 92, 93,
    94, 95, 4127, 4126, 4125, 4124, 4123, 4122, 96, 97, 98, 99, 100, 101, 102, 103, 4135, 4134, 4133, 4132,
    4131, 4130, 104, 105, 106, 107, 108, 109, 110, 111, 4143, 4142, 4141, 4140, 4139, 4138, 112, 113, 114, 115,
    116, 117, 118, 119, 4151, 4150, 4149, 4148, 4147, 4146, 120, 121, 122, 123, 124, 125, 126, 127, 4159, 4158,
    4157, 4156, 4155, 4154, 128, 129, 130, 131, 132, 133, 134, 135, 4167, 4166, 4165, 4164, 4163, 4162, 136, 137,
    138, 12288, 12544, 12800, 139, 140, 141, 142, 143, 4175, 4174, 4173, 4172, 4171, 4170, 144, 145, 146, 147, 148,
    149, 150, 151, 4183, 4182, 4181, 4180, 4179, 4178, 152, 153, 154, 155, 156, 157, 158, 12289, 12545, 12801, 159,
    4191, 4190, 4189, 4188, 4187, 4186, 160, 161, 162, 163, 164, 165, 166, 167, 4199, 4198, 4197, 4196, 4195, 4194,
    168, 169, 170, 171, 172, 173, 174, 175, 4207, 4206, 4205, 4204, 4203, 4202, 176, 177, 178, 179, 180, 181,
    182, 183, 4215, 4214, 4213, 12290, 12546, 12802, 4212, 4211, 4210, 184, 185, 186, 187, 188, 189, 190, 191, 4223,
    4222, 4221, 4220, 4219, 4218, 192, 193, 194, 195, 196, 197, 198, 199, 4231, 4230, 4229, 4228, 4227, 4226, 200,
    201, 202, 203, 204, 205, 206, 207, 4239, 4238, 4237, 4236, 4235, 4234, 208, 209, 210, 211, 212, 213, 214,
    215, 4247, 4246, 4245, 4244, 4243, 4242, 216, 217, 218, 219, 220, 221, 222, 12291, 12547, 12803, 223, 4255, 4254,
    4253, 4252, 4251, 4250, 224, 225, 226, 227, 228, 229, 230, 231, 4263, 4262, 4261, 4260, 4259, 4258, 232, 233,
    234, 235, 236, 237, 238, 239, 4271, 4270, 4269, 4268, 4267, 4266, 240, 241, 242, 243, 244, 245, 246, 247,
    4279, 4278, 4277, 4276, 4275, 4274, 248, 249, 250, 251, 252, 253, 254, 255, 4287, 4286, 4285, 4284, 4283, 4282,
    4295, 4294, 4293, 4292, 4291, 4290, 4303, 4302, 4301, 4300, 4299, 4298, 4311, 4310, 4309, 4308, 4307, 4306, 4319, 4318,
    4317, 4316, 4315, 4314, 4327, 8194, 8450, 8706, 4326, 12292, 12548, 12804, 4325, 4324, 4323, 4322, 4335, 4334, 4333, 4332,
    4331, 4330, 4343, 4342, 4341, 4340, 4339, 4338, 4351, 4350, 4349, 4348, 4347, 4346, 4105, 4104, 4113, 4112, 4121, 4120,
    4129, 4128, 4137, 4136, 4145, 4144, 4153, 4152, 8197, 8453, 8709, 4161, 4160, 4169, 4168, 4177, 4176, 4185, 4184, 4193,
    4192, 4201, 4200, 4209, 4208, 4217, 4216, 4225, 4224, 4233, 4232, 12293, 12549, 12805, 4241, 4240, 8199, 8455, 8711, 4249,
    8196, 8452, 8708, 8195, 8451, 8707, 8193, 8449, 8705, 8198, 8454, 8710, 4248, 8192, 8448, 8704, 4257, 4256, 4265, 4264,
    4273, 4272, 4281, 4280, 4289, 4288, 4297, 20486, 20742, 20998, 4296, 4305, 4304, 4313, 4312, 4321, 4320, 4329, 4328, 4337,
    4336, 4345, 4344,
};
int build_tasks(uint16_t* t) {
  int n = 0;
#ifdef DEV_ORDER
  if (const char* fn = getenv("ORDER")) {
    FILE* f = fopen(fn, "r");
    int v;
    while (fscanf(f, "%d", &v) == 1) t[n++] = v;
    fclose(f);
    return n;
  }
#endif
  static_assert(sizeof(h_order) / 2 <= MAXTASK, "tasks");
  for (; n < (int)(sizeof(h_order) / 2); n++) t[n] = h_order[n];
  return n;
}

}

extern "C" void kernel_launch(void* const* d_in, const int* in_sizes, int n_in, void* d_out, int out_size) {
  (void)in_sizes; (void)n_in; (void)out_size;
  static EncodeFn enc = nullptr;
  static void* scr = nullptr;
  if (!enc) {
    cudaDriverEntryPointQueryResult q;
    cudaGetDriverEntryPoint("cuTensorMapEncodeTiled", (void**)&enc, cudaEnableDefault, &q);
    cudaGetSymbolAddress(&scr, g_scr);
    cudaFuncSetAttribute(main_kernel, cudaFuncAttributeMaxDynamicSharedMemorySize, M_SMEM);
    rmt_setup();
  }
  rmt_launch(enc, d_in, scr, d_out);

  MainParams P;
  map2d(enc, &P.ckv, d_in[1], SEQ, 512, 128);
  map3d(enc, &P.wuk, d_in[3], 512, HDALL, 64, 2);
  map3d(enc, &P.wuv, d_in[4], 512, HDALL, 64, 2);
  map2d(enc, &P.ax, d_in[0], SEQ, DM, 64);
  map2d(enc, &P.wq, d_in[2], DM, HDALL, 64);
  map2d(enc, &P.scr, scr, 4 * SEQ, HDALL, 128);
  map3d(enc, &P.woa, d_in[5], HDALL, DM, 32, 3);
  map3d(enc, &P.wob, d_in[11], HDALL, DM, 32, 3);
  map2d(enc, &P.scr_st, scr, 4 * SEQ, HDALL, ST_ROWS);
  map2d(enc, &P.out_st, d_out, SEQ, 2 * DM, ST_ROWS);
  map3d(enc, &P.woa2, d_in[5], HDALL, DM, 32, 2);
  map3d(enc, &P.wob2, d_in[11], HDALL, DM, 32, 2);
  P.ntask = build_tasks(P.tasks);

  cudaLaunchConfig_t cfg = {};
  cfg.gridDim = dim3(2 * NCL);
  cfg.blockDim = dim3(384);
  cfg.dynamicSmemBytes = M_SMEM;
  cfg.stream = cudaStreamPerThread;
  cudaLaunchAttribute at[1];
  at[0].id = cudaLaunchAttributeProgrammaticStreamSerialization;
  at[0].val.programmaticStreamSerializationAllowed = 1;
  cfg.attrs = at;
  cfg.numAttrs = 1;
#ifdef DEV_SERIAL
  cfg.numAttrs = 0;
#endif
  cudaLaunchKernelEx(&cfg, main_kernel, P);
}
```

```cpp
#include <cuda_runtime.h>
#include <cuda_bf16.h>
#include <cuda.h>
#include <stdint.h>
#ifdef DEV_ORDER
#include <stdio.h>
#include <stdlib.h>
#endif

namespace {

constexpr int SEQ = 2048, DM = 576, HDALL = 4096;

__device__ __nv_bfloat16 g_scr[4ull * SEQ * HDALL];
constexpr int SY_Q = 0, SY_EXIT = 16, SY_KV = 32, SY_CTX = 32 + 256, SY_OX = 32 + 512, SY_N = 32 + 512 + 32;
__device__ unsigned g_sync[SY_N];

#ifdef DEV_END
__device__ long long g_end[512];
#define TRE(i) do { long long c_; asm volatile("mov.u64 %0, %%globaltimer;" : "=l"(c_)); g_end[i] = c_; } while (0)
#else
#define TRE(i)
#endif
#ifdef DEV_TRACE
__device__ long long g_trace[132 * 4096];
#ifdef DEV_TRF
#define TRF(slot) do { if (w4 == 0 && ti < 60) { uint32_t c_; asm volatile("mov.u32 %0, %%clock;" : "=r"(c_)::"memory"); if (elect()) g_trace[blockIdx.x * 4096 + 2048 + ti * 32 + wg * 16 + (slot)] = c_; __syncwarp(); } } while (0)
#else
#define TRF(slot)
#endif
#define TRM(slot) do { if ((threadIdx.x & 31) == 0) { long long c_; asm volatile("mov.u64 %0, %%globaltimer;" : "=l"(c_)); g_trace[blockIdx.x * 4096 + 4080 + (slot)] = c_; } } while (0)
#else
#define TRM(slot)
#define TRF(slot)
#endif

__device__ __forceinline__ void wgmma_ss_n256_a0b1(float (&d)[128], uint64_t da, uint64_t db, int sc) {
  asm volatile("{.reg .pred p; setp.ne.b32 p, %130, 0; wgmma.mma_async.sync.aligned.m64n256k16.f32.bf16.bf16 {%0,%1,%2,%3,%4,%5,%6,%7,%8,%9,%10,%11,%12,%13,%14,%15,%16,%17,%18,%19,%20,%21,%22,%23,%24,%25,%26,%27,%28,%29,%30,%31,%32,%33,%34,%35,%36,%37,%38,%39,%40,%41,%42,%43,%44,%45,%46,%47,%48,%49,%50,%51,%52,%53,%54,%55,%56,%57,%58,%59,%60,%61,%62,%63,%64,%65,%66,%67,%68,%69,%70,%71,%72,%73,%74,%75,%76,%77,%78,%79,%80,%81,%82,%83,%84,%85,%86,%87,%88,%89,%90,%91,%92,%93,%94,%95,%96,%97,%98,%99,%100,%101,%102,%103,%104,%105,%106,%107,%108,%109,%110,%111,%112,%113,%114,%115,%116,%117,%118,%119,%120,%121,%122,%123,%124,%125,%126,%127}, %128, %129, p, 1, 1, 0, 1;}"
    : "+f"(d[0]),"+f"(d[1]),"+f"(d[2]),"+f"(d[3]),"+f"(d[4]),"+f"(d[5]),"+f"(d[6]),"+f"(d[7]),"+f"(d[8]),"+f"(d[9]),"+f"(d[10]),"+f"(d[11]),"+f"(d[12]),"+f"(d[13]),"+f"(d[14]),"+f"(d[15]),"+f"(d[16]),"+f"(d[17]),"+f"(d[18]),"+f"(d[19]),"+f"(d[20]),"+f"(d[21]),"+f"(d[22]),"+f"(d[23]),"+f"(d[24]),"+f"(d[25]),"+f"(d[26]),"+f"(d[27]),"+f"(d[28]),"+f"(d[29]),"+f"(d[30]),"+f"(d[31]),"+f"(d[32]),"+f"(d[33]),"+f"(d[34]),"+f"(d[35]),"+f"(d[36]),"+f"(d[37]),"+f"(d[38]),"+f"(d[39]),"+f"(d[40]),"+f"(d[41]),"+f"(d[42]),"+f"(d[43]),"+f"(d[44]),"+f"(d[45]),"+f"(d[46]),"+f"(d[47]),"+f"(d[48]),"+f"(d[49]),"+f"(d[50]),"+f"(d[51]),"+f"(d[52]),"+f"(d[53]),"+f"(d[54]),"+f"(d[55]),"+f"(d[56]),"+f"(d[57]),"+f"(d[58]),"+f"(d[59]),"+f"(d[60]),"+f"(d[61]),"+f"(d[62]),"+f"(d[63]),"+f"(d[64]),"+f"(d[65]),"+f"(d[66]),"+f"(d[67]),"+f"(d[68]),"+f"(d[69]),"+f"(d[70]),"+f"(d[71]),"+f"(d[72]),"+f"(d[73]),"+f"(d[74]),"+f"(d[75]),"+f"(d[76]),"+f"(d[77]),"+f"(d[78]),"+f"(d[79]),"+f"(d[80]),"+f"(d[81]),"+f"(d[82]),"+f"(d[83]),"+f"(d[84]),"+f"(d[85]),"+f"(d[86]),"+f"(d[87]),"+f"(d[88]),"+f"(d[89]),"+f"(d[90]),"+f"(d[91]),"+f"(d[92]),"+f"(d[93]),"+f"(d[94]),"+f"(d[95]),"+f"(d[96]),"+f"(d[97]),"+f"(d[98]),"+f"(d[99]),"+f"(d[100]),"+f"(d[101]),"+f"(d[102]),"+f"(d[103]),"+f"(d[104]),"+f"(d[105]),"+f"(d[106]),"+f"(d[107]),"+f"(d[108]),"+f"(d[109]),"+f"(d[110]),"+f"(d[111]),"+f"(d[112]),"+f"(d[113]),"+f"(d[114]),"+f"(d[115]),"+f"(d[116]),"+f"(d[117]),"+f"(d[118]),"+f"(d[119]),"+f"(d[120]),"+f"(d[121]),"+f"(d[122]),"+f"(d[123]),"+f"(d[124]),"+f"(d[125]),"+f"(d[126]),"+f"(d[127])
    : "l"(da), "l"(db), "r"(sc));
}
__device__ __forceinline__ void wgmma_ss_n192_a0b1(float (&d)[96], uint64_t da, uint64_t db, int sc) {
  asm volatile("{.reg .pred p; setp.ne.b32 p, %98, 0; wgmma.mma_async.sync.aligned.m64n192k16.f32.bf16.bf16 {%0,%1,%2,%3,%4,%5,%6,%7,%8,%9,%10,%11,%12,%13,%14,%15,%16,%17,%18,%19,%20,%21,%22,%23,%24,%25,%26,%27,%28,%29,%30,%31,%32,%33,%34,%35,%36,%37,%38,%39,%40,%41,%42,%43,%44,%45,%46,%47,%48,%49,%50,%51,%52,%53,%54,%55,%56,%57,%58,%59,%60,%61,%62,%63,%64,%65,%66,%67,%68,%69,%70,%71,%72,%73,%74,%75,%76,%77,%78,%79,%80,%81,%82,%83,%84,%85,%86,%87,%88,%89,%90,%91,%92,%93,%94,%95}, %96, %97, p, 1, 1, 0, 1;}"
    : "+f"(d[0]),"+f"(d[1]),"+f"(d[2]),"+f"(d[3]),"+f"(d[4]),"+f"(d[5]),"+f"(d[6]),"+f"(d[7]),"+f"(d[8]),"+f"(d[9]),"+f"(d[10]),"+f"(d[11]),"+f"(d[12]),"+f"(d[13]),"+f"(d[14]),"+f"(d[15]),"+f"(d[16]),"+f"(d[17]),"+f"(d[18]),"+f"(d[19]),"+f"(d[20]),"+f"(d[21]),"+f"(d[22]),"+f"(d[23]),"+f"(d[24]),"+f"(d[25]),"+f"(d[26]),"+f"(d[27]),"+f"(d[28]),"+f"(d[29]),"+f"(d[30]),"+f"(d[31]),"+f"(d[32]),"+f"(d[33]),"+f"(d[34]),"+f"(d[35]),"+f"(d[36]),"+f"(d[37]),"+f"(d[38]),"+f"(d[39]),"+f"(d[40]),"+f"(d[41]),"+f"(d[42]),"+f"(d[43]),"+f"(d[44]),"+f"(d[45]),"+f"(d[46]),"+f"(d[47]),"+f"(d[48]),"+f"(d[49]),"+f"(d[50]),"+f"(d[51]),"+f"(d[52]),"+f"(d[53]),"+f"(d[54]),"+f"(d[55]),"+f"(d[56]),"+f"(d[57]),"+f"(d[58]),"+f"(d[59]),"+f"(d[60]),"+f"(d[61]),"+f"(d[62]),"+f"(d[63]),"+f"(d[64]),"+f"(d[65]),"+f"(d[66]),"+f"(d[67]),"+f"(d[68]),"+f"(d[69]),"+f"(d[70]),"+f"(d[71]),"+f"(d[72]),"+f"(d[73]),"+f"(d[74]),"+f"(d[75]),"+f"(d[76]),"+f"(d[77]),"+f"(d[78]),"+f"(d[79]),"+f"(d[80]),"+f"(d[81]),"+f"(d[82]),"+f"(d[83]),"+f"(d[84]),"+f"(d[85]),"+f"(d[86]),"+f"(d[87]),"+f"(d[88]),"+f"(d[89]),"+f"(d[90]),"+f"(d[91]),"+f"(d[92]),"+f"(d[93]),"+f"(d[94]),"+f"(d[95])
    : "l"(da), "l"(db), "r"(sc));
}
__device__ __forceinline__ void wgmma_rs_n64_b0(float (&d)[32], uint32_t a0, uint32_t a1, uint32_t a2, uint32_t a3, uint64_t db, int sc) {
  asm volatile("{.reg .pred p; setp.ne.b32 p, %37, 0; wgmma.mma_async.sync.aligned.m64n64k16.f32.bf16.bf16 {%0,%1,%2,%3,%4,%5,%6,%7,%8,%9,%10,%11,%12,%13,%14,%15,%16,%17,%18,%19,%20,%21,%22,%23,%24,%25,%26,%27,%28,%29,%30,%31}, {%32,%33,%34,%35}, %36, p, 1, 1, 0;}"
    : "+f"(d[0]),"+f"(d[1]),"+f"(d[2]),"+f"(d[3]),"+f"(d[4]),"+f"(d[5]),"+f"(d[6]),"+f"(d[7]),"+f"(d[8]),"+f"(d[9]),"+f"(d[10]),"+f"(d[11]),"+f"(d[12]),"+f"(d[13]),"+f"(d[14]),"+f"(d[15]),"+f"(d[16]),"+f"(d[17]),"+f"(d[18]),"+f"(d[19]),"+f"(d[20]),"+f"(d[21]),"+f"(d[22]),"+f"(d[23]),"+f"(d[24]),"+f"(d[25]),"+f"(d[26]),"+f"(d[27]),"+f"(d[28]),"+f"(d[29]),"+f"(d[30]),"+f"(d[31])
    : "r"(a0), "r"(a1), "r"(a2), "r"(a3), "l"(db), "r"(sc));
}
__device__ __forceinline__ void wgmma_ss_n128_a0b1(float (&d)[64], uint64_t da, uint64_t db, int sc) {
  asm volatile("{.reg .pred p; setp.ne.b32 p, %66, 0; wgmma.mma_async.sync.aligned.m64n128k16.f32.bf16.bf16 {%0,%1,%2,%3,%4,%5,%6,%7,%8,%9,%10,%11,%12,%13,%14,%15,%16,%17,%18,%19,%20,%21,%22,%23,%24,%25,%26,%27,%28,%29,%30,%31,%32,%33,%34,%35,%36,%37,%38,%39,%40,%41,%42,%43,%44,%45,%46,%47,%48,%49,%50,%51,%52,%53,%54,%55,%56,%57,%58,%59,%60,%61,%62,%63}, %64, %65, p, 1, 1, 0, 1;}"
    : "+f"(d[0]),"+f"(d[1]),"+f"(d[2]),"+f"(d[3]),"+f"(d[4]),"+f"(d[5]),"+f"(d[6]),"+f"(d[7]),"+f"(d[8]),"+f"(d[9]),"+f"(d[10]),"+f"(d[11]),"+f"(d[12]),"+f"(d[13]),"+f"(d[14]),"+f"(d[15]),"+f"(d[16]),"+f"(d[17]),"+f"(d[18]),"+f"(d[19]),"+f"(d[20]),"+f"(d[21]),"+f"(d[22]),"+f"(d[23]),"+f"(d[24]),"+f"(d[25]),"+f"(d[26]),"+f"(d[27]),"+f"(d[28]),"+f"(d[29]),"+f"(d[30]),"+f"(d[31]),"+f"(d[32]),"+f"(d[33]),"+f"(d[34]),"+f"(d[35]),"+f"(d[36]),"+f"(d[37]),"+f"(d[38]),"+f"(d[39]),"+f"(d[40]),"+f"(d[41]),"+f"(d[42]),"+f"(d[43]),"+f"(d[44]),"+f"(d[45]),"+f"(d[46]),"+f"(d[47]),"+f"(d[48]),"+f"(d[49]),"+f"(d[50]),"+f"(d[51]),"+f"(d[52]),"+f"(d[53]),"+f"(d[54]),"+f"(d[55]),"+f"(d[56]),"+f"(d[57]),"+f"(d[58]),"+f"(d[59]),"+f"(d[60]),"+f"(d[61]),"+f"(d[62]),"+f"(d[63])
    : "l"(da), "l"(db), "r"(sc));
}
__device__ __forceinline__ void wgmma_rs_n128_b0(float (&d)[64], uint32_t a0, uint32_t a1, uint32_t a2, uint32_t a3, uint64_t db, int sc) {
  asm volatile("{.reg .pred p; setp.ne.b32 p, %69, 0; wgmma.mma_async.sync.aligned.m64n128k16.f32.bf16.bf16 {%0,%1,%2,%3,%4,%5,%6,%7,%8,%9,%10,%11,%12,%13,%14,%15,%16,%17,%18,%19,%20,%21,%22,%23,%24,%25,%26,%27,%28,%29,%30,%31,%32,%33,%34,%35,%36,%37,%38,%39,%40,%41,%42,%43,%44,%45,%46,%47,%48,%49,%50,%51,%52,%53,%54,%55,%56,%57,%58,%59,%60,%61,%62,%63}, {%64,%65,%66,%67}, %68, p, 1, 1, 0;}"
    : "+f"(d[0]),"+f"(d[1]),"+f"(d[2]),"+f"(d[3]),"+f"(d[4]),"+f"(d[5]),"+f"(d[6]),"+f"(d[7]),"+f"(d[8]),"+f"(d[9]),"+f"(d[10]),"+f"(d[11]),"+f"(d[12]),"+f"(d[13]),"+f"(d[14]),"+f"(d[15]),"+f"(d[16]),"+f"(d[17]),"+f"(d[18]),"+f"(d[19]),"+f"(d[20]),"+f"(d[21]),"+f"(d[22]),"+f"(d[23]),"+f"(d[24]),"+f"(d[25]),"+f"(d[26]),"+f"(d[27]),"+f"(d[28]),"+f"(d[29]),"+f"(d[30]),"+f"(d[31]),"+f"(d[32]),"+f"(d[33]),"+f"(d[34]),"+f"(d[35]),"+f"(d[36]),"+f"(d[37]),"+f"(d[38]),"+f"(d[39]),"+f"(d[40]),"+f"(d[41]),"+f"(d[42]),"+f"(d[43]),"+f"(d[44]),"+f"(d[45]),"+f"(d[46]),"+f"(d[47]),"+f"(d[48]),"+f"(d[49]),"+f"(d[50]),"+f"(d[51]),"+f"(d[52]),"+f"(d[53]),"+f"(d[54]),"+f"(d[55]),"+f"(d[56]),"+f"(d[57]),"+f"(d[58]),"+f"(d[59]),"+f"(d[60]),"+f"(d[61]),"+f"(d[62]),"+f"(d[63])
    : "r"(a0), "r"(a1), "r"(a2), "r"(a3), "l"(db), "r"(sc));
}
__device__ __forceinline__ void wgmma_rs_n128_b1(float (&d)[64], uint32_t a0, uint32_t a1, uint32_t a2, uint32_t a3, uint64_t db, int sc) {
  asm volatile("{.reg .pred p; setp.ne.b32 p, %69, 0; wgmma.mma_async.sync.aligned.m64n128k16.f32.bf16.bf16 {%0,%1,%2,%3,%4,%5,%6,%7,%8,%9,%10,%11,%12,%13,%14,%15,%16,%17,%18,%19,%20,%21,%22,%23,%24,%25,%26,%27,%28,%29,%30,%31,%32,%33,%34,%35,%36,%37,%38,%39,%40,%41,%42,%43,%44,%45,%46,%47,%48,%49,%50,%51,%52,%53,%54,%55,%56,%57,%58,%59,%60,%61,%62,%63}, {%64,%65,%66,%67}, %68, p, 1, 1, 1;}"
    : "+f"(d[0]),"+f"(d[1]),"+f"(d[2]),"+f"(d[3]),"+f"(d[4]),"+f"(d[5]),"+f"(d[6]),"+f"(d[7]),"+f"(d[8]),"+f"(d[9]),"+f"(d[10]),"+f"(d[11]),"+f"(d[12]),"+f"(d[13]),"+f"(d[14]),"+f"(d[15]),"+f"(d[16]),"+f"(d[17]),"+f"(d[18]),"+f"(d[19]),"+f"(d[20]),"+f"(d[21]),"+f"(d[22]),"+f"(d[23]),"+f"(d[24]),"+f"(d[25]),"+f"(d[26]),"+f"(d[27]),"+f"(d[28]),"+f"(d[29]),"+f"(d[30]),"+f"(d[31]),"+f"(d[32]),"+f"(d[33]),"+f"(d[34]),"+f"(d[35]),"+f"(d[36]),"+f"(d[37]),"+f"(d[38]),"+f"(d[39]),"+f"(d[40]),"+f"(d[41]),"+f"(d[42]),"+f"(d[43]),"+f"(d[44]),"+f"(d[45]),"+f"(d[46]),"+f"(d[47]),"+f"(d[48]),"+f"(d[49]),"+f"(d[50]),"+f"(d[51]),"+f"(d[52]),"+f"(d[53]),"+f"(d[54]),"+f"(d[55]),"+f"(d[56]),"+f"(d[57]),"+f"(d[58]),"+f"(d[59]),"+f"(d[60]),"+f"(d[61]),"+f"(d[62]),"+f"(d[63])
    : "r"(a0), "r"(a1), "r"(a2), "r"(a3), "l"(db), "r"(sc));
}
__device__ __forceinline__ void wgmma_rs_n32_b0(float (&d)[16], uint32_t a0, uint32_t a1, uint32_t a2, uint32_t a3, uint64_t db, int sc) {
  asm volatile("{.reg .pred p; setp.ne.b32 p, %21, 0; wgmma.mma_async.sync.aligned.m64n32k16.f32.bf16.bf16 {%0,%1,%2,%3,%4,%5,%6,%7,%8,%9,%10,%11,%12,%13,%14,%15}, {%16,%17,%18,%19}, %20, p, 1, 1, 0;}"
    : "+f"(d[0]),"+f"(d[1]),"+f"(d[2]),"+f"(d[3]),"+f"(d[4]),"+f"(d[5]),"+f"(d[6]),"+f"(d[7]),"+f"(d[8]),"+f"(d[9]),"+f"(d[10]),"+f"(d[11]),"+f"(d[12]),"+f"(d[13]),"+f"(d[14]),"+f"(d[15])
    : "r"(a0), "r"(a1), "r"(a2), "r"(a3), "l"(db), "r"(sc));
}
__device__ __forceinline__ void wgmma_ss_n32_a1b0(float (&d)[16], uint64_t da, uint64_t db, int sc) {
  asm volatile("{.reg .pred p; setp.ne.b32 p, %18, 0; wgmma.mma_async.sync.aligned.m64n32k16.f32.bf16.bf16 {%0,%1,%2,%3,%4,%5,%6,%7,%8,%9,%10,%11,%12,%13,%14,%15}, %16, %17, p, 1, 1, 1, 0;}"
    : "+f"(d[0]),"+f"(d[1]),"+f"(d[2]),"+f"(d[3]),"+f"(d[4]),"+f"(d[5]),"+f"(d[6]),"+f"(d[7]),"+f"(d[8]),"+f"(d[9]),"+f"(d[10]),"+f"(d[11]),"+f"(d[12]),"+f"(d[13]),"+f"(d[14]),"+f"(d[15])
    : "l"(da), "l"(db), "r"(sc));
}
__device__ __forceinline__ void wgmma_ss_n40_a1b0(float (&d)[20], uint64_t da, uint64_t db, int sc) {
  asm volatile("{.reg .pred p; setp.ne.b32 p, %22, 0; wgmma.mma_async.sync.aligned.m64n40k16.f32.bf16.bf16 {%0,%1,%2,%3,%4,%5,%6,%7,%8,%9,%10,%11,%12,%13,%14,%15,%16,%17,%18,%19}, %20, %21, p, 1, 1, 1, 0;}"
    : "+f"(d[0]),"+f"(d[1]),"+f"(d[2]),"+f"(d[3]),"+f"(d[4]),"+f"(d[5]),"+f"(d[6]),"+f"(d[7]),"+f"(d[8]),"+f"(d[9]),"+f"(d[10]),"+f"(d[11]),"+f"(d[12]),"+f"(d[13]),"+f"(d[14]),"+f"(d[15]),"+f"(d[16]),"+f"(d[17]),"+f"(d[18]),"+f"(d[19])
    : "l"(da), "l"(db), "r"(sc));
}
__device__ __forceinline__ void wgmma_ss_n40_a1b1(float (&d)[20], uint64_t da, uint64_t db, int sc) {
  asm volatile("{.reg .pred p; setp.ne.b32 p, %22, 0; wgmma.mma_async.sync.aligned.m64n40k16.f32.bf16.bf16 {%0,%1,%2,%3,%4,%5,%6,%7,%8,%9,%10,%11,%12,%13,%14,%15,%16,%17,%18,%19}, %20, %21, p, 1, 1, 1, 1;}"
    : "+f"(d[0]),"+f"(d[1]),"+f"(d[2]),"+f"(d[3]),"+f"(d[4]),"+f"(d[5]),"+f"(d[6]),"+f"(d[7]),"+f"(d[8]),"+f"(d[9]),"+f"(d[10]),"+f"(d[11]),"+f"(d[12]),"+f"(d[13]),"+f"(d[14]),"+f"(d[15]),"+f"(d[16]),"+f"(d[17]),"+f"(d[18]),"+f"(d[19])
    : "l"(da), "l"(db), "r"(sc));
}
__device__ __forceinline__ void wgmma_rs_n40_b0(float (&d)[20], uint32_t a0, uint32_t a1, uint32_t a2, uint32_t a3, uint64_t db, int sc) {
  asm volatile("{.reg .pred p; setp.ne.b32 p, %25, 0; wgmma.mma_async.sync.aligned.m64n40k16.f32.bf16.bf16 {%0,%1,%2,%3,%4,%5,%6,%7,%8,%9,%10,%11,%12,%13,%14,%15,%16,%17,%18,%19}, {%20,%21,%22,%23}, %24, p, 1, 1, 0;}"
    : "+f"(d[0]),"+f"(d[1]),"+f"(d[2]),"+f"(d[3]),"+f"(d[4]),"+f"(d[5]),"+f"(d[6]),"+f"(d[7]),"+f"(d[8]),"+f"(d[9]),"+f"(d[10]),"+f"(d[11]),"+f"(d[12]),"+f"(d[13]),"+f"(d[14]),"+f"(d[15]),"+f"(d[16]),"+f"(d[17]),"+f"(d[18]),"+f"(d[19])
    : "r"(a0), "r"(a1), "r"(a2), "r"(a3), "l"(db), "r"(sc));
}
__device__ __forceinline__ void wgmma_ssz_n256_a0b1(float (&d)[128], uint64_t da, uint64_t db) {
  asm volatile("{.reg .pred p; setp.ne.b32 p, 0, 0; wgmma.mma_async.sync.aligned.m64n256k16.f32.bf16.bf16 {%0,%1,%2,%3,%4,%5,%6,%7,%8,%9,%10,%11,%12,%13,%14,%15,%16,%17,%18,%19,%20,%21,%22,%23,%24,%25,%26,%27,%28,%29,%30,%31,%32,%33,%34,%35,%36,%37,%38,%39,%40,%41,%42,%43,%44,%45,%46,%47,%48,%49,%50,%51,%52,%53,%54,%55,%56,%57,%58,%59,%60,%61,%62,%63,%64,%65,%66,%67,%68,%69,%70,%71,%72,%73,%74,%75,%76,%77,%78,%79,%80,%81,%82,%83,%84,%85,%86,%87,%88,%89,%90,%91,%92,%93,%94,%95,%96,%97,%98,%99,%100,%101,%102,%103,%104,%105,%106,%107,%108,%109,%110,%111,%112,%113,%114,%115,%116,%117,%118,%119,%120,%121,%122,%123,%124,%125,%126,%127}, %128, %129, p, 1, 1, 0, 1;}"
    : "=f"(d[0]),"=f"(d[1]),"=f"(d[2]),"=f"(d[3]),"=f"(d[4]),"=f"(d[5]),"=f"(d[6]),"=f"(d[7]),"=f"(d[8]),"=f"(d[9]),"=f"(d[10]),"=f"(d[11]),"=f"(d[12]),"=f"(d[13]),"=f"(d[14]),"=f"(d[15]),"=f"(d[16]),"=f"(d[17]),"=f"(d[18]),"=f"(d[19]),"=f"(d[20]),"=f"(d[21]),"=f"(d[22]),"=f"(d[23]),"=f"(d[24]),"=f"(d[25]),"=f"(d[26]),"=f"(d[27]),"=f"(d[28]),"=f"(d[29]),"=f"(d[30]),"=f"(d[31]),"=f"(d[32]),"=f"(d[33]),"=f"(d[34]),"=f"(d[35]),"=f"(d[36]),"=f"(d[37]),"=f"(d[38]),"=f"(d[39]),"=f"(d[40]),"=f"(d[41]),"=f"(d[42]),"=f"(d[43]),"=f"(d[44]),"=f"(d[45]),"=f"(d[46]),"=f"(d[47]),"=f"(d[48]),"=f"(d[49]),"=f"(d[50]),"=f"(d[51]),"=f"(d[52]),"=f"(d[53]),"=f"(d[54]),"=f"(d[55]),"=f"(d[56]),"=f"(d[57]),"=f"(d[58]),"=f"(d[59]),"=f"(d[60]),"=f"(d[61]),"=f"(d[62]),"=f"(d[63]),"=f"(d[64]),"=f"(d[65]),"=f"(d[66]),"=f"(d[67]),"=f"(d[68]),"=f"(d[69]),"=f"(d[70]),"=f"(d[71]),"=f"(d[72]),"=f"(d[73]),"=f"(d[74]),"=f"(d[75]),"=f"(d[76]),"=f"(d[77]),"=f"(d[78]),"=f"(d[79]),"=f"(d[80]),"=f"(d[81]),"=f"(d[82]),"=f"(d[83]),"=f"(d[84]),"=f"(d[85]),"=f"(d[86]),"=f"(d[87]),"=f"(d[88]),"=f"(d[89]),"=f"(d[90]),"=f"(d[91]),"=f"(d[92]),"=f"(d[93]),"=f"(d[94]),"=f"(d[95]),"=f"(d[96]),"=f"(d[97]),"=f"(d[98]),"=f"(d[99]),"=f"(d[100]),"=f"(d[101]),"=f"(d[102]),"=f"(d[103]),"=f"(d[104]),"=f"(d[105]),"=f"(d[106]),"=f"(d[107]),"=f"(d[108]),"=f"(d[109]),"=f"(d[110]),"=f"(d[111]),"=f"(d[112]),"=f"(d[113]),"=f"(d[114]),"=f"(d[115]),"=f"(d[116]),"=f"(d[117]),"=f"(d[118]),"=f"(d[119]),"=f"(d[120]),"=f"(d[121]),"=f"(d[122]),"=f"(d[123]),"=f"(d[124]),"=f"(d[125]),"=f"(d[126]),"=f"(d[127])
    : "l"(da), "l"(db));
}
__device__ __forceinline__ void wgmma_ssz_n128_a0b1(float (&d)[64], uint64_t da, uint64_t db) {
  asm volatile("{.reg .pred p; setp.ne.b32 p, 0, 0; wgmma.mma_async.sync.aligned.m64n128k16.f32.bf16.bf16 {%0,%1,%2,%3,%4,%5,%6,%7,%8,%9,%10,%11,%12,%13,%14,%15,%16,%17,%18,%19,%20,%21,%22,%23,%24,%25,%26,%27,%28,%29,%30,%31,%32,%33,%34,%35,%36,%37,%38,%39,%40,%41,%42,%43,%44,%45,%46,%47,%48,%49,%50,%51,%52,%53,%54,%55,%56,%57,%58,%59,%60,%61,%62,%63}, %64, %65, p, 1, 1, 0, 1;}"
    : "=f"(d[0]),"=f"(d[1]),"=f"(d[2]),"=f"(d[3]),"=f"(d[4]),"=f"(d[5]),"=f"(d[6]),"=f"(d[7]),"=f"(d[8]),"=f"(d[9]),"=f"(d[10]),"=f"(d[11]),"=f"(d[12]),"=f"(d[13]),"=f"(d[14]),"=f"(d[15]),"=f"(d[16]),"=f"(d[17]),"=f"(d[18]),"=f"(d[19]),"=f"(d[20]),"=f"(d[21]),"=f"(d[22]),"=f"(d[23]),"=f"(d[24]),"=f"(d[25]),"=f"(d[26]),"=f"(d[27]),"=f"(d[28]),"=f"(d[29]),"=f"(d[30]),"=f"(d[31]),"=f"(d[32]),"=f"(d[33]),"=f"(d[34]),"=f"(d[35]),"=f"(d[36]),"=f"(d[37]),"=f"(d[38]),"=f"(d[39]),"=f"(d[40]),"=f"(d[41]),"=f"(d[42]),"=f"(d[43]),"=f"(d[44]),"=f"(d[45]),"=f"(d[46]),"=f"(d[47]),"=f"(d[48]),"=f"(d[49]),"=f"(d[50]),"=f"(d[51]),"=f"(d[52]),"=f"(d[53]),"=f"(d[54]),"=f"(d[55]),"=f"(d[56]),"=f"(d[57]),"=f"(d[58]),"=f"(d[59]),"=f"(d[60]),"=f"(d[61]),"=f"(d[62]),"=f"(d[63])
    : "l"(da), "l"(db));
}


__device__ __forceinline__ void wg_fence() { asm volatile("wgmma.fence.sync.aligned;" ::: "memory"); }
__device__ __forceinline__ void wg_commit() { asm volatile("wgmma.commit_group.sync.aligned;" ::: "memory"); }
template <int N> __device__ __forceinline__ void wg_wait() { asm volatile("wgmma.wait_group.sync.aligned %0;" ::"n"(N) : "memory"); }
template <int N> __device__ __forceinline__ void fence_regs(float (&d)[N]) {
#pragma unroll
  for (int i = 0; i < N; i++) asm volatile("" : "+f"(d[i])::"memory");
}
template <int N> __device__ __forceinline__ void fence_regs(uint32_t (&d)[N]) {
#pragma unroll
  for (int i = 0; i < N; i++) asm volatile("" : "+r"(d[i])::"memory");
}
__device__ __forceinline__ uint64_t mk_desc(uint32_t lo, uint32_t hi) {
  uint64_t d;
  asm("mov.b64 %0, {%1,%2};" : "=l"(d) : "r"(lo), "r"(hi));
  return d;
}
constexpr uint32_t DHI_SW128 = (1024u >> 4) | (1u << 30);
__device__ __forceinline__ uint32_t desc_lo(uint32_t addr, uint32_t lbo) { return ((addr & 0x3FFFF) >> 4) | ((lbo >> 4) << 16); }

__device__ __forceinline__ void mbar_init(uint32_t bar, uint32_t cnt) { asm volatile("mbarrier.init.shared::cta.b64 [%0], %1;" ::"r"(bar), "r"(cnt) : "memory"); }
__device__ __forceinline__ uint32_t mbar_try(uint32_t bar, uint32_t par) {
  uint32_t ok;
  asm volatile("{.reg .pred p; mbarrier.try_wait.parity.shared::cta.b64 p, [%1], %2; selp.u32 %0, 1, 0, p;}" : "=r"(ok) : "r"(bar), "r"(par) : "memory");
  return ok;
}
__device__ __noinline__ void mbar_wait_slow(uint32_t bar, uint32_t par) {
  for (int i = 0; i < (1 << 22); i++)
    if (mbar_try(bar, par)) return;
  __trap();
}
__device__ __forceinline__ void mbar_wait(uint32_t bar, uint32_t par) {
  asm volatile(
      "{\n.reg .pred p;\n.reg .u32 c;\n"
      "mbarrier.try_wait.parity.shared::cta.b64 p, [%0], %1;\n"
      "@p bra DONE;\n"
      "mov.u32 c, 0;\n"
      "LOOP:\n"
      "mbarrier.try_wait.parity.shared::cta.b64 p, [%0], %1;\n"
      "@p bra DONE;\n"
      "add.u32 c, c, 1;\n"
      "setp.lt.u32 p, c, 4000000;\n"
      "@p bra LOOP;\n"
      "trap;\n"
      "DONE:\n}" ::"r"(bar), "r"(par) : "memory");
}
__device__ __forceinline__ void mbar_wait2(uint32_t b0, uint32_t p0, uint32_t b1, uint32_t p1) {
  asm volatile(
      "{\n.reg .pred p, q;\n.reg .u32 c;\n"
      "mov.u32 c, 0;\n"
      "LOOP:\n"
      "mbarrier.try_wait.parity.shared::cta.b64 p, [%0], %1;\n"
      "mbarrier.try_wait.parity.shared::cta.b64 q, [%2], %3;\n"
      "and.pred p, p, q;\n"
      "@p bra DONE;\n"
      "add.u32 c, c, 1;\n"
      "setp.lt.u32 p, c, 4000000;\n"
      "@p bra LOOP;\n"
      "trap;\n"
      "DONE:\n}" ::"r"(b0), "r"(p0), "r"(b1), "r"(p1) : "memory");
}
__device__ __forceinline__ void mbar_wait_cl(uint32_t bar, uint32_t par) {
  asm volatile(
      "{\n.reg .pred p;\n.reg .u32 c;\n"
      "mbarrier.try_wait.parity.acquire.cluster.shared::cta.b64 p, [%0], %1;\n"
      "@p bra DONE;\n"
      "mov.u32 c, 0;\n"
      "LOOP:\n"
      "mbarrier.try_wait.parity.acquire.cluster.shared::cta.b64 p, [%0], %1;\n"
      "@p bra DONE;\n"
      "add.u32 c, c, 1;\n"
      "setp.lt.u32 p, c, 4000000;\n"
      "@p bra LOOP;\n"
      "trap;\n"
      "DONE:\n}" ::"r"(bar), "r"(par) : "memory");
}
__device__ __forceinline__ void mbar_arrive(uint32_t bar) { asm volatile("mbarrier.arrive.shared::cta.b64 _, [%0];" ::"r"(bar) : "memory"); }
__device__ __forceinline__ void mbar_arrive_cl(uint32_t bar) { asm volatile("mbarrier.arrive.shared::cluster.b64 _, [%0];" ::"r"(bar) : "memory"); }
__device__ __forceinline__ void mbar_expect(uint32_t bar, uint32_t bytes) { asm volatile("mbarrier.arrive.expect_tx.shared::cta.b64 _, [%0], %1;" ::"r"(bar), "r"(bytes) : "memory"); }
__device__ __forceinline__ void mbar_expect_cl(uint32_t bar, uint32_t bytes) { asm volatile("mbarrier.arrive.expect_tx.shared::cluster.b64 _, [%0], %1;" ::"r"(bar), "r"(bytes) : "memory"); }
__device__ __forceinline__ uint32_t mapa(uint32_t addr, uint32_t rank) {
  uint32_t r;
  asm("mapa.shared::cluster.u32 %0, %1, %2;" : "=r"(r) : "r"(addr), "r"(rank));
  return r;
}
__device__ __forceinline__ void st_async32(uint32_t addr, uint32_t v, uint32_t bar) {
  asm volatile("st.async.shared::cluster.mbarrier::complete_tx::bytes.b32 [%0], %1, [%2];" ::"r"(addr), "r"(v), "r"(bar) : "memory");
}
__device__ __forceinline__ void st_async64(uint32_t addr, uint32_t a, uint32_t b, uint32_t bar) {
  asm volatile("st.async.shared::cluster.mbarrier::complete_tx::bytes.v2.b32 [%0], {%1,%2}, [%3];" ::"r"(addr), "r"(a), "r"(b), "r"(bar) : "memory");
}
__device__ __forceinline__ void st_async128(uint32_t addr, uint32_t a, uint32_t b, uint32_t c, uint32_t d, uint32_t bar) {
  asm volatile("st.async.shared::cluster.mbarrier::complete_tx::bytes.v4.b32 [%0], {%1,%2,%3,%4}, [%5];" ::"r"(addr), "r"(a), "r"(b), "r"(c), "r"(d), "r"(bar) : "memory");
}
__device__ __forceinline__ void bar_sync(int id, int n) { asm volatile("bar.sync %0, %1;" ::"r"(id), "r"(n) : "memory"); }
__device__ __forceinline__ void bar_arrive(int id, int n) { asm volatile("bar.arrive %0, %1;" ::"r"(id), "r"(n) : "memory"); }
__device__ __forceinline__ void cluster_sync() { asm volatile("barrier.cluster.arrive.aligned;\nbarrier.cluster.wait.aligned;" ::: "memory"); }
__device__ __forceinline__ bool elect() {
  uint32_t p;
  asm volatile("{.reg .pred q; elect.sync _|q, 0xffffffff; selp.u32 %0, 1, 0, q;}" : "=r"(p));
  return p != 0;
}
__device__ __forceinline__ void fence_async_smem() { asm volatile("fence.proxy.async.shared::cta;" ::: "memory"); }
__device__ __forceinline__ void fence_async_all() { asm volatile("fence.proxy.async;" ::: "memory"); }
__device__ __forceinline__ void tma2d(uint32_t dst, const CUtensorMap* m, int c0, int c1, uint32_t bar) {
  asm volatile("cp.async.bulk.tensor.2d.shared::cluster.global.mbarrier::complete_tx::bytes [%0], [%1, {%2,%3}], [%4];" ::"r"(dst), "l"(m), "r"(c0), "r"(c1), "r"(bar) : "memory");
}
__device__ __forceinline__ void tma2d_mc(uint32_t dst, const CUtensorMap* m, int c0, int c1, uint32_t bar, uint16_t mask) {
  asm volatile("cp.async.bulk.tensor.2d.shared::cluster.global.mbarrier::complete_tx::bytes.multicast::cluster [%0], [%1, {%2,%3}], [%4], %5;" ::"r"(dst), "l"(m), "r"(c0), "r"(c1), "r"(bar), "h"(mask) : "memory");
}
__device__ __forceinline__ void tma3d(uint32_t dst, const CUtensorMap* m, int c0, int c1, int c2, uint32_t bar) {
  asm volatile("cp.async.bulk.tensor.3d.shared::cluster.global.mbarrier::complete_tx::bytes [%0], [%1, {%2,%3,%4}], [%5];" ::"r"(dst), "l"(m), "r"(c0), "r"(c1), "r"(c2), "r"(bar) : "memory");
}
__device__ __forceinline__ void tma3d_mc(uint32_t dst, const CUtensorMap* m, int c0, int c1, int c2, uint32_t bar, uint16_t mask) {
  asm volatile("cp.async.bulk.tensor.3d.shared::cluster.global.mbarrier::complete_tx::bytes.multicast::cluster [%0], [%1, {%2,%3,%4}], [%5], %6;" ::"r"(dst), "l"(m), "r"(c0), "r"(c1), "r"(c2), "r"(bar), "h"(mask) : "memory");
}
__device__ __forceinline__ uint32_t ld_acquire(const unsigned* p) {
  uint32_t v;
  asm volatile("ld.acquire.gpu.global.u32 %0, [%1];" : "=r"(v) : "l"(p) : "memory");
  return v;
}
__device__ __forceinline__ uint32_t pack_bf16(float lo, float hi) {
  uint32_t r;
  asm("cvt.rn.bf16x2.f32 %0, %1, %2;" : "=r"(r) : "f"(hi), "f"(lo));
  return r;
}
__device__ __forceinline__ float ex2(float x) {
  float y;
  asm("ex2.approx.ftz.f32 %0, %1;" : "=f"(y) : "f"(x));
  return y;
}
__device__ __forceinline__ float rcp(float x) {
  float y;
  asm("rcp.approx.ftz.f32 %0, %1;" : "=f"(y) : "f"(x));
  return y;
}
__device__ __forceinline__ void stg128(void* p, uint32_t a, uint32_t b, uint32_t c, uint32_t d) {
  asm volatile("st.global.v4.b32 [%0], {%1,%2,%3,%4};" ::"l"(p), "r"(a), "r"(b), "r"(c), "r"(d) : "memory");
}
__device__ __forceinline__ void sts128(uint32_t a, uint32_t x, uint32_t y, uint32_t z, uint32_t w) {
  asm volatile("st.shared.v4.b32 [%0], {%1,%2,%3,%4};" ::"r"(a), "r"(x), "r"(y), "r"(z), "r"(w) : "memory");
}
__device__ __forceinline__ void stsm4(uint32_t a, uint32_t r0, uint32_t r1, uint32_t r2, uint32_t r3) {
  asm volatile("stmatrix.sync.aligned.m8n8.x4.shared.b16 [%0], {%1,%2,%3,%4};" ::"r"(a), "r"(r0), "r"(r1), "r"(r2), "r"(r3) : "memory");
}
__device__ __forceinline__ void arrive_elect(uint32_t bar) {
  asm volatile("{.reg .pred q; elect.sync _|q, 0xffffffff; @q mbarrier.arrive.shared::cta.b64 _, [%0];}" ::"r"(bar) : "memory");
}
__device__ __forceinline__ void sched_fence(uint32_t v) { asm volatile("{.reg .pred p; setp.eq.u32 p, %0, 0; @p trap;}" ::"r"(v) : "memory"); }
template <int V> struct IC { static constexpr int value = V; };
template <int A, int B, class F> __device__ __forceinline__ void static_for(F&& f) {
  if constexpr (A < B) {
    f(IC<A>());
    static_for<A + 1, B>(f);
  }
}
__device__ __forceinline__ uint32_t lds32(uint32_t a) {
  uint32_t v;
  asm volatile("ld.shared.b32 %0, [%1];" : "=r"(v) : "r"(a) : "memory");
  return v;
}

constexpr int MAXTASK = 256 + 256 + 200;
constexpr int T_KV = 0, T_FA = 1, T_OA = 2, T_OB = 3, T_MA = 4, T_MB = 5;
constexpr uint32_t TASK_END = 0xFFFF;
constexpr int NCL = 34;
struct MainParams {
  CUtensorMap ckv, wuk, wuv, ax, wq, scr, woa, wob, scr_st, out_st, woa2, wob2;
  uint32_t ntask;
  uint16_t tasks[MAXTASK];
};

constexpr int M_GR = 16384, M_NG = 12;
constexpr int M_STG = M_GR * M_NG;
constexpr int M_BAR = M_STG + 32768;
constexpr int M_FULL = M_BAR, M_EMPTY = M_BAR + 64, M_TFULL = M_BAR + 128, M_TEMPTY = M_BAR + 160, M_EPI = M_BAR + 192, M_SFREE = M_BAR + 224, M_GO = M_BAR + 240,
              M_TSLOT = M_BAR + 256;
constexpr int M_SMEM = M_BAR + 512 + 1024;
constexpr int OX_TARGET = 64;

#ifndef PF_ON
#define PF_ON 0
#endif
#ifndef ST_ROWS
#define ST_ROWS 16
#endif
#ifndef ST_DEPTH
#define ST_DEPTH 1
#endif
#ifndef KV_SKEW
#define KV_SKEW 7
#endif
#ifndef FM_NJ
#define FM_NJ 2
#endif
#ifndef Q_SKEW
#define Q_SKEW 6
#endif
struct Ring {
  uint32_t e, g;
  __device__ __forceinline__ uint32_t take(int z) {
    if (g + z > M_NG) g = 0;
    const uint32_t r = g;
    g += z;
    return r;
  }
  __device__ __forceinline__ uint32_t bar() const { return (e & 7) * 8; }
  __device__ __forceinline__ uint32_t par() const { return (e >> 3) & 1; }
};
__device__ __forceinline__ int task_entries(int type, int p) { return type == T_KV ? 9 : type == T_FA ? 9 + 2 * (2 * p + 2) : 65; }
__device__ __forceinline__ int entry_size(int type, int it) { return type == T_FA || (type == T_KV && it == 8) || type >= T_MA ? 2 : 3; }

__device__ __forceinline__ void need_flag(uint32_t& v, int bit, const unsigned* flag, unsigned target) {
  for (int it = 0; !((__ballot_sync(0xffffffffu, v >= target) >> bit) & 1); it++) {
    if (it > (1 << 21)) __trap();
    if (it) __nanosleep(40);
    v = ld_acquire(flag);
  }
}

constexpr float SM_C = 0.08838834764831845f * 1.4426950408889634f;
template <int NJ> __device__ __forceinline__ void softmax_max(const float (&s)[64], float& m0, float& m1, float& a0, float& a1, float& c0, float& c1) {
  float x0 = fmaxf(s[0], s[4]), y0 = fmaxf(s[1], s[5]), x1 = fmaxf(s[2], s[6]), y1 = fmaxf(s[3], s[7]);
#pragma unroll
  for (int j = 2; j < NJ; j++) {
    x0 = fmaxf(x0, s[4 * j]);
    y0 = fmaxf(y0, s[4 * j + 1]);
    x1 = fmaxf(x1, s[4 * j + 2]);
    y1 = fmaxf(y1, s[4 * j + 3]);
  }
  x0 = fmaxf(x0, y0);
  x1 = fmaxf(x1, y1);
  x0 = fmaxf(x0, __shfl_xor_sync(0xffffffffu, x0, 1));
  x1 = fmaxf(x1, __shfl_xor_sync(0xffffffffu, x1, 1));
  x0 = fmaxf(x0, __shfl_xor_sync(0xffffffffu, x0, 2));
  x1 = fmaxf(x1, __shfl_xor_sync(0xffffffffu, x1, 2));
  const float n0 = fmaxf(m0, x0), n1 = fmaxf(m1, x1);
  a0 = ex2((m0 - n0) * SM_C);
  a1 = ex2((m1 - n1) * SM_C);
  m0 = n0;
  m1 = n1;
  c0 = -n0 * SM_C;
  c1 = -n1 * SM_C;
}
template <int J0, int J1> __device__ __forceinline__ void softmax_exp(const float (&s)[64], uint32_t (&p)[32], float c0, float c1, float (&t)[4]) {
#pragma unroll
  for (int j = J0; j < J1; j++) {
    const float e0 = ex2(fmaf(s[4 * j], SM_C, c0)), e1 = ex2(fmaf(s[4 * j + 1], SM_C, c0));
    const float e2 = ex2(fmaf(s[4 * j + 2], SM_C, c1)), e3 = ex2(fmaf(s[4 * j + 3], SM_C, c1));
    p[2 * j] = pack_bf16(e0, e1);
    p[2 * j + 1] = pack_bf16(e2, e3);
    if (j == 0) { t[0] = e0; t[1] = e1; t[2] = e2; t[3] = e3; }
    else { t[0] += e0; t[1] += e1; t[2] += e2; t[3] += e3; }
  }
}
template <int I0, int I1> __device__ __forceinline__ void fence_part(uint32_t (&d)[32]) {
#pragma unroll
  for (int i = I0; i < I1; i++) asm volatile("" : "+r"(d[i])::"memory");
}
template <int J0, int J1, int N> __device__ __forceinline__ void stage_tile(const float (&d)[N], uint32_t a, float f0, float f1) {
#pragma unroll
  for (int j = J0; j < J1; j += 2)
    stsm4((a ^ (((j - J0) & 7) << 4)) + ((j - J0) >> 3) * 8192, pack_bf16(d[4 * j] * f0, d[4 * j + 1] * f0), pack_bf16(d[4 * j + 2] * f1, d[4 * j + 3] * f1),
          pack_bf16(d[4 * j + 4] * f0, d[4 * j + 5] * f0), pack_bf16(d[4 * j + 6] * f1, d[4 * j + 7] * f1));
}
template <int J0, int J1> __device__ __forceinline__ void causal_mask(float (&s)[64], int lim0) {
#pragma unroll
  for (int j = J0; j < J1; j++) {
    if (8 * j > lim0) s[4 * j] = -INFINITY;
    if (8 * j + 1 > lim0) s[4 * j + 1] = -INFINITY;
    if (8 * j > lim0 + 8) s[4 * j + 2] = -INFINITY;
    if (8 * j + 1 > lim0 + 8) s[4 * j + 3] = -INFINITY;
  }
}

__global__ void __cluster_dims__(2, 1, 1) __launch_bounds__(384, 1) main_kernel(const __grid_constant__ MainParams P) {
  extern __shared__ uint8_t smem_raw[];
  const uint32_t sb = ((uint32_t)__cvta_generic_to_shared(smem_raw) + 1023u) & ~1023u;
  const int warp = __shfl_sync(0xffffffffu, threadIdx.x >> 5, 0), lane = threadIdx.x & 31;
  uint32_t rank;
  asm("mov.u32 %0, %%cluster_ctarank;" : "=r"(rank));
  rank = __shfl_sync(0xffffffffu, rank, 0);
#ifdef DEV_TRACE
  if (threadIdx.x == 0) { long long c; asm volatile("mov.u64 %0, %%globaltimer;" : "=l"(c)); g_trace[blockIdx.x * 4096 + 4090] = c; }
#endif
  const uint32_t cluster = blockIdx.x >> 1;
  static_assert(M_EMPTY == M_FULL + 64 && M_TFULL == M_FULL + 128 && M_TEMPTY == M_FULL + 160 && M_EPI == M_FULL + 192 && M_SFREE == M_FULL + 224, "barriers");
  if (warp == 8 && elect()) {
#pragma unroll 1
    for (int i = 0; i < 4; i++) {
      const uint32_t st = sb + i * 3 * M_GR, fb = sb + M_FULL + 8 * i;
      mbar_init(fb, 1);
      mbar_expect(fb, 49152);
      tma2d(st, &P.ckv, i * 64, (cluster & 7) * 256 + rank * 128, fb);
      tma3d(st + 16384, &P.wuk, 0, i * 64, (cluster >> 3) * 2, fb);
      tma3d(st + 32768, &P.wuv, 0, i * 64, (cluster >> 3) * 2, fb);
    }
    asm volatile("fence.mbarrier_init.release.cluster;" ::: "memory");
  }
  const uint32_t task0 = cluster;
  if (warp >= 1 && warp < 8 && elect()) {
    const uint32_t b = sb + M_FULL + 32 * warp, cnt = (warp & 14) == 2 ? 16 : warp == 5 ? 22 : warp == 6 ? 4 : 1;
#pragma unroll
    for (int i = 0; i < 4; i++) mbar_init(b + 8 * i, cnt);
    asm volatile("fence.mbarrier_init.release.cluster;" ::: "memory");
  }
  __syncwarp();
  if (warp == 8) TRM(5);
  asm volatile("barrier.cluster.arrive.relaxed.aligned;" ::: "memory");
  auto started = [&]() { asm volatile("barrier.cluster.wait.aligned;" ::: "memory"); };
  const uint32_t tempty0 = mapa(sb + M_TEMPTY, 0);
  auto read_task = [&](int ti) -> uint32_t {
    if (ti == 0) return task0;
    mbar_wait(sb + M_TFULL + 8 * ((ti - 1) & 3), ((ti - 1) >> 2) & 1);
    return __shfl_sync(0xffffffffu, lds32(sb + M_TSLOT + 4 * ((ti - 1) & 3)), 0);
  };
  auto free_task = [&](int ti) {
    if (ti > 0 && lane == 0) mbar_arrive_cl(tempty0 + 8 * ((ti - 1) & 3));
  };

  if (warp >= 8) {
    asm volatile("setmaxnreg.dec.sync.aligned.u32 40;");
    if (warp == 8) {
      if (lane >= 3 && lane < 12) asm volatile("prefetch.tensormap [%0];" ::"l"(&P.ckv + lane) : "memory");
      __syncwarp();
      started();
      TRM(4);
      Ring r{0, 0};
      uint32_t lin = 0;
      uint32_t mypos = 0, mypar = 2;
      const uint32_t myempty = sb + M_EMPTY + 8 * (lane & 7);
      auto alloc = [&](int z, uint32_t& fb) -> uint32_t {
        if (r.g + z > M_NG) lin += M_NG - r.g;
        const uint32_t st = sb + r.take(z) * M_GR;
        const uint32_t need = mypar < 2 && lin + z - mypos > M_NG;
        for (int it = 0;; it++) {
          uint32_t ok;
          asm volatile("{.reg .pred p, q; setp.eq.u32 q, %3, 0; mov.pred p, q; @!q mbarrier.try_wait.parity.shared::cta.b64 p, [%1], %2; selp.u32 %0, 1, 0, p;}"
                       : "=r"(ok) : "r"(myempty), "r"(mypar), "r"(need) : "memory");
          if (__all_sync(0xffffffffu, ok)) break;
          if (it > 4000000) __trap();
        }
        mypar = need ? 2 : mypar;
        if (lane == (r.e & 7)) { mypos = lin; mypar = r.par(); }
        lin += z;
        fb = sb + M_FULL + r.bar();
        r.e++;
        return st;
      };
      auto go = [&]() { if (rank == 0) arrive_elect(sb + M_GO); };
      for (int ti = 0;; ti++) {
        const uint32_t task = read_task(ti);
        free_task(ti);
        if (task == TASK_END) break;
        const int type = task >> 12, nn = (task >> 8) & 15, h = (task >> 3) & 31, p = task & 7;
        uint32_t fb, fv = 0;
        if (type == T_KV) {
          const CUtensorMap* w = rank ? &P.wuv : &P.wuk;
          const int row = p * 256 + rank * 128;
#pragma unroll 1
          for (int k = 0; k < 512; k += 64) {
            const uint32_t st = alloc(3, fb);
            if ((ti > 0 || k >= 256) && elect()) {
              mbar_expect(fb, 49152);
              tma2d(st, &P.ckv, k, row, fb);
              tma3d_mc(st + 16384 + rank * 16384, w, 0, k, h * 2, fb, 3);
            }
            if (k == 384) go();
            if (PF_ON && ti == 0 && h < 4 && k == 192 && elect()) {
              asm volatile("cp.async.bulk.prefetch.tensor.3d.L2.global [%0, {0,%1,%2}];" ::"l"(w), "r"(p * 64), "r"((h + 4) * 2) : "memory");
              if (h == 0) asm volatile("cp.async.bulk.prefetch.tensor.3d.L2.global [%0, {0,%1,%2}];" ::"l"(w), "r"(p * 64), "r"(16) : "memory");
            }
            if (PF_ON && ti == 1 && h < 8 && k >= 192 && elect()) {
              const int c = (k - 192) / 32 + rank;
              if (c < 9) asm volatile("cp.async.bulk.prefetch.tensor.2d.L2.global [%0, {%1,%2}];" ::"l"(&P.ax), "r"(c * 64), "r"(p * 256 + (h & 3) * 64) : "memory");
              if (k == 192) asm volatile("cp.async.bulk.prefetch.tensor.2d.L2.global [%0, {%1,%2}];" ::"l"(&P.wq), "r"((h & 3) * 128 + rank * 64), "r"(p * 64) : "memory");
            }
            __syncwarp();
          }
          alloc(2, fb);
          arrive_elect(fb);
        } else if (type == T_FA) {
          const unsigned* flag = g_sync + SY_KV + h * 8 + (lane & 7);
          asm volatile("ld.relaxed.gpu.global.u32 %0, [%1];" : "=r"(fv) : "l"(flag) : "memory");
          const int r0 = p * 256 + rank * 64, r1 = p * 256 + 192 - rank * 64, col = h * 128 + rank * 64;
#pragma unroll 1
          for (int k = 0; k < 576; k += 64) {
            const uint32_t st = alloc(2, fb);
            if (elect()) {
              mbar_expect(fb, 32768);
              tma2d(st, &P.ax, k, r0, fb);
              tma2d(st + 8192, &P.ax, k, r1, fb);
              tma2d_mc(st + 16384 + rank * 8192, &P.wq, col, k, fb, 3);
            }
          }
          auto kv = [&](int row) {
            const uint32_t st = alloc(2, fb);
            if (elect()) {
              mbar_expect(fb, 32768);
              tma2d_mc(st + rank * 16384, &P.scr, col, row, fb, 3);
            }
          };
          need_flag(fv, p, flag, 4);
          kv((2 * p + 1) * 128);
#pragma unroll 1
          for (int j = 2 * p; j >= 0; j--) {
            need_flag(fv, j >> 1, flag, 4);
            if (j == 0) go();
            kv(j * 128);
            kv(SEQ + (j + 1) * 128);
          }
          kv(SEQ);
        } else {
          const int part = type & 1;
          const unsigned* flag = g_sync + (part ? SY_OX + 2 * p + 1 : SY_CTX + p * 32 + lane);
          const unsigned target = part ? OX_TARGET : 4;
          const int row = (2 + part) * SEQ + p * 256 + rank * 128;
          const int nch = type >= T_MA ? 2 : 3;
          const CUtensorMap* w = &P.woa + part + (type >= T_MA ? 4 : 0);
#pragma unroll 1
          for (int k = 0; k < HDALL; k += 64) {
            need_flag(fv, k >> 7, flag, target);
            const uint32_t st = alloc(nch, fb);
            if (elect()) {
              mbar_expect(fb, 16384 + nch * 8192);
              tma2d(st, &P.scr, k, row, fb);
              tma3d_mc(st + 16384 + rank * nch * 4096, w, 0, k + rank * 32, nn * nch, fb, 3);
            }
            if (k == HDALL - 192) go();
          }
          alloc(nch, fb);
          arrive_elect(fb);
        }
      }
    } else if (warp == 9) {
      started();
      TRM(0);
      if (rank == 0) {
        for (int ti = 0;; ti++) {
          uint32_t q = 0;
          mbar_wait(sb + M_GO, ti & 1);
          if (lane == 0) q = atomicAdd(&g_sync[SY_Q], 1u);
          q = __shfl_sync(0xffffffffu, q, 0);
          if (ti == 0 && q < 100000) TRM(1);
          const uint32_t t = q < P.ntask ? (uint32_t)P.tasks[q] : TASK_END;
          if (ti == 0 && t < 100000) TRM(2);
          mbar_wait(sb + M_TEMPTY + 8 * (ti & 3), ((ti >> 2) & 1) ^ 1);
          if (lane < 2) {
            const uint32_t b = mapa(sb + M_TFULL + 8 * (ti & 3), lane);
            mbar_expect_cl(b, 4);
            st_async32(mapa(sb + M_TSLOT + 4 * (ti & 3), lane), t, b);
          }
          __syncwarp();
          if (t == TASK_END) break;
        }
      }
    } else {
      const int wg = warp - 10;
      const uint32_t emptyx = mapa(sb + M_EMPTY, lane & 1);
      Ring r{0, 0};
      int lead = wg;
      started();
      for (int ti = 0;; ti++) {
        const int sl = ti & 1;
        const uint32_t task = read_task(ti);
        const int type = task >> 12, nn = (task >> 8) & 15, h = (task >> 3) & 31, p = task & 7;
        if (task != TASK_END) {
          const int nit = task_entries(type, p);
          uint32_t st = 0;
          for (int it = 0; it < nit; it++) st = r.take(entry_size(type, it));
          r.e += nit - 1;
          int row = p * 256 + rank * 128 + wg * 64;
          if (type == T_FA) {
            row = 2 * SEQ + p * 256 + (lead ? 3 - (int)rank : (int)rank) * 64;
            lead ^= 1;
          }
          mbar_wait(sb + M_EPI + 8 * (sl * 2 + wg), (ti >> 1) & 1);
          auto store = [&](const CUtensorMap* m, uint32_t src, int r0, int c0, int n32, bool fast = true) {
            if (lane == 0) {
#pragma unroll 1
              for (int i = 0; i < n32 * (32 / ST_ROWS); i++) {
                asm volatile("cp.async.bulk.tensor.2d.global.shared::cta.bulk_group [%0, {%1,%2}], [%3];" ::"l"(m), "r"((c0 + i / (64 / ST_ROWS)) * 64), "r"(r0 + i % (64 / ST_ROWS) * ST_ROWS), "r"(src + i * ST_ROWS * 128) : "memory");
                asm volatile("cp.async.bulk.commit_group;" ::: "memory");
                if (fast) asm volatile("cp.async.bulk.wait_group.read %0;" ::"n"(ST_DEPTH) : "memory");
                else asm volatile("cp.async.bulk.wait_group.read 0;" ::: "memory");
              }
              asm volatile("cp.async.bulk.wait_group.read 0;" ::: "memory");
            }
            __syncwarp();
          };
          if (type != T_FA) {
            if (type == T_KV) store(&P.scr_st, sb + st * M_GR + wg * 16384, SEQ + row, h * 2, 4);
            else if (type < T_MA) store(&P.out_st, sb + st * M_GR + wg * 24576, row, (type & 1) * 9 + nn * 3, 6);
            else store(&P.out_st, sb + st * M_GR + wg * 16384, row, (type & 1) * 9 + nn * 2, 4);
            if (lane < 2) asm volatile("mbarrier.arrive.shared::cluster.b64 _, [%0], 4;" ::"r"(emptyx + r.bar()) : "memory");
          }
          r.e++;
          if (type <= T_FA) store(&P.scr_st, sb + M_STG + wg * 16384, row, h * 2, 4, false);
          if (lane == 0) mbar_arrive(sb + M_SFREE + 8 * wg);
          if (lane == 0) {
            asm volatile("cp.async.bulk.wait_group 0;" ::: "memory");
            if (type <= T_FA) {
              __threadfence();
              atomicAdd(type == T_KV ? &g_sync[SY_KV + h * 8 + p] : &g_sync[SY_CTX + p * 32 + h], 1u);
            }
          }
        }
        __syncwarp();
        free_task(ti);
        if (task == TASK_END) break;
      }
    }
    __syncwarp();
    cluster_sync();
    if (threadIdx.x == 288) TRE(256 + blockIdx.x);
    if (warp == 9) {
      uint32_t old = 0;
      if (lane == 0) {
        __threadfence();
        old = atomicAdd(&g_sync[SY_EXIT], 1u);
        __threadfence();
      }
      if (__shfl_sync(0xffffffffu, old, 0) == gridDim.x - 1) {
        asm volatile("griddepcontrol.wait;" ::: "memory");
        for (int i = lane; i < SY_N; i += 32) g_sync[i] = 0;
      }
    }
  } else {
    asm volatile("setmaxnreg.inc.sync.aligned.u32 232;");
    if (warp == 0) TRM(3);
    const int wg = warp >> 2, w4 = warp & 3, g = lane >> 2, t4 = lane & 3;
    const uint32_t emptyx = mapa(sb + M_EMPTY, lane & 1);
    Ring r{0, 0};
    int lead = wg;
    auto release = [&](uint32_t bar) {
      if (lane < 2) mbar_arrive_cl(emptyx + bar);
    };
    auto acquire = [&](int z, uint32_t& bar) -> uint32_t {
      bar = r.bar();
      mbar_wait(sb + M_FULL + bar, r.par());
      r.e++;
      return sb + r.take(z) * M_GR;
    };
    const uint32_t sa = (w4 * 16 + ((lane >> 3) & 1) * 8 + (lane & 7)) * 128 + (((lane >> 4) ^ (lane & 7)) << 4);
    uint32_t ntask = task0;
    started();
    for (int ti = 0;; ti++) {
      const int sl = ti & 1;
      const uint32_t task = ntask;
      if (task == TASK_END) break;
      auto next_task = [&]() { ntask = read_task(ti + 1); free_task(ti + 1); };
      const int type = task >> 12, p = task & 7;
#ifdef DEV_TRACE
      if (w4 == 0 && lane == 0 && ti < 250) { long long c; asm volatile("mov.u64 %0, %%globaltimer;" : "=l"(c)); g_trace[blockIdx.x * 4096 + ti * 8 + wg * 4] = c; g_trace[blockIdx.x * 4096 + ti * 8 + wg * 4 + 2] = task; g_trace[blockIdx.x * 4096 + ti * 8 + wg * 4 + 3] = clock64(); }
#endif
      if (type == T_KV) {
        float acc[128];
        uint32_t prev;
        {
          const uint32_t st = acquire(3, prev);
          if (ti == 0 && warp == 0) TRM(6);
          const uint32_t a = desc_lo(st + wg * 8192, 16), b = desc_lo(st + 16384, 8192);
          wg_fence();
          wgmma_ssz_n256_a0b1(acc, mk_desc(a, DHI_SW128), mk_desc(b, DHI_SW128));
#pragma unroll
          for (int kk = 1; kk < 4; kk++) wgmma_ss_n256_a0b1(acc, mk_desc(a + kk * 2, DHI_SW128), mk_desc(b + kk * 128, DHI_SW128), 1);
          wg_commit();
        }
#pragma unroll 1
        for (int kb = 1; kb < 8; kb++) {
          uint32_t bar;
          const uint32_t st = acquire(3, bar);
          const uint32_t a = desc_lo(st + wg * 8192, 16), b = desc_lo(st + 16384, 8192);
          if (KV_SKEW < 8 && kb == KV_SKEW && !lead) {
            wg_wait<0>();
            release(prev);
            bar_sync(5, 256);
          }
          wg_fence();
#pragma unroll
          for (int kk = 0; kk < 4; kk++) wgmma_ss_n256_a0b1(acc, mk_desc(a + kk * 2, DHI_SW128), mk_desc(b + kk * 128, DHI_SW128), 1);
          wg_commit();
          if (KV_SKEW < 8 && kb == 7 && lead) bar_arrive(5, 256);
          if (KV_SKEW < 8 && kb == KV_SKEW && !lead) { prev = bar; continue; }
          wg_wait<1>();
          release(prev);
          prev = bar;
        }
        if (ti == 0 && warp == 0) TRM(7);
        next_task();
        uint32_t bar;
        const uint32_t st = acquire(2, bar);
        mbar_wait(sb + M_SFREE + 8 * wg, (ti & 1) ^ 1);
        wg_wait<0>();
        release(prev);
        fence_regs(acc);
        stage_tile<16, 32>(acc, st + wg * 16384 + sa, 1.f, 1.f);
        stage_tile<0, 16>(acc, sb + M_STG + wg * 16384 + sa, 1.f, 1.f);
        fence_async_smem();
        __syncwarp();
        arrive_elect(sb + M_EPI + 8 * (sl * 2 + wg));
      } else if (type == T_FA) {
        const int lng = lead;
        lead ^= 1;
        const int grp = lng ? 3 - (int)rank : (int)rank;
        const int n = 2 * p + 1 + lng;
        float s[64], o[64];
        uint32_t pr[32], q[32];
        TRF(0);
        {
          uint32_t prev;
          {
            const uint32_t st = acquire(2, prev);
            const uint32_t a = desc_lo(st + lng * 8192, 16), b = desc_lo(st + 16384, 8192);
            wg_fence();
            wgmma_ssz_n128_a0b1(s, mk_desc(a, DHI_SW128), mk_desc(b, DHI_SW128));
#pragma unroll
            for (int kk = 1; kk < 4; kk++) wgmma_ss_n128_a0b1(s, mk_desc(a + kk * 2, DHI_SW128), mk_desc(b + kk * 128, DHI_SW128), 1);
            wg_commit();
          }
#pragma unroll 1
          for (int kb = 1; kb < 9; kb++) {
            uint32_t bar;
            if (kb == 1) TRF(8);
            if (kb == 5) TRF(9);
            const uint32_t st = acquire(2, bar);
            const uint32_t a = desc_lo(st + lng * 8192, 16), b = desc_lo(st + 16384, 8192);
            const bool hold = kb == Q_SKEW && !lng;
            if (hold) {
              wg_wait<0>();
              release(prev);
              bar_sync(5, 256);
            }
            wg_fence();
#pragma unroll
            for (int kk = 0; kk < 4; kk++) wgmma_ss_n128_a0b1(s, mk_desc(a + kk * 2, DHI_SW128), mk_desc(b + kk * 128, DHI_SW128), 1);
            wg_commit();
            if (Q_SKEW < 9 && kb == 8 && lng) bar_arrive(5, 256);
            if (hold) { prev = bar; continue; }
            wg_wait<1>();
            release(prev);
            prev = bar;
          }
#pragma unroll
          for (int i = 0; i < 64; i++) o[i] = 0.f;
          wg_wait<0>();
          release(prev);
          fence_regs(s);
#pragma unroll
          for (int i = 0; i < 32; i++) q[i] = pack_bf16(s[2 * i], s[2 * i + 1]);
        }
        TRF(1);
        const int lim0 = (grp & 1) * 64 + w4 * 16 + g - 2 * t4;
        float m0 = -INFINITY, m1 = -INFINITY, l0 = 0.f, l1 = 0.f;
        auto issue_s = [&](uint32_t st) {
          const uint32_t b = desc_lo(st, 16);
#pragma unroll
          for (int kk = 0; kk < 8; kk++) wgmma_rs_n128_b0(s, q[4 * kk], q[4 * kk + 1], q[4 * kk + 2], q[4 * kk + 3], mk_desc(b + (kk >> 2) * 1024 + (kk & 3) * 2, DHI_SW128), kk);
          wg_commit();
        };
        auto issue_pv = [&](uint32_t st) {
          const uint32_t b = desc_lo(st, 16384);
#pragma unroll
          for (int kk = 0; kk < 8; kk++) {
            wgmma_rs_n128_b1(o, pr[4 * kk], pr[4 * kk + 1], pr[4 * kk + 2], pr[4 * kk + 3], mk_desc(b + kk * 128, DHI_SW128), 1);
            if (kk == 1 || kk == 3 || kk == 7) wg_commit();
          }
        };
        auto skip = [&]() {
          uint32_t bar;
          acquire(2, bar);
          release(bar);
        };
        const bool half = !(grp & 1);
        float t[4];
        auto first = [&]() {
          float a0, a1, c0, c1;
          uint32_t kb;
          const uint32_t kst = acquire(2, kb);
          if (!lng) bar_sync(1 + wg, 256);
          fence_regs(q);
          fence_regs(s);
          if (half) {
            const uint32_t b = desc_lo(kst, 16);
            wg_fence();
#pragma unroll
            for (int kk = 0; kk < 8; kk++) wgmma_rs_n64_b0(reinterpret_cast<float(&)[32]>(s), q[4 * kk], q[4 * kk + 1], q[4 * kk + 2], q[4 * kk + 3], mk_desc(b + (kk >> 2) * 1024 + (kk & 3) * 2, DHI_SW128), kk);
            wg_commit();
            bar_arrive(2 - wg, 256);
            wg_wait<0>();
            fence_regs(s);
            causal_mask<0, 8>(s, lim0);
          } else {
            wg_fence();
            issue_s(kst);
            bar_arrive(2 - wg, 256);
            wg_wait<0>();
            fence_regs(s);
            causal_mask<8, 16>(s, lim0);
          }
          release(kb);
          TRF(2);
          softmax_max<FM_NJ>(s, m0, m1, a0, a1, c0, c1);
          softmax_exp<0, 8>(s, pr, c0, c1, t);
          if (half) {
#pragma unroll
            for (int i = 16; i < 32; i++) pr[i] = 0;
          } else {
            softmax_exp<8, 16>(s, pr, c0, c1, t);
          }
        };
        auto block = [&]() {
          const uint32_t kb = r.bar(), kp = r.par(), kst = sb + r.take(2) * M_GR;
          r.e++;
          const uint32_t vb = r.bar(), vp = r.par(), vst = sb + r.take(2) * M_GR;
          r.e++;
          mbar_wait2(sb + M_FULL + kb, kp, sb + M_FULL + vb, vp);
          fence_regs(o);
          fence_regs(pr);
          fence_regs(s);
          bar_sync(1 + wg, 256);
          wg_fence();
          issue_s(kst);
          issue_pv(vst);
          bar_arrive(2 - wg, 256);
          wg_wait<3>();
          release(kb);
          fence_regs(s);
          const float d0 = -m0 * SM_C, d1 = -m1 * SM_C;
          wg_wait<2>();
          fence_part<0, 8>(pr);
          softmax_exp<0, 4>(s, pr, d0, d1, t);
          fence_part<0, 8>(pr);
          sched_fence(kst);
          wg_wait<1>();
          fence_part<8, 16>(pr);
          softmax_exp<4, 8>(s, pr, d0, d1, t);
          fence_part<8, 16>(pr);
          sched_fence(vst);
          wg_wait<0>();
          release(vb);
          fence_regs(o);
          fence_part<16, 32>(pr);
          softmax_exp<8, 16>(s, pr, d0, d1, t);
        };
        auto check = [&](bool hlf) {
          if (__builtin_expect(__any_sync(0xffffffffu, !((t[0] + t[1]) + (t[2] + t[3]) < 1.8446744e19f)), 0)) {
            float a0, a1, c0, c1;
            if (hlf) {
#pragma unroll
              for (int i = 32; i < 64; i++) s[i] = -INFINITY;
            }
            softmax_max<16>(s, m0, m1, a0, a1, c0, c1);
            l0 *= a0;
            l1 *= a1;
#pragma unroll
            for (int i = 0; i < 16; i++) { o[4 * i] *= a0; o[4 * i + 1] *= a0; o[4 * i + 2] *= a1; o[4 * i + 3] *= a1; }
            softmax_exp<0, 16>(s, pr, c0, c1, t);
          }
          l0 += t[0] + t[1];
          l1 += t[2] + t[3];
        };
        if (!lng) skip();
        first();
        check(half);
        if (!lng) skip();
        TRF(3);
#pragma unroll 1
        for (int j = 1; j < n; j++) {
          if (j == n - 1) TRF(4);
          block();
          check(false);
        }
        TRF(5);
        uint32_t vb;
        const uint32_t vst = acquire(2, vb);
        fence_regs(o);
        fence_regs(pr);
        if (!lng) bar_sync(1 + wg, 256);
        wg_fence();
        issue_pv(vst);
        l0 += __shfl_xor_sync(0xffffffffu, l0, 1);
        l1 += __shfl_xor_sync(0xffffffffu, l1, 1);
        l0 += __shfl_xor_sync(0xffffffffu, l0, 2);
        l1 += __shfl_xor_sync(0xffffffffu, l1, 2);
        const float i0 = rcp(l0), i1 = rcp(l1);
        next_task();
        mbar_wait(sb + M_SFREE + 8 * wg, (ti & 1) ^ 1);
        wg_wait<0>();
        release(vb);
        fence_regs(o);
        fence_regs(pr);
        TRF(6);
        stage_tile<0, 16>(o, sb + M_STG + wg * 16384 + sa, i0, i1);
        fence_async_smem();
        __syncwarp();
        arrive_elect(sb + M_EPI + 8 * (sl * 2 + wg));
        TRF(7);
      } else if (type >= T_MA) {
        float acc[64];
#pragma unroll
        for (int i = 0; i < 64; i++) acc[i] = 0.f;
        uint32_t prev = 0;
        for (int kb = 0; kb < 64; kb++) {
          uint32_t bar;
          const uint32_t st = acquire(2, bar);
          const uint32_t a = desc_lo(st + wg * 8192, 16), b = desc_lo(st + 16384, 4096);
          wg_fence();
#pragma unroll
          for (int kk = 0; kk < 4; kk++) wgmma_ss_n128_a0b1(acc, mk_desc(a + kk * 2, DHI_SW128), mk_desc(b + (kk >> 1) * 512 + (kk & 1) * 128, DHI_SW128), kk | kb);
          wg_commit();
          if (kb > 0) { wg_wait<1>(); release(prev); }
          prev = bar;
        }
        next_task();
        uint32_t bar;
        const uint32_t st = acquire(2, bar);
        mbar_wait(sb + M_SFREE + 8 * wg, (ti & 1) ^ 1);
        wg_wait<0>();
        release(prev);
        fence_regs(acc);
        stage_tile<0, 16>(acc, st + wg * 16384 + sa, 1.f, 1.f);
        fence_async_smem();
        __syncwarp();
        arrive_elect(sb + M_EPI + 8 * (sl * 2 + wg));
      } else {
        float acc[96];
#pragma unroll
        for (int i = 0; i < 96; i++) acc[i] = 0.f;
        uint32_t prev = 0;
        for (int kb = 0; kb < 64; kb++) {
          uint32_t bar;
          const uint32_t st = acquire(3, bar);
          const uint32_t a = desc_lo(st + wg * 8192, 16), b = desc_lo(st + 16384, 4096);
          wg_fence();
#pragma unroll
          for (int kk = 0; kk < 4; kk++) wgmma_ss_n192_a0b1(acc, mk_desc(a + kk * 2, DHI_SW128), mk_desc(b + (kk >> 1) * 768 + (kk & 1) * 128, DHI_SW128), kk | kb);
          wg_commit();
          if (kb > 0) { wg_wait<1>(); release(prev); }
          prev = bar;
        }
        next_task();
        uint32_t bar;
        const uint32_t st = acquire(3, bar);
        mbar_wait(sb + M_SFREE + 8 * wg, (ti & 1) ^ 1);
        wg_wait<0>();
        release(prev);
        fence_regs(acc);
        stage_tile<0, 24>(acc, st + wg * 24576 + sa, 1.f, 1.f);
        fence_async_smem();
        __syncwarp();
        arrive_elect(sb + M_EPI + 8 * (sl * 2 + wg));
      }
#ifdef DEV_TRACE
      if (w4 == 0 && lane == 0 && ti < 250) { long long c; asm volatile("mov.u64 %0, %%globaltimer;" : "=l"(c)); g_trace[blockIdx.x * 4096 + ti * 8 + wg * 4 + 1] = c; }
#endif
    }
    cluster_sync();
  }
}

typedef CUresult (*EncodeFn)(CUtensorMap*, CUtensorMapDataType, cuuint32_t, void*, const cuuint64_t*, const cuuint64_t*, const cuuint32_t*,
                             const cuuint32_t*, CUtensorMapInterleave, CUtensorMapSwizzle, CUtensorMapL2promotion, CUtensorMapFloatOOBfill);

void map2d(EncodeFn enc, CUtensorMap* m, const void* p, int rows, int cols, int boxr) {
  cuuint64_t gd[2] = {(cuuint64_t)cols, (cuuint64_t)rows}, gs[1] = {(cuuint64_t)cols * 2};
  cuuint32_t bx[2] = {64, (cuuint32_t)boxr}, es[2] = {1, 1};
  enc(m, CU_TENSOR_MAP_DATA_TYPE_BFLOAT16, 2, (void*)p, gd, gs, bx, es, CU_TENSOR_MAP_INTERLEAVE_NONE, CU_TENSOR_MAP_SWIZZLE_128B,
      CU_TENSOR_MAP_L2_PROMOTION_L2_256B, CU_TENSOR_MAP_FLOAT_OOB_FILL_NONE);
}
void map3d(EncodeFn enc, CUtensorMap* m, const void* p, int rows, int cols, int boxr, int nch) {
  cuuint64_t gd[3] = {64, (cuuint64_t)rows, (cuuint64_t)cols / 64}, gs[2] = {(cuuint64_t)cols * 2, 128};
  cuuint32_t bx[3] = {64, (cuuint32_t)boxr, (cuuint32_t)nch}, es[3] = {1, 1, 1};
  enc(m, CU_TENSOR_MAP_DATA_TYPE_BFLOAT16, 3, (void*)p, gd, gs, bx, es, CU_TENSOR_MAP_INTERLEAVE_NONE, CU_TENSOR_MAP_SWIZZLE_128B,
      CU_TENSOR_MAP_L2_PROMOTION_L2_256B, CU_TENSOR_MAP_FLOAT_OOB_FILL_NONE);
}

#ifndef R_KR
#define R_KR 24
#endif
#ifndef R_VR
#define R_VR 9
#endif
constexpr int R_NS = 36 - R_KR;
constexpr int R_WQ = 0, R_WK = R_WQ + R_NS * 2048, R_WV = R_WK + R_NS * 2048;
constexpr int R_OS = 102 * 1024;
constexpr int R_RS = 103 * 1024;
static_assert(R_WV + (36 - R_VR) * 2048 <= R_OS, "weights");
constexpr int R_HC = 9216, R_H = 114 * 1024, R_HM = R_H + 4096;
__host__ __device__ constexpr int hoff(int c) { return (c < 8 ? 1 + (c >> 1) + 4 * (c & 1) : 0) * R_HC; }
constexpr int R_PS = R_H + 9 * R_HC;
constexpr int R_GS = 1056, R_HS = 12288, R_QS = 201 * 1024;
static_assert(R_PS + 5120 <= R_QS, "layout");
constexpr int R_BAR = R_QS + 2 * R_HS;
static_assert(3 * 73728 <= R_BAR, "prologue staging");
constexpr int RB_MEM = R_BAR  , RB_RS = R_BAR + 40, RB_QK = R_BAR + 48, RB_XF = R_BAR + 88  , RB_QXL = R_BAR + 104, RB_W = R_BAR + 112  ;
constexpr int RB_TF = R_BAR + 128  , RB_TE = R_BAR + 224  , RB_TR = R_BAR + 256;
constexpr int R_SMEM = R_BAR + 320;
static_assert(R_SMEM <= 232448, "smem");
constexpr int QK_TX = 2048 + 8 * R_GS;
constexpr int NB_P1 = 1, NB_P3 = 2, NB_PM = 3, NB_O = 4, NB_PX = 5, NB_RD = 6, NB_S = 7, NB_O2 = 8;
static_assert(R_NS >= 9 && R_NS <= 18, "R_KR");
__host__ __device__ constexpr int nsm(int c) { return c < R_NS - 9 ? 2 : 1; }
__host__ __device__ constexpr int sm0(int c) { return c < R_NS - 9 ? 2 * c : c + R_NS - 9; }
__host__ __device__ constexpr bool qk_in_reg(int k) { return (k & 3) >= nsm(k >> 2); }
__host__ __device__ constexpr int qk_slot(int k) { return qk_in_reg(k) ? k - sm0((k >> 2) + 1) : sm0(k >> 2) + (k & 3); }
__host__ __device__ constexpr int qk_step(int slot, bool reg) {
  for (int k = 0; k < 36; k++)
    if (qk_in_reg(k) == reg && qk_slot(k) == slot) return k;
  return -1;
}
#ifndef B_SEQ
#define B_SEQ "qkqkqkqkQkqkKqkq|QKQKQKqkQkqKqkQkqKqkQkqKqkQkqKqkQkqKqkQkqKqkQkqKqkQkqKqk"
#endif
__host__ __device__ constexpr int seq_count(char c, int n) {
  int r = 0;
  for (int i = 0; i < n; i++) r += B_SEQ[i] == c;
  return r;
}
static_assert(sizeof(B_SEQ) == 74 && seq_count('q', 73) == R_KR && seq_count('k', 73) == R_KR && seq_count('Q', 73) == R_NS && seq_count('K', 73) == R_NS, "B_SEQ");
#ifndef V_N1
#define V_N1 10
#endif
#ifndef V_PER
#define V_PER 3
#endif
#ifndef V_K0
#define V_K0 11
#endif
#ifndef QX_AFTER
#define QX_AFTER 2
#endif
#ifndef P1_PRE
#define P1_PRE 2
#endif
#ifndef B_DELAY
#define B_DELAY 0
#endif
#ifndef PUB_REL
#define PUB_REL 0
#endif
#ifndef PF_V
#define PF_V 0
#endif
#ifndef PF_MAIN
#define PF_MAIN 0
#endif
#ifndef PRE_EARLY
#define PRE_EARLY 1
#endif
#ifndef P3_EARLY
#define P3_EARLY 0
#endif
#ifndef POLL_STAG
#define POLL_STAG 80
#endif
#ifndef POLL_DELAY
#define POLL_DELAY 240
#endif
__host__ __device__ constexpr bool v_in_reg(int k) { return k >= V_K0 && (k - V_K0) % V_PER == 0 && (k - V_K0) / V_PER < R_VR; }
__host__ __device__ constexpr int v_nreg_before(int k) { return k <= V_K0 ? 0 : ((k - V_K0 + V_PER - 1) / V_PER < R_VR ? (k - V_K0 + V_PER - 1) / V_PER : R_VR); }
__host__ __device__ constexpr int v_slot(int k) { return v_in_reg(k) ? (k - V_K0) / V_PER : k - v_nreg_before(k); }
static_assert(V_K0 + (R_VR - 1) * V_PER < 36, "Wv split");

struct RmtParams {
  CUtensorMap wq, wk, wv, wo, x, mem, ox, ox64, wo3;
  const __nv_bfloat16 *ckv, *wuk, *wuv;
  uint32_t* out;
};
constexpr int XCH_CL = 16 * 288, XCH_SLOT = 4 * XCH_CL;
__device__ uint32_t g_xch[2 * XCH_SLOT];
#ifdef DEV_TRACE
__device__ long long g_trace_b[64 * 4096];
#ifndef TR_S0
#define TR_S0 24
#endif
#ifndef TR_MASK
#define TR_MASK 0xffffffffu
#endif
#define TRW(slot, w) do { if (((TR_MASK >> (slot)) & 1) && w4 == (w) && s >= TR_S0 && s < TR_S0 + 16) { uint32_t c_; asm volatile("mov.u32 %0, %%clock;" : "=r"(c_)::"memory"); sts32(sb + R_QS + R_GS + ((s >> 3) & 1) * R_HS + (s & 7) * 128 + (slot) * 4, c_); } } while (0)
#else
#define TRW(slot, w)
#endif
#define TRB(slot) TRW(slot, 0)
#ifdef DEV_TRACE
#ifndef TRG_MASK
#define TRG_MASK 0x41
#endif
#define TRT(slot, w) do { if (warp == (w) && (threadIdx.x & 31) == 0) { long long c_; asm volatile("mov.u64 %0, %%globaltimer;" : "=l"(c_)); g_trace_b[bid * 4096 + 2200 + (slot)] = c_; } } while (0)
#define TRG(slot) do { if (((slot) >= 16 || ((TRG_MASK >> (slot)) & 1)) && (threadIdx.x & 127) == 0) { long long c_; asm volatile("mov.u64 %0, %%globaltimer;" : "=l"(c_)); g_trace_b[bid * 4096 + 2048 + (slot)] = c_; if ((slot) < 8) g_trace_b[bid * 4096 + 2056 + (slot)] = clock64(); } } while (0)
#else
#define TRG(slot)
#define TRT(slot, w)
#endif

__device__ __forceinline__ void ldsm4(uint32_t (&r)[4], uint32_t a) {
  asm volatile("ldmatrix.sync.aligned.m8n8.x4.shared.b16 {%0,%1,%2,%3}, [%4];" : "=r"(r[0]), "=r"(r[1]), "=r"(r[2]), "=r"(r[3]) : "r"(a) : "memory");
}
__device__ __forceinline__ void ldsm4t(uint32_t (&r)[4], uint32_t a) {
  asm volatile("ldmatrix.sync.aligned.m8n8.x4.trans.shared.b16 {%0,%1,%2,%3}, [%4];" : "=r"(r[0]), "=r"(r[1]), "=r"(r[2]), "=r"(r[3]) : "r"(a) : "memory");
}
__device__ __forceinline__ void stsm4t(uint32_t a, uint32_t r0, uint32_t r1, uint32_t r2, uint32_t r3) {
  asm volatile("stmatrix.sync.aligned.m8n8.x4.trans.shared.b16 [%0], {%1,%2,%3,%4};" ::"r"(a), "r"(r0), "r"(r1), "r"(r2), "r"(r3) : "memory");
}
__device__ __forceinline__ void stsm2t(uint32_t a, uint32_t r0, uint32_t r1) {
  asm volatile("stmatrix.sync.aligned.m8n8.x2.trans.shared.b16 [%0], {%1,%2};" ::"r"(a), "r"(r0), "r"(r1) : "memory");
}
__device__ __forceinline__ void mma16816(float (&c)[4], const uint32_t (&a)[4], uint32_t b0, uint32_t b1) {
  asm volatile("mma.sync.aligned.m16n8k16.row.col.f32.bf16.bf16.f32 {%0,%1,%2,%3}, {%4,%5,%6,%7}, {%8,%9}, {%0,%1,%2,%3};"
               : "+f"(c[0]), "+f"(c[1]), "+f"(c[2]), "+f"(c[3])
               : "r"(a[0]), "r"(a[1]), "r"(a[2]), "r"(a[3]), "r"(b0), "r"(b1));
}
__device__ __forceinline__ void sts32(uint32_t a, uint32_t v) { asm volatile("st.shared.b32 [%0], %1;" ::"r"(a), "r"(v) : "memory"); }
__device__ __forceinline__ uint2 lds64(uint32_t a) {
  uint2 v;
  asm volatile("ld.shared.v2.b32 {%0,%1}, [%2];" : "=r"(v.x), "=r"(v.y) : "r"(a) : "memory");
  return v;
}
__device__ __forceinline__ float4 lds128f(uint32_t a) {
  float4 v;
  asm volatile("ld.shared.v4.f32 {%0,%1,%2,%3}, [%4];" : "=f"(v.x), "=f"(v.y), "=f"(v.z), "=f"(v.w) : "r"(a) : "memory");
  return v;
}
__device__ __forceinline__ uint4 ld_relaxed128(const uint32_t* p) {
  uint4 v;
  asm volatile("ld.relaxed.gpu.global.v4.u32 {%0,%1,%2,%3}, [%4];" : "=r"(v.x), "=r"(v.y), "=r"(v.z), "=r"(v.w) : "l"(p) : "memory");
  return v;
}
__device__ __forceinline__ void st_relaxed32(uint32_t* p, uint32_t v) { asm volatile("st.relaxed.gpu.global.u32 [%0], %1;" ::"l"(p), "r"(v) : "memory"); }

__device__ __forceinline__ void mma1688(float (&c)[4], uint32_t a0, uint32_t a1, uint32_t b0) {
  asm volatile("mma.sync.aligned.m16n8k8.row.col.f32.bf16.bf16.f32 {%0,%1,%2,%3}, {%4,%5}, {%6}, {%0,%1,%2,%3};"
               : "+f"(c[0]), "+f"(c[1]), "+f"(c[2]), "+f"(c[3])
               : "r"(a0), "r"(a1), "r"(b0));
}
__device__ __forceinline__ uint2 ld_relaxed64(const uint32_t* p) {
  uint2 v;
  asm volatile("{.reg .b64 t; ld.relaxed.gpu.global.b64 t, [%2]; mov.b64 {%0,%1}, t;}" : "=r"(v.x), "=r"(v.y) : "l"(p) : "memory");
  return v;
}
__device__ __forceinline__ void st_relaxed64(uint32_t* p, uint32_t a, uint32_t b) { asm volatile("{.reg .b64 t; mov.b64 t, {%1,%2}; st.relaxed.gpu.global.b64 [%0], t;}" ::"l"(p), "r"(a), "r"(b) : "memory"); }

__device__ __forceinline__ void mma16816z(float (&c)[4], const uint32_t (&a)[4], uint32_t b0, uint32_t b1) {
  asm volatile("mma.sync.aligned.m16n8k16.row.col.f32.bf16.bf16.f32 {%0,%1,%2,%3}, {%4,%5,%6,%7}, {%8,%9}, {0f00000000,0f00000000,0f00000000,0f00000000};"
               : "=f"(c[0]), "=f"(c[1]), "=f"(c[2]), "=f"(c[3])
               : "r"(a[0]), "r"(a[1]), "r"(a[2]), "r"(a[3]), "r"(b0), "r"(b1));
}
template <int NB> __device__ __forceinline__ uint2 xch_reduce(uint32_t a, int key, uint32_t* dst, uint32_t tag) {
  uint32_t m[NB][4];
  float c[2][4];
#pragma unroll
  for (int j = 0; j < NB; j++) ldsm4t(m[j], a ^ (j << 5));
#pragma unroll
  for (int j = 0; j < NB; j++) {
    const uint32_t one = key == j ? 0x3f803f80u : 0u;
    if (j < 2) mma16816z(c[j], m[j], one, one);
    else mma16816(c[j & 1], m[j], one, one);
  }
  const uint2 o = make_uint2((__float_as_uint(c[0][0] + c[1][0]) & ~1u) | tag, __float_as_uint(c[0][2] + c[1][2]));
  st_relaxed64(dst, o.x, o.y);
  return o;
}
__device__ __forceinline__ uint32_t xch_sum(const uint2 (&v)[4]) {
  return pack_bf16((__uint_as_float(v[0].x) + __uint_as_float(v[1].x)) + (__uint_as_float(v[2].x) + __uint_as_float(v[3].x)),
                   (__uint_as_float(v[0].y) + __uint_as_float(v[1].y)) + (__uint_as_float(v[2].y) + __uint_as_float(v[3].y)));
}
__device__ __forceinline__ void xch_probe(uint2 (&v)[4], const uint32_t* x, int cl) {
#pragma unroll
  for (int c = 0; c < 4; c++)
    asm volatile("{.reg .pred p; .reg .b64 t; setp.ne.s32 p, %3, %4; mov.b64 t, {%0,%1}; @p ld.relaxed.gpu.global.b64 t, [%2]; mov.b64 {%0,%1}, t;}"
                 : "+r"(v[c].x), "+r"(v[c].y) : "l"(x + c * XCH_CL), "r"(cl), "r"(c) : "memory");
}
__device__ __forceinline__ uint32_t xch_bad(const uint2 (&v)[4]) {
  uint32_t bad;
  asm("{.reg .b32 t; lop3.b32 t, %1, %2, %3, 0x7e; lop3.b32 %0, t, %4, %3, 0xf6;}" : "=r"(bad) : "r"(v[0].x), "r"(v[1].x), "r"(v[2].x), "r"(v[3].x));
  return bad;
}
template <bool TWO> __device__ __forceinline__ uint32_t xch_poll(const uint32_t* x, int cl, uint2 o, const uint32_t* x2, uint2 o2, uint32_t& r2) {
  uint2 v[4] = {o, o, o, o}, w[4] = {o2, o2, o2, o2};
  uint32_t r;
#pragma unroll 1
  for (int it = 0;; it++) {
    xch_probe(v, x, cl);
    if (TWO) xch_probe(w, x2, cl);
    if (it > (1 << 20)) __trap();
    uint32_t bad = xch_bad(v);
    if (TWO) { bad |= xch_bad(w); r2 = xch_sum(w); }
    r = xch_sum(v);
    if (!__any_sync(0xffffffffu, bad & 1)) break;
  }
  return r;
}
constexpr uint32_t CTA1 = 1u << 24;
template <int NSEND, int NPRE> struct XSend {
  uint32_t d[NPRE], b[NPRE];
  static __device__ constexpr uint32_t off(int i) { return ((2 * i + 2 * i / NSEND) & (NSEND - 1)) * CTA1; }
  __device__ __forceinline__ XSend(uint32_t dst, uint32_t bar) {
#pragma unroll
    for (int i = 0; i < NPRE; i++) { d[i] = dst ^ off(i); b[i] = bar ^ off(i); }
    fence_regs(d);
    fence_regs(b);
  }
  __device__ __forceinline__ void send(uint32_t v) {
    asm volatile("" : "+r"(d[0]), "+r"(b[0]));
#pragma unroll
    for (int i = 0; i < NSEND; i++) st_async32(i < NPRE ? d[i] : d[0] ^ off(i), v, i < NPRE ? b[i] : b[0] ^ off(i));
  }
};
__device__ __forceinline__ uint32_t mbar_try_addr(uint32_t bar, uint32_t par, uint32_t good) {
  uint32_t r;
  asm volatile("{.reg .pred p; .reg .b32 t; mbarrier.try_wait.parity.shared::cta.b64 p, [%1], %2; xor.b32 t, %3, 16; selp.b32 %0, %3, t, p;}" : "=r"(r) : "r"(bar), "r"(par), "r"(good) : "memory");
  return r;
}

#ifdef DEV_TRACE
__device__ __noinline__ void trace_sync() {
  if (threadIdx.x == 0) {
    uint32_t g0, g1, c_;
    asm volatile("mov.u32 %0, %%globaltimer_lo;" : "=r"(g0));
    do { asm volatile("mov.u32 %0, %%globaltimer_lo;" : "=r"(g1)); asm volatile("mov.u32 %0, %%clock;" : "=r"(c_)); } while ((g1 >> 10) == (g0 >> 10));
    g_trace_b[(int)blockIdx.x * 4096 + 2160] = g1; g_trace_b[(int)blockIdx.x * 4096 + 2161] = c_;
  }
}
#endif
template <bool MASK>
__device__ __forceinline__ void rmt_softmax_row(const float (&d)[20], int u, int lim, uint32_t pax, uint32_t pam) {
  constexpr float C = 0.08838834764831845f * 1.4426950408889634f;
  float v[10];
#pragma unroll
  for (int j = 0; j < 5; j++) {
    v[2 * j] = (!MASK || j == 4 || 2 * j <= lim) ? d[4 * j + 2 * u] : -INFINITY;
    v[2 * j + 1] = (!MASK || j == 4 || 2 * j + 1 <= lim) ? d[4 * j + 2 * u + 1] : -INFINITY;
  }
  float m = fmaxf(fmaxf(fmaxf(v[0], v[1]), fmaxf(v[2], v[3])), fmaxf(fmaxf(fmaxf(v[4], v[5]), fmaxf(v[6], v[7])), fmaxf(v[8], v[9])));
  m = fmaxf(m, __shfl_xor_sync(0xffffffffu, m, 1));
  m = fmaxf(m, __shfl_xor_sync(0xffffffffu, m, 2));
  const float mc = -m * C;
#pragma unroll
  for (int i = 0; i < 10; i++) v[i] = ex2(fmaf(v[i], C, mc));
  float l = ((v[0] + v[1]) + (v[2] + v[3])) + (((v[4] + v[5]) + (v[6] + v[7])) + (v[8] + v[9]));
  l += __shfl_xor_sync(0xffffffffu, l, 1);
  l += __shfl_xor_sync(0xffffffffu, l, 2);
  const float inv = rcp(l);
  sts128(pax, pack_bf16(v[0] * inv, v[1] * inv), pack_bf16(v[2] * inv, v[3] * inv), pack_bf16(v[4] * inv, v[5] * inv), pack_bf16(v[6] * inv, v[7] * inv));
  sts32(pam, pack_bf16(v[8] * inv, v[9] * inv));
}

__global__ void __launch_bounds__(256, 1) rmt_kernel(const __grid_constant__ RmtParams P) {
  extern __shared__ __align__(1024) uint8_t smem_rmt[];
  const uint32_t sb = (uint32_t)__cvta_generic_to_shared(smem_rmt);
  const int warp = __shfl_sync(0xffffffffu, threadIdx.x >> 5, 0);
  const int lane = __shfl_sync(0xffffffffu, threadIdx.x & 31, threadIdx.x & 31);
  const int w4 = warp & 3, g = lane >> 2, t4 = lane & 3, rho = lane & 7, li = lane >> 3;
  uint32_t rank;
  asm("mov.u32 %0, %%cluster_ctarank;" : "=r"(rank));
  constexpr int ST_O = R_WV, ST_Q = ST_O + 73728, ST_K = ST_Q + R_KR * 2048, ST_V0 = R_OS, ST_V1 = ST_K + R_KR * 2048 - 6 * 2048;
  static_assert(ST_V0 + 6 * 2048 <= R_H && ST_V0 + 6 * 2048 <= ST_Q && ST_V1 + R_VR * 2048 <= R_BAR, "staging");

#ifdef DEV_SYNC
  trace_sync();
#endif
  if (threadIdx.x == 0) {
    if ((sb & 1023) || mapa(sb, 15) != (mapa(sb, 0) ^ (15 * CTA1))) __trap();
    for (int i = 0; i < 6; i++) mbar_init(sb + RB_MEM + 8 * i, 1);
    mbar_init(sb + RB_QK, 5); mbar_init(sb + RB_XF, 1); mbar_init(sb + RB_XF + 8, 1); mbar_init(sb + RB_QXL, 4); mbar_init(sb + RB_W, 1); mbar_init(sb + RB_W + 8, 1);
#pragma unroll 1
    for (int i = 0; i < 17; i++) mbar_init(sb + RB_TF + 8 * i, i >> 2 == 3 ? 4 : 1);
    asm volatile("fence.mbarrier_init.release.cluster;" ::: "memory");
    mbar_expect(sb + RB_TR, 49152);
    mbar_expect(sb + RB_W, 2 * 73728);
    mbar_expect(sb + RB_W + 8, 73728);
  }
  if (threadIdx.x == 32) TRE(blockIdx.x);
  asm volatile("griddepcontrol.launch_dependents;");
  const int cl = blockIdx.x >> 4;
  __syncthreads();
  const int bid = cl * 16 + rank, c0 = bid * 64;
  if (warp == 0) TRG(0);
  auto prefetch_main = [&]() {
    asm volatile("cp.async.bulk.prefetch.L2.global [%0], 4096;" ::"l"(P.ckv + (bid * 8 + warp) * 2048) : "memory");
    asm volatile("cp.async.bulk.prefetch.L2.global [%0], 1280;" ::"l"(P.wuk + (bid * 8 + warp) * HDALL) : "memory");
    asm volatile("cp.async.bulk.prefetch.L2.global [%0], 1280;" ::"l"(P.wuv + (bid * 8 + warp) * HDALL) : "memory");
  };
  if (PF_MAIN == 1 && elect()) prefetch_main();
  __syncwarp();
  if (B_DELAY > 0) __nanosleep(B_DELAY);
  if (elect()) {
    for (int i = warp; i < 9; i += 8) tma2d(sb + ST_O + i * 8192, &P.wo, i * 64, c0, sb + RB_W + 8);
    if (warp == 1 && bid < 27) asm volatile("cp.async.bulk.prefetch.tensor.2d.L2.global [%0, {%1,%2}];" ::"l"(bid < 18 ? &P.x : &P.mem), "r"(bid % 9 * 64), "r"(bid / 9 % 2 * 32) : "memory");
    for (int k = warp; k < 36; k += 8) {
      const int o = qk_slot(k) * 2048;
      tma2d(sb + (qk_in_reg(k) ? ST_Q : R_WQ) + o, &P.wq, c0, k * 16, sb + RB_W);
      tma2d(sb + (qk_in_reg(k) ? ST_K : R_WK) + o, &P.wk, c0, k * 16, sb + RB_W);
    }
    if (PF_V) for (int i = warp; i < 36; i += 8) asm volatile("cp.async.bulk.prefetch.tensor.2d.L2.global [%0, {%1,%2}];" ::"l"(&P.wv), "r"(c0), "r"(i * 16) : "memory");
    if (PF_MAIN == 2) prefetch_main();
  }
  __syncwarp();
  uint32_t wa = sb + ((li >> 1) * 8 + rho) * 128 + (((2 * w4 + (li & 1)) ^ rho) << 4);
  uint32_t la = sb + rho * 128 + ((li ^ rho) << 4);
  int ln = lane;
  if (warp == 0) TRG(1);
  mbar_wait(sb + RB_W + 8 * (warp >> 2), 0);
  if (warp == 0) TRG(2);

  if (warp < 4) {
    uint32_t wq[R_KR][4], wk[R_KR][4];
#pragma unroll
    for (int k = 0; k < R_KR; k++) { ldsm4t(wq[k], wa + ST_Q + k * 2048); ldsm4t(wk[k], wa + ST_K + k * 2048); }
    fence_async_smem();
    bar_sync(NB_P3, 256);
    asm volatile("barrier.cluster.arrive.relaxed.aligned;" ::: "memory");
    if (w4 < 2 && elect()) {
      mbar_expect(sb + RB_XF + 8 * w4, 9 * 4096);
      for (int i = 0; i < 9; i++) tma2d(sb + R_H + hoff(i) + w4 * 5120, &P.x, i * 64, w4 * 32, sb + RB_XF + 8 * w4);
    }
    if (w4 == 3 && elect()) {
      mbar_expect(sb + RB_QK, QK_TX);
      for (int i = 0; i < 5; i++) mbar_expect(sb + RB_MEM + 8 * i, i < 4 ? 2048 : 1024);
      for (int i = 0; i < 9; i++) tma2d(sb + R_HM + hoff(i), &P.mem, i * 64, 0, sb + RB_MEM + 8 * (i >> 1));
    }
    if (w4 == 2) sts128(sb + R_PS + (8 + lane) * 128 + ((5 ^ rho) << 4), 0u, 0u, 0u, 0u);
    __syncwarp();
    uint32_t qm = __shfl_sync(0xffffffffu, sb + R_QS + (rank & 1) * R_HS + (w4 * 16 + g) * 16 + t4 * 4, lane);
    const uint32_t peer = mapa(sb, rank ^ 1) - sb;

    uint32_t aq[P1_PRE][4], ak[P1_PRE][4];
    auto preload = [&]() {
#pragma unroll
      for (int i = 0; i < P1_PRE; i++) { ldsm4t(aq[i], wa + R_WQ + i * 2048); ldsm4t(ak[i], wa + R_WK + i * 2048); }
    };
    auto chain = [&](int s) {
      const bool LAST = s == 63;
      float cq[2][4], ck[2][4];
      for (;;) {
        uint32_t b[3][4];
        if (!PRE_EARLY) preload();
        mbar_wait(sb + RB_MEM, s & 1);
        TRB(0);
        uint32_t lb = la, bad = 0;
        ldsm4(b[0], lb + R_HM + hoff(0));
        ldsm4(b[1], (lb ^ 64) + R_HM + hoff(0));
#pragma unroll
        for (int hc = 0; hc < 18; hc++) {
          if (hc + 2 < 18) {
            if ((hc & 3) == 2) { lb = mbar_try_addr(sb + RB_MEM + 8 * ((hc + 2) >> 2), s & 1, la); bad |= lb ^ la; }
            ldsm4(b[(hc + 2) % 3], ((hc & 1) ? (lb ^ 64) : lb) + R_HM + hoff((hc + 2) >> 1));
          }
#pragma unroll
          for (int j = 0; j < 2; j++) {
            const int k = 2 * hc + j, sl = qk_slot(k);
            if (qk_in_reg(k)) {
              mma16816(cq[j], wq[sl], b[hc % 3][2 * j], b[hc % 3][2 * j + 1]);
              mma16816(ck[j], wk[sl], b[hc % 3][2 * j], b[hc % 3][2 * j + 1]);
            } else {
              static_assert(nsm(0) == 2, "first two steps come from shared memory");
              if (hc == 0) {
                mma16816z(cq[j], aq[j], b[0][2 * j], b[0][2 * j + 1]);
                mma16816z(ck[j], ak[j], b[0][2 * j], b[0][2 * j + 1]);
              } else {
                mma16816(cq[j], aq[sl % P1_PRE], b[hc % 3][2 * j], b[hc % 3][2 * j + 1]);
                mma16816(ck[j], ak[sl % P1_PRE], b[hc % 3][2 * j], b[hc % 3][2 * j + 1]);
              }
              if (sl + P1_PRE < R_NS) { ldsm4t(aq[sl % P1_PRE], wa + R_WQ + (sl + P1_PRE) * 2048); ldsm4t(ak[sl % P1_PRE], wa + R_WK + (sl + P1_PRE) * 2048); }
            }
          }
        }
        if (!__any_sync(0xffffffffu, bad)) break;
#pragma unroll 1
        for (int i = 1; i < 5; i++) mbar_wait(sb + RB_MEM + 8 * i, s & 1);
        if (PRE_EARLY) preload();
      }
      const uint32_t q0 = pack_bf16(cq[0][0] + cq[1][0], cq[0][1] + cq[1][1]), q1 = pack_bf16(cq[0][2] + cq[1][2], cq[0][3] + cq[1][3]);
      const uint32_t k0 = pack_bf16(ck[0][0] + ck[1][0], ck[0][1] + ck[1][1]), k1 = pack_bf16(ck[0][2] + ck[1][2], ck[0][3] + ck[1][3]);
      const uint32_t qp = qm + peer, bp = sb + RB_QK + peer;
      st_async32(qp, q0, bp);
      st_async32(qp + 128, q1, bp);
      st_async32(qp + 10 * R_GS, k0, bp);
      st_async32(qp + 10 * R_GS + 128, k1, bp);
      sts32(qm, q0);
      sts32(qm + 128, q1);
      sts32(qm + 10 * R_GS, k0);
      sts32(qm + 10 * R_GS + 128, k1);
      bar_arrive(NB_P1, 256);
      fence_async_smem();
      __syncwarp();
      arrive_elect(sb + RB_QK);
      TRB(1);
      float d[20];
#pragma unroll
      for (int i = 0; i < 20; i++) d[i] = 0.f;
      constexpr uint32_t HI = R_GS >> 4;
      const uint32_t qd = desc_lo(sb + R_QS, 128);
      mbar_wait(sb + RB_QK, s & 1);
      TRB(16);
      wg_fence();
#pragma unroll
      for (int k = 0; k < 8; k++) wgmma_ss_n40_a1b1(d, mk_desc(qd + (k >> 2) * (R_HS >> 4) + (k & 3) * 16, HI), mk_desc(qd + (k >> 2) * (R_HS >> 4) + (k & 3) * 16 + 6 * HI, HI), k != 0);
      wg_commit();
      bar_arrive(NB_S, 256);
      if (LAST) asm volatile("barrier.cluster.arrive.relaxed.aligned;" ::: "memory");
      const int ln = (qm >> 2) & 31, tt = ln & 3;
      if (w4 == 0) {
        const int gg = ln >> 2;
        const uint32_t pa = sb + R_PS + gg * 128;
        const uint32_t pax = pa + ((tt ^ gg) << 4), pam = pa + ((4 ^ gg) << 4) + tt * 4;
        wg_wait<0>();
        fence_regs(d);
        TRB(17);
        rmt_softmax_row<false>(d, 0, 0, pax, pam);
        bar_arrive(NB_PM, 160);
        TRB(18);
      } else if (w4 < 3) {
        const int tq = (ln & 24) + 4 * (w4 - 1) + ((ln >> 2) & 1), r7 = tq & 7;
        const uint32_t pa = sb + R_PS + (8 + tq) * 128;
        wg_wait<0>();
        fence_regs(d);
        rmt_softmax_row<true>(d, 0, tq - 8 * tt, pa + ((tt ^ r7) << 4), pa + ((4 ^ r7) << 4) + tt * 4);
        rmt_softmax_row<true>(d, 1, tq + 2 - 8 * tt, pa + 256 + ((tt ^ r7 ^ 2) << 4), pa + 256 + ((6 ^ r7) << 4) + tt * 4);
        fence_async_smem();
        bar_arrive(NB_PX, 192);
        TRW(15, 1);
      } else {
        if (!LAST) {
          if (ln < 7) mbar_expect(sb + RB_MEM + 8 * ln, ln == 6 ? QK_TX : ln == 5 ? 9216 : ln == 4 ? 1024 : 2048);
          if (ln == 11 && s < 62) mbar_expect(sb + RB_XF + 8 * (s & 1), 9 * 4096);
          __syncwarp();
        }
        wg_wait<0>();
        fence_regs(d);
      }
    };
    auto bulk = [&](int s) {
      const bool FIRST = s < 0;
      float dq[16], dk[16];
#pragma unroll
      for (int i = 0; i < 16; i++) dq[i] = dk[i] = 0.f;
      mbar_wait(sb + RB_XF + 8 * ((s + 1) & 1), ((s + 1) >> 1) & 1);
      const uint32_t hd = desc_lo(sb + R_H + ((s + 1) & 1) * 5120, 16), wd = desc_lo(sb + R_WQ, 16);
      auto bdesc = [&](int k) { return mk_desc(hd + (hoff(k >> 2) >> 4) + (k & 3) * 2, DHI_SW128); };
      const uint32_t qx = qm + 2 * R_GS + (qm & 12) * (R_GS / 4 - 1);
      if (s == 60 && w4 < 2) asm volatile("prefetch.tensormap [%0];" ::"l"(&P.ox64 + w4) : "memory");
      if (!FIRST) bar_sync(NB_P3, 256);
      TRB(2);
      wg_fence();
      static_for<0, 73>([&](auto i_) {
        constexpr int i = decltype(i_)::value;
        constexpr char c = B_SEQ[i];
        constexpr int r = seq_count(c, i), nq = seq_count('q', i) + seq_count('Q', i), nk = seq_count('k', i) + seq_count('K', i);
        if constexpr (c == 'q') wgmma_rs_n32_b0(dq, wq[r][0], wq[r][1], wq[r][2], wq[r][3], bdesc(qk_step(r, true)), nq != 0);
        if constexpr (c == 'k') wgmma_rs_n32_b0(dk, wk[r][0], wk[r][1], wk[r][2], wk[r][3], bdesc(qk_step(r, true)), nk != 0);
        if constexpr (c == 'Q') wgmma_ss_n32_a1b0(dq, mk_desc(wd + r * 128, DHI_SW128), bdesc(qk_step(r, false)), nq != 0);
        if constexpr (c == 'K') wgmma_ss_n32_a1b0(dk, mk_desc(wd + (R_NS + r) * 128, DHI_SW128), bdesc(qk_step(r, false)), nk != 0);
        if constexpr (c == '|') {
          if (!FIRST) bar_sync(NB_RD, 256);
          TRB(6);
        }
      });
      wg_commit();
      if (FIRST) asm volatile("barrier.cluster.wait.aligned;" ::: "memory");
      if (PRE_EARLY) preload();
      wg_wait<0>();
      fence_regs(dq);
      fence_regs(dk);
      TRB(3);
#pragma unroll
      for (int r = 0; r < 2; r++) {
        sts128(qx + r * 128, pack_bf16(dq[2 * r], dq[2 * r + 1]), pack_bf16(dq[4 + 2 * r], dq[5 + 2 * r]), pack_bf16(dq[8 + 2 * r], dq[9 + 2 * r]), pack_bf16(dq[12 + 2 * r], dq[13 + 2 * r]));
        sts128(qx + 4 * R_GS + r * 128, pack_bf16(dk[2 * r], dk[2 * r + 1]), pack_bf16(dk[4 + 2 * r], dk[5 + 2 * r]), pack_bf16(dk[8 + 2 * r], dk[9 + 2 * r]), pack_bf16(dk[12 + 2 * r], dk[13 + 2 * r]));
      }
      __syncwarp();
      arrive_elect(sb + RB_QXL);
      TRB(4);
    };
    TRG(3);
#pragma unroll 1
    for (int s = -1; s < 63;) {
      asm volatile("" : "+r"(wa), "+r"(la), "+r"(qm));
      bulk(s);
      s++;
#ifdef DEV_TRS
      TRG(16 + s);
#endif
      chain(s);
    }
#ifdef DEV_TRACE
    bar_sync(NB_S, 256);
    for (int i = threadIdx.x; i < 16 * 32; i += 128) g_trace_b[bid * 4096 + i] = lds32(sb + R_QS + R_GS + ((i >> 8) ^ 1) * R_HS + (i & 255) * 4);
#endif
  } else {
    uint32_t wo[9][4][4], wv[R_VR][4];
#pragma unroll
    for (int i = 0; i < 9; i++) {
      const int T = i < 8 ? 8 * (i >> 1) + 2 * w4 + (i & 1) : 32 + 2 * (w4 & 1) + (w4 >> 1);
      const int quad = i < 8 ? (g >> 2) * 2 + (g & 1) : g & 3, odd = i < 8 ? (g >> 1) & 1 : g >> 2;
      const uint32_t a = sb + ST_O + (T >> 2) * 8192 + t4 * 256 + (quad & 1) * 8;
      const uint32_t ch = (T & 3) * 2 + (quad >> 1), sel = odd ? 0x7632 : 0x5410;
      const uint32_t a0 = a + ((ch ^ (2 * t4)) << 4), a1 = a + 128 + ((ch ^ (2 * t4 + 1)) << 4);
#pragma unroll
      for (int k = 0; k < 8; k++) {
        const uint2 x = lds64(a0 + k * 1024), y = lds64(a1 + k * 1024);
        wo[i][k >> 1][(k & 1) * 2] = __byte_perm(x.x, y.x, sel);
        wo[i][k >> 1][(k & 1) * 2 + 1] = __byte_perm(x.y, y.y, sel);
      }
    }
    fence_async_smem();
    bar_arrive(NB_P3, 256);
    bar_sync(NB_O, 128);
    if (w4 == 0 && elect()) mbar_expect(sb + RB_W + 8, 73728);
    if (elect())
      for (int k = w4; k < 36; k += 4) {
        const int sl = v_slot(k);
        tma2d(sb + (v_in_reg(k) ? (sl < 6 ? ST_V0 : ST_V1) : R_WV) + sl * 2048, &P.wv, c0, k * 16, sb + RB_W + 8);
      }
    __syncwarp();
    mbar_wait(sb + RB_W + 8, 1);
#pragma unroll
    for (int r = 0; r < R_VR; r++) ldsm4t(wv[r], wa + (r < 6 ? ST_V0 : ST_V1) + r * 2048);
    fence_async_smem();
    asm volatile("barrier.cluster.arrive.relaxed.aligned;" ::: "memory");
    const uint32_t sb0 = mapa(sb, 0), tok = rank & 7;
    uint32_t rsb = mapa(sb + RB_RS, (w4 & 1) * 8 + 2 * t4);
    const uint32_t rrow = rank ^ ((t4 & 1) << 3) ^ (t4 & 2), nrow = rank ^ ((t4 & 1) << 2);
    uint32_t rsA = rsb + (R_RS - RB_RS) + rrow * 128 + (((w4 >> 1) * 64 + g * 8) ^ ((rrow & 7) << 4));
    uint32_t rsN = rsb + (R_RS + 8192 - RB_RS) + nrow * 64 + (((w4 >> 1) * 32 + g * 4) ^ (((nrow >> 1) & 3) << 4));
    const uint32_t cp = 16 * (t4 >> 1) + 8 * ((g >> 1) & 1) + 4 * (t4 & 1) + 2 * (g >> 2) + (g & 1);
    uint32_t agd = sb0 + R_HM + tok * 128 + hoff(2 * w4 + (cp >> 4)) + ((((rank >> 3) * 4 + ((cp & 15) >> 2)) ^ tok) << 4) + (cp & 3) * 4;
    uint32_t* xb = g_xch + rank * 288 + w4 * 64 + lane * 2;
    uint32_t vx[8];
#pragma unroll
    for (int i = 0; i < 8; i++) vx[i] = 0;

    auto step = [&](int s) {
      const bool FIRST = s < 0, LAST = s == 63, MID = !FIRST && !LAST;
      const int par = (s + 1) & 1;
      float d[20];
#pragma unroll
      for (int i = 0; i < 20; i++) d[i] = 0.f;
      if (!LAST) mbar_wait(sb + RB_XF + 8 * par, ((s + 1) >> 1) & 1);
      const uint32_t hd = desc_lo(sb + R_H + par * 4096, 16), vd = desc_lo(sb + R_WV, 16);
      if (!FIRST) {
        if (w4 == 0) {
          mbar_wait(sb + RB_QXL, s & 1);
          mbar_wait(sb + RB_MEM + QX_AFTER * 8, s & 1);
          fence_async_smem();
          if (elect()) {
            const uint32_t src = sb + R_QS + (rank & 1) * R_HS + 2 * R_GS, dst = mapa(src, rank ^ 1), bar = mapa(sb + RB_QK, rank ^ 1), cut = 256 + rank * 512;
            asm volatile("cp.async.bulk.shared::cluster.shared::cta.mbarrier::complete_tx::bytes [%0], [%1], %2, [%3];" ::"r"(dst + cut), "r"(src + cut), "r"(8 * R_GS - cut), "r"(bar) : "memory");
            asm volatile("cp.async.bulk.shared::cluster.shared::cta.mbarrier::complete_tx::bytes [%0], [%1], %2, [%3];" ::"r"(dst), "r"(src), "r"(cut), "r"(bar) : "memory");
          }
          __syncwarp();
          TRW(7, 0);
        }
#pragma unroll
        for (int i = 0; i < 5; i++) { mbar_wait(sb + RB_MEM + 8 * i, s & 1); if (i == 4) TRW(30, 2); }
        fence_async_smem();
        bar_sync(NB_P1, 256);
      }
      wg_fence();
#pragma unroll
      for (int k = 0; k < 36; k++) {
        if (k == V_N1 && !FIRST) bar_sync(NB_S, 256);
        const uint64_t db = mk_desc(hd + (hoff(k >> 2) >> 4) + (k & 3) * 2, DHI_SW128);
        if (v_in_reg(k)) wgmma_rs_n40_b0(d, wv[v_slot(k)][0], wv[v_slot(k)][1], wv[v_slot(k)][2], wv[v_slot(k)][3], db, 1);
        else wgmma_ss_n40_a1b0(d, mk_desc(vd + v_slot(k) * 128, DHI_SW128), db, k != 0);
      }
      wg_commit();
      TRB(8);
      uint32_t vm0, vm1, vn[8];
      auto pack_v = [&]() {
#pragma unroll
        for (int i = 0; i < 8; i++) vn[i] = par ? pack_bf16(d[2 * i + 4], d[2 * i + 5]) : pack_bf16(d[2 * i], d[2 * i + 1]);
      };
      if (MID) {
        float o[4] = {0.f, 0.f, 0.f, 0.f};
        uint32_t b0[4], b1[4];
        bar_sync(NB_PM, 160);
        ldsm4(b0, la + R_PS);
        ldsm4(b1, (la ^ 64) + R_PS);
        {
          const uint32_t x0[4] = {vx[0], vx[1], vx[2], vx[3]}, x1[4] = {vx[4], vx[5], vx[6], vx[7]};
          float o2[4] = {0.f, 0.f, 0.f, 0.f};
          wg_wait<0>();
          fence_regs(d);
          TRB(9);
          mma16816(o, x0, b0[0], b0[1]);
          mma16816(o2, x1, b0[2], b0[3]);
          vm0 = par ? pack_bf16(d[0], d[1]) : pack_bf16(d[16], d[17]);
          vm1 = par ? pack_bf16(d[2], d[3]) : pack_bf16(d[18], d[19]);
          float o3[4] = {0.f, 0.f, 0.f, 0.f};
          mma1688(o3, vm0, vm1, b1[0]);
          stsm2t(wa + R_OS, pack_bf16(o[0] + o2[0] + o3[0], o[1] + o2[1] + o3[1]), pack_bf16(o[2] + o2[2] + o3[2], o[3] + o2[3] + o3[3]));
        }
        bar_sync(NB_O, 128);
        TRB(11);
        ldsm4(b0, la + R_OS);
        ldsm4(b1, (la ^ 64) + R_OS);
        auto send = [&](int j, const float (&c0_)[4], const float (&c1_)[4]) {
          st_async64(rsA + j * 2048, pack_bf16(c0_[0], c0_[2]), pack_bf16(c1_[0], c1_[2]), rsb);
          st_async64(rsA + j * 2048 + CTA1, pack_bf16(c0_[1], c0_[3]), pack_bf16(c1_[1], c1_[3]), rsb + CTA1);
        };
        auto tile = [&](float (&c)[4], int i, int k) {
          if (k == 0) mma16816z(c, wo[i][0], b0[0], b0[1]);
          else mma16816(c, wo[i][k], k < 2 ? b0[2 * k] : b1[2 * k - 4], k < 2 ? b0[2 * k + 1] : b1[2 * k - 3]);
        };
        {
          float c[4][4];
          mma16816z(c[0], wo[0][0], b0[0], b0[1]);
          mma16816z(c[1], wo[1][0], b0[0], b0[1]);
          mma16816z(c[2], wo[0][2], b1[0], b1[1]);
          mma16816z(c[3], wo[1][2], b1[0], b1[1]);
          mma16816(c[0], wo[0][1], b0[2], b0[3]);
          mma16816(c[1], wo[1][1], b0[2], b0[3]);
          mma16816(c[2], wo[0][3], b1[2], b1[3]);
          mma16816(c[3], wo[1][3], b1[2], b1[3]);
          pack_v();
#pragma unroll
          for (int i = 0; i < 4; i++) { c[0][i] += c[2][i]; c[1][i] += c[3][i]; }
          send(0, c[0], c[1]);
          fence_regs(vn);
        }
        sched_fence(rsb);
        TRB(13);
        {
          float c[3][4];
#pragma unroll
          for (int k = 0; k < 4; k++) { tile(c[0], 8, k); tile(c[1], 2, k); tile(c[2], 3, k); }
          st_async32(rsN, pack_bf16(c[0][0], c[0][2]), rsb);
          st_async32(rsN + CTA1, pack_bf16(c[0][1], c[0][3]), rsb + CTA1);
          send(1, c[1], c[2]);
        }
        sched_fence(la);
        {
          float c[4][4];
#pragma unroll
          for (int k = 0; k < 4; k++)
#pragma unroll
            for (int i = 0; i < 4; i++) tile(c[i], 4 + i, k);
          if (P3_EARLY == 1) { sched_fence(rsA); bar_arrive(NB_P3, 256); }
          send(2, c[0], c[1]);
          send(3, c[2], c[3]);
          if (P3_EARLY == 2) bar_arrive(NB_P3, 256);
        }
        TRB(12);
      } else {
        if (LAST) bar_sync(NB_PM, 160);
        wg_wait<0>();
        fence_regs(d);
        if (LAST) asm volatile("barrier.cluster.arrive.relaxed.aligned;" ::: "memory");
        vm0 = pack_bf16(d[16], d[17]);
        vm1 = pack_bf16(d[18], d[19]);
        pack_v();
      }
      if (FIRST) {
        asm volatile("barrier.cluster.wait.aligned;" ::: "memory");
        TRG(7);
      } else {
        float e[16];
#pragma unroll
        for (int i = 0; i < 16; i++) e[i] = 0.f;
        uint32_t z0 = 0, z1 = 0;
        asm volatile("" : "+r"(z0), "+r"(z1), "+r"(vm0), "+r"(vm1));
        const uint32_t pd = desc_lo(sb + R_PS + 1024, 16);
        fence_regs(vx);
        bar_sync(NB_PX, 192);
        wg_fence();
        wgmma_rs_n32_b0(e, vx[0], vx[1], vx[2], vx[3], mk_desc(pd, DHI_SW128), 0);
        wgmma_rs_n32_b0(e, vx[4], vx[5], vx[6], vx[7], mk_desc(pd + 2, DHI_SW128), 1);
        wgmma_rs_n32_b0(e, vm0, vm1, z0, z1, mk_desc(pd + 4, DHI_SW128), 1);
        wg_commit();
        if (!P3_EARLY && !LAST) bar_arrive(NB_P3, 256);
        wg_wait<0>();
        fence_regs(e);
        fence_regs(vx);
        bar_sync(NB_O, 128);
        stsm4t(wa + R_PS + 1024, pack_bf16(e[0], e[1]), pack_bf16(e[2], e[3]), pack_bf16(e[4], e[5]), pack_bf16(e[6], e[7]));
        stsm4t(wa + R_PS + 3072, pack_bf16(e[8], e[9]), pack_bf16(e[10], e[11]), pack_bf16(e[12], e[13]), pack_bf16(e[14], e[15]));
        TRB(14);
      }
      auto store_x = [&]() {
        fence_async_smem();
        if (w4 == 2) bar_sync(NB_O2, 128); else bar_arrive(NB_O2, 128);
        if (w4 == 2 && elect()) {
          asm volatile("cp.async.bulk.tensor.2d.global.shared::cta.bulk_group [%0, {%1,%2}], [%3];" ::"l"(&P.ox), "r"(c0), "r"(3 * SEQ + s * 32), "r"(sb + R_PS + 1024) : "memory");
          asm volatile("cp.async.bulk.commit_group;" ::: "memory");
        }
        __syncwarp();
      };
      if (MID) {
        const uint32_t tag = ((s >> 1) & 1) ^ 1;
        uint32_t* x = xb + (s & 1) * XCH_SLOT;
        uint32_t* xw = x + cl * XCH_CL;
        const int src = (ln & 7) + (ln >> 4) * 8, hf = (ln >> 3) & 1;
        const uint32_t ra = sb + R_RS + w4 * 2048 + src * 128 + ((hf ^ (ln & 7)) << 4);
        auto delay = [&](uint32_t t0) {
          while ((uint32_t)clock() - t0 < POLL_DELAY + w4 * POLL_STAG) {}
        };
        uint32_t rn;
        const uint32_t agb = sb0 + RB_MEM + 8 * w4 + (uint32_t)(ln >> 5);
        if (w4 == 3) {
          const int cn = 8 * (ln & 1) + (ln >> 2), no = 64 + 2 * (cn - ln);
          const uint32_t rb = sb + R_RS + 8192 + src * 64 + ((hf ^ ((ln >> 1) & 3)) << 4);
          mbar_wait(sb + RB_RS, s & 1);
          const uint2 o = xch_reduce<4>(ra, ln >> 3, xw, tag);
          const uint2 on = xch_reduce<2>(rb, hf, xw + no, tag);
          const uint32_t t0 = clock();
          bar_arrive(NB_RD, 256);
          TRW(27, 3);
          store_x();
          const uint32_t off = (ln & 2) * 4 * CTA1;
          const uint32_t agn = sb0 + R_HM + tok * 128 + hoff(8) + ((((rank >> 3) * 4 + (cn >> 2)) ^ tok) << 4) + (cn & 3) * 4;
          XSend<16, 6> xs(agd, agb);
          delay(t0);
          const uint32_t r = xch_poll<true>(x, cl, o, x + no, on, rn);
          TRW(28, 3);
          xs.send(r);
          XSend<8, 1>(agn ^ off, (agb + 8) ^ off).send(rn);
          TRW(22, 3);
        } else {
          mbar_wait(sb + RB_RS, s & 1);
          TRB(19);
          const uint2 o = xch_reduce<4>(ra, ln >> 3, xw, tag);
          const uint32_t t0 = clock();
          bar_arrive(NB_RD, 256);
          TRB(25);
          store_x();
          if (w4 == 1 && rank < 9 && s < 62 && elect()) {
            tma2d_mc(sb + R_H + hoff(rank) + (s & 1) * 5120, &P.x, rank * 64, (s + 2) * 32, sb + RB_XF + 8 * (s & 1), 0xffff);
            asm volatile("cp.async.bulk.prefetch.tensor.2d.L2.global [%0, {%1,%2}];" ::"l"(&P.x), "r"(rank * 64), "r"(min(s + 3 + cl, 63) * 32) : "memory");
          }
          __syncwarp();
          XSend<16, 12> xs(agd, agb);
          delay(t0);
          asm volatile("cp.async.bulk.wait_group.read 0;" ::: "memory");
          const uint32_t r = xch_poll<false>(x, cl, o, x, o, rn);
          TRB(26); TRW(10, 1); TRW(20, 2);
          xs.send(r);
          TRB(21); TRW(23, 1); TRW(24, 2);
          if (w4 == 2 && ((s & 3) == 3 || s == 61)) {
            asm volatile("cp.async.bulk.wait_group 0;" ::: "memory");
#if PUB_REL
            asm volatile("{.reg .pred q; elect.sync _|q, 0xffffffff; @q red.release.gpu.global.add.u32 [%0], 1;}" ::"l"(&g_sync[SY_OX + (s >> 2)]) : "memory");
#else
            asm volatile("{.reg .pred q; elect.sync _|q, 0xffffffff; @q red.relaxed.gpu.global.add.u32 [%0], 1;}" ::"l"(&g_sync[SY_OX + (s >> 2)]) : "memory");
#endif
          }
        }
      }
#pragma unroll
      for (int i = 0; i < 8; i++) vx[i] = vn[i];
    };
    TRG(5);
#pragma unroll 1
    for (int s = -1; s < 64; s++) {
      asm volatile("" : "+r"(wa), "+r"(la), "+r"(rsb), "+r"(rsA), "+r"(rsN), "+r"(agd), "+r"(ln), "+l"(xb));
      step(s);
    }
    if (threadIdx.x == 128) TRE(64 + blockIdx.x);
    fence_async_smem();
    bar_sync(NB_O2, 128);
    if (w4 == 2) {
      if (elect()) {
        asm volatile("cp.async.bulk.tensor.2d.global.shared::cta.bulk_group [%0, {%1,%2}], [%3];" ::"l"(&P.ox), "r"(c0), "r"(3 * SEQ + 63 * 32), "r"(sb + R_PS + 1024) : "memory");
        asm volatile("cp.async.bulk.commit_group;" ::: "memory");
        asm volatile("cp.async.bulk.wait_group 0;" ::: "memory");
#if PUB_REL
        asm volatile("red.release.gpu.global.add.u32 [%0], 1;" ::"l"(&g_sync[SY_OX + 16]) : "memory");
#else
        asm volatile("red.relaxed.gpu.global.add.u32 [%0], 1;" ::"l"(&g_sync[SY_OX + 16]) : "memory");
#endif
      }
      __syncwarp();
    } else {
      uint32_t* z = g_xch + XCH_SLOT + cl * XCH_CL + rank * 288 + (w4 == 3 ? 64 : w4 * 32) + ln;
      st_relaxed32(z, 0u); st_relaxed32(z + 96, 0u); st_relaxed32(z + 192, 0u);
    }
#ifdef DEV_TRACE
    bar_sync(NB_S, 256);
#endif
  }
  asm volatile("barrier.cluster.wait.aligned;\nbarrier.cluster.arrive.relaxed.aligned;" ::: "memory");
  {
    uint32_t rank, cl, sb, warp;
    asm volatile("mov.u32 %0, %%cluster_ctarank;" : "=r"(rank));
    asm volatile("{.reg .b32 t; mov.u32 t, %%ctaid.x; shr.u32 %0, t, 4;}" : "=r"(cl));
    asm volatile("{.reg .b64 t; cvta.to.shared.u64 t, %1; cvt.u32.u64 %0, t;}" : "=r"(sb) : "l"(smem_rmt));
    asm volatile("{.reg .b32 t; mov.u32 t, %%tid.x; shr.u32 t, t, 5; shfl.sync.idx.b32 %0, t, 0, 31, -1;}" : "=r"(warp));
    const int w4 = warp & 3;
    const int lane = threadIdx.x & 31, wg = warp >> 2, u = rank >> 1, blk = cl == 3 ? 12 + (rank & 1) : 14 + (rank & 1), nn = min(cl, 2u);
    constexpr int T_E = 40960, T_R = 4 * T_E;
    auto load_w = [&](int kb) {
      const uint32_t fb = sb + RB_TF + 8 * (kb & 3);
      mbar_expect(fb, 24576);
      tma3d_mc(sb + (kb & 3) * T_E + 16384 + (rank & 1) * 12288, &P.wo3, 0, u * 512 + kb * 64 + (rank & 1) * 32, nn * 3, fb, 3 << (rank & 14));
    };
    auto load_a = [&](int kb, int h) {
      const uint32_t fb = sb + RB_TF + 32 + 32 * h + 8 * (kb & 3);
      mbar_expect(fb, 8192);
      tma2d(sb + (kb & 3) * T_E + h * 8192, &P.ox64, u * 512 + kb * 64, 3 * SEQ + blk * 128 + h * 64, fb);
    };
    TRT(0, 0);
    if (w4 == 0 && elect()) {
#pragma unroll 1
      for (int kb = 4 * wg; kb < 4; kb++) load_w(kb);
      for (int it = 0; ld_acquire(g_sync + SY_OX + blk + (blk == 15 ? wg : 0)) < OX_TARGET; it++)
        if (it > (1 << 22)) __trap();
#pragma unroll 1
      for (int kb = 0; kb < 4; kb++) load_a(kb, wg);
    }
    __syncwarp();
    TRT(1, 4);
    float acc[96];
#pragma unroll
    for (int i = 0; i < 96; i++) acc[i] = 0.f;
    const uint32_t te = mapa(sb + RB_TE, (rank & 14) + (lane & 1));
#pragma unroll 1
    for (int kb = 0; kb < 8; kb++) {
      const uint32_t st = sb + (kb & 3) * T_E, a = desc_lo(st + wg * 8192, 16), b = desc_lo(st + 16384, 4096);
      mbar_wait2(sb + RB_TF + 8 * (kb & 3), kb >> 2, sb + RB_TF + 32 + 32 * wg + 8 * (kb & 3), kb >> 2);
      if (kb == 0) TRT(2, 4);
      wg_fence();
#pragma unroll
      for (int kk = 0; kk < 4; kk++) wgmma_ss_n192_a0b1(acc, mk_desc(a + kk * 2, DHI_SW128), mk_desc(b + (kk >> 1) * 768 + (kk & 1) * 128, DHI_SW128), 1);
      wg_commit();
      wg_wait<1>();
      if (kb >= 1 && kb <= 4) {
        if (w4 == 0 && lane < 2) mbar_arrive_cl(te + 8 * (kb - 1));
        if (warp == 4) {
          mbar_wait(sb + RB_TE + 8 * (kb - 1), 0);
          if (elect()) { load_w(kb + 3); load_a(kb + 3, 0); load_a(kb + 3, 1); }
        }
        __syncwarp();
      }
    }
    asm volatile("barrier.cluster.wait.aligned;" ::: "memory");
    wg_wait<0>();
    fence_regs(acc);
    TRT(3, 4);
    const uint32_t ra = mapa(sb + T_R + u * 6144 + ((lane ^ u) << 4), 2 * warp + (rank & 1)), rb = mapa(sb + RB_TR, 2 * warp + (rank & 1));
#pragma unroll
    for (int j = 0; j < 12; j++) {
      const int o = 16 * (j >> 1) + (j & 1);
      st_async128(ra + j * 512, pack_bf16(acc[o], acc[o + 2]), pack_bf16(acc[o + 4], acc[o + 6]), pack_bf16(acc[o + 8], acc[o + 10]), pack_bf16(acc[o + 12], acc[o + 14]), rb);
    }
    TRT(4, 4);
    const int r = lane & 7, m = lane >> 3, g = lane >> 2;
    const uint32_t la = sb + T_R + r * 6144 + wg * 3072 + (m >> 1) * 512;
    uint32_t* out = P.out + (blk * 128 + u * 16 + 2 * w4 + 8 * (g & 1)) * DM + DM / 2 + nn * 96 + wg * 48 + (g >> 1) * 4 + (lane & 3);
    mbar_wait(sb + RB_TR, 0);
    TRT(5, 0);
    asm volatile("barrier.cluster.arrive.relaxed.aligned;" ::: "memory");
#pragma unroll 1
    for (int J = 0; J < 3; J++) {
      float c[2][4];
      uint32_t v[4][4];
#pragma unroll
      for (int j = 0; j < 4; j++) ldsm4t(v[j], la + J * 1024 + (((8 * w4 + 4 * (m & 1) + j) ^ r) << 4));
#pragma unroll
      for (int j = 0; j < 4; j++) {
        const uint32_t b0 = g == 2 * j ? 0x3f803f80u : 0u, b1 = g == 2 * j + 1 ? 0x3f803f80u : 0u;
        if (j < 2) mma16816z(c[j], v[j], b0, b1);
        else mma16816(c[j & 1], v[j], b0, b1);
      }
      out[J * 16] = pack_bf16(c[0][0] + c[1][0], c[0][1] + c[1][1]);
      out[J * 16 + DM] = pack_bf16(c[0][2] + c[1][2], c[0][3] + c[1][3]);
    }
    TRT(6, 0);
    if (warp == 0) TRG(6);
    asm volatile("barrier.cluster.wait.aligned;" ::: "memory");
  }
  if (threadIdx.x == 96) TRE(128 + blockIdx.x);
}

void rmt_setup() {
  cudaFuncSetAttribute(rmt_kernel, cudaFuncAttributeMaxDynamicSharedMemorySize, R_SMEM);
  cudaFuncSetAttribute(rmt_kernel, cudaFuncAttributeNonPortableClusterSizeAllowed, 1);
}
void rmt_launch(EncodeFn enc, void* const* d_in, void* scr, void* out) {
  RmtParams R;
  map2d(enc, &R.wq, d_in[8], DM, HDALL, 16);
  map2d(enc, &R.wk, d_in[9], DM, HDALL, 16);
  map2d(enc, &R.wv, d_in[10], DM, HDALL, 16);
  map2d(enc, &R.wo, d_in[11], HDALL, DM, 64);
  map2d(enc, &R.x, d_in[6], SEQ, DM, 32);
  map2d(enc, &R.mem, d_in[7], 8, DM, 8);
  map2d(enc, &R.ox, scr, 4 * SEQ, HDALL, 32);
  cudaLaunchConfig_t cfg = {};
  map2d(enc, &R.ox64, scr, 4 * SEQ, HDALL, 64);
  map3d(enc, &R.wo3, d_in[11], HDALL, DM, 32, 3);
  R.out = (uint32_t*)out;
  R.ckv = (const __nv_bfloat16*)d_in[1]; R.wuk = (const __nv_bfloat16*)d_in[3]; R.wuv = (const __nv_bfloat16*)d_in[4];
  cfg.gridDim = dim3(64);
  cfg.blockDim = dim3(256);
  cfg.dynamicSmemBytes = R_SMEM;
  cfg.stream = cudaStreamPerThread;
  cudaLaunchAttribute at[1];
  at[0].id = cudaLaunchAttributeClusterDimension;
  at[0].val.clusterDim.x = 16;
  at[0].val.clusterDim.y = 1;
  at[0].val.clusterDim.z = 1;
  cfg.attrs = at;
  cfg.numAttrs = 1;
  cudaLaunchKernelEx(&cfg, rmt_kernel, R);
}


const uint16_t h_order[] = {
    4096, 4097, 34, 35, 36, 37, 38, 39, 40, 41, 42, 43, 44, 45, 46, 47, 48, 49, 50, 51,
    52, 53, 54, 55, 56, 57, 58, 59, 60, 61, 62, 63, 64, 65, 66, 67, 68, 69, 70, 71,
    4103, 4102, 4101, 4100, 4099, 4098, 72, 73, 74, 75, 76, 77, 78, 79, 4111, 4110, 4109, 4108, 4107, 4106,
    80, 81, 82, 83, 84, 85, 86, 87, 4119, 4118, 4117, 4116, 4115, 4114, 88, 89, 90, 91, 92, 93,
    94, 95, 4127, 4126, 4125, 4124, 4123, 4122, 96, 97, 98, 99, 100, 101, 102, 103, 4135, 4134, 4133, 4132,
    4131, 4130, 104, 105, 106, 107, 108, 109, 110, 111, 4143, 4142, 4141, 4140, 4139, 4138, 112, 113, 114, 115,
    116, 117, 118, 119, 4151, 4150, 4149, 4148, 4147, 4146, 120, 121, 122, 123, 124, 125, 126, 127, 4159, 4158,
    4157, 4156, 4155, 4154, 128, 129, 130, 131, 132, 133, 134, 135, 4167, 4166, 4165, 4164, 4163, 4162, 136, 137,
    138, 12288, 12544, 12800, 139, 140, 141, 142, 143, 4175, 4174, 4173, 4172, 4171, 4170, 144, 145, 146, 147, 148,
    149, 150, 151, 4183, 4182, 4181, 4180, 4179, 4178, 152, 153, 154, 155, 156, 157, 158, 12289, 12545, 12801, 159,
    4191, 4190, 4189, 4188, 4187, 4186, 160, 161, 162, 163, 164, 165, 166, 167, 4199, 4198, 4197, 4196, 4195, 4194,
    168, 169, 170, 171, 172, 173, 174, 175, 4207, 4206, 4205, 4204, 4203, 4202, 176, 177, 178, 179, 180, 181,
    182, 183, 4215, 4214, 4213, 12290, 12546, 12802, 4212, 4211, 4210, 184, 185, 186, 187, 188, 189, 190, 191, 4223,
    4222, 4221, 4220, 4219, 4218, 192, 193, 194, 195, 196, 197, 198, 199, 4231, 4230, 4229, 4228, 4227, 4226, 200,
    201, 202, 203, 204, 205, 206, 207, 4239, 4238, 4237, 4236, 4235, 4234, 208, 209, 210, 211, 212, 213, 214,
    215, 4247, 4246, 4245, 4244, 4243, 4242, 216, 217, 218, 219, 220, 221, 222, 12291, 12547, 12803, 223, 4255, 4254,
    4253, 4252, 4251, 4250, 224, 225, 226, 227, 228, 229, 230, 231, 4263, 4262, 4261, 4260, 4259, 4258, 232, 233,
    234, 235, 236, 237, 238, 239, 4271, 4270, 4269, 4268, 4267, 4266, 240, 241, 242, 243, 244, 245, 246, 247,
    4279, 4278, 4277, 4276, 4275, 4274, 248, 249, 250, 251, 252, 253, 254, 255, 4287, 4286, 4285, 4284, 4283, 4282,
    4295, 4294, 4293, 4292, 4291, 4290, 4303, 4302, 4301, 4300, 4299, 4298, 4311, 4310, 4309, 4308, 4307, 4306, 4319, 4318,
    4317, 4316, 4315, 4314, 4327, 8194, 8450, 8706, 4326, 12292, 12548, 12804, 4325, 4324, 4323, 4322, 4335, 4334, 4333, 4332,
    4331, 4330, 4343, 4342, 4341, 4340, 4339, 4338, 4351, 4350, 4349, 4348, 4347, 4346, 4105, 4104, 4113, 4112, 4121, 4120,
    4129, 4128, 4137, 4136, 4145, 4144, 4153, 4152, 8197, 8453, 8709, 4161, 4160, 4169, 4168, 4177, 4176, 4185, 4184, 4193,
    4192, 4201, 4200, 4209, 4208, 4217, 4216, 4225, 4224, 4233, 4232, 12293, 12549, 12805, 4241, 4240, 8199, 8455, 8711, 4249,
    8196, 8452, 8708, 8195, 8451, 8707, 8193, 8449, 8705, 8198, 8454, 8710, 4248, 8192, 8448, 8704, 4257, 4256, 4265, 4264,
    4273, 4272, 4281, 4280, 4289, 4288, 4297, 20486, 20742, 20998, 4296, 4305, 4304, 4313, 4312, 4321, 4320, 4329, 4328, 4337,
    4336, 4345, 4344,
};
int build_tasks(uint16_t* t) {
  int n = 0;
#ifdef DEV_ORDER
  if (const char* fn = getenv("ORDER")) {
    FILE* f = fopen(fn, "r");
    int v;
    while (fscanf(f, "%d", &v) == 1) t[n++] = v;
    fclose(f);
    return n;
  }
#endif
  static_assert(sizeof(h_order) / 2 <= MAXTASK, "tasks");
  for (; n < (int)(sizeof(h_order) / 2); n++) t[n] = h_order[n];
  return n;
}

}

extern "C" void kernel_launch(void* const* d_in, const int* in_sizes, int n_in, void* d_out, int out_size) {
  (void)in_sizes; (void)n_in; (void)out_size;
  static EncodeFn enc = nullptr;
  static void* scr = nullptr;
  if (!enc) {
    cudaDriverEntryPointQueryResult q;
    cudaGetDriverEntryPoint("cuTensorMapEncodeTiled", (void**)&enc, cudaEnableDefault, &q);
    cudaGetSymbolAddress(&scr, g_scr);
    cudaFuncSetAttribute(main_kernel, cudaFuncAttributeMaxDynamicSharedMemorySize, M_SMEM);
    rmt_setup();
  }
  rmt_launch(enc, d_in, scr, d_out);

  MainParams P;
  map2d(enc, &P.ckv, d_in[1], SEQ, 512, 128);
  map3d(enc, &P.wuk, d_in[3], 512, HDALL, 64, 2);
  map3d(enc, &P.wuv, d_in[4], 512, HDALL, 64, 2);
  map2d(enc, &P.ax, d_in[0], SEQ, DM, 64);
  map2d(enc, &P.wq, d_in[2], DM, HDALL, 64);
  map2d(enc, &P.scr, scr, 4 * SEQ, HDALL, 128);
  map3d(enc, &P.woa, d_in[5], HDALL, DM, 32, 3);
  map3d(enc, &P.wob, d_in[11], HDALL, DM, 32, 3);
  map2d(enc, &P.scr_st, scr, 4 * SEQ, HDALL, ST_ROWS);
  map2d(enc, &P.out_st, d_out, SEQ, 2 * DM, ST_ROWS);
  map3d(enc, &P.woa2, d_in[5], HDALL, DM, 32, 2);
  map3d(enc, &P.wob2, d_in[11], HDALL, DM, 32, 2);
  P.ntask = build_tasks(P.tasks);

  cudaLaunchConfig_t cfg = {};
  cfg.gridDim = dim3(2 * NCL);
  cfg.blockDim = dim3(384);
  cfg.dynamicSmemBytes = M_SMEM;
  cfg.stream = cudaStreamPerThread;
  cudaLaunchAttribute at[1];
  at[0].id = cudaLaunchAttributeProgrammaticStreamSerialization;
  at[0].val.programmaticStreamSerializationAllowed = 1;
  cfg.attrs = at;
  cfg.numAttrs = 1;
#ifdef DEV_SERIAL
  cfg.numAttrs = 0;
#endif
  cudaLaunchKernelEx(&cfg, main_kernel, P);
}
```

```cpp
#include <cuda_runtime.h>
#include <cuda_bf16.h>
#include <cuda.h>
#include <stdint.h>
#ifdef DEV_ORDER
#include <stdio.h>
#include <stdlib.h>
#endif

namespace {

constexpr int SEQ = 2048, DM = 576, HDALL = 4096;

__device__ __nv_bfloat16 g_scr[4ull * SEQ * HDALL];
constexpr int SY_Q = 0, SY_EXIT = 16, SY_KV = 32, SY_CTX = 32 + 256, SY_OX = 32 + 512, SY_N = 32 + 512 + 32;
__device__ unsigned g_sync[SY_N];

#ifdef DEV_END
__device__ long long g_end[1024];
#define TRE(i) do { long long c_; asm volatile("mov.u64 %0, %%globaltimer;" : "=l"(c_)); g_end[i] = c_; g_end[512 + (i)] = clock64(); } while (0)
#else
#define TRE(i)
#endif
#ifdef DEV_TRACE
__device__ long long g_trace[132 * 4096];
#ifdef DEV_TRF
#define TRF(slot) do { if (w4 == 0 && ti < 60) { uint32_t c_; asm volatile("mov.u32 %0, %%clock;" : "=r"(c_)::"memory"); if (elect()) g_trace[blockIdx.x * 4096 + 2048 + ti * 32 + wg * 16 + (slot)] = c_; __syncwarp(); } } while (0)
#else
#define TRF(slot)
#endif
#ifdef DEV_TRK
#define TRK(slot) do { if (w4 == 0 && ti < 60) { uint32_t c_; asm volatile("mov.u32 %0, %%clock;" : "=r"(c_)::"memory"); if (elect()) g_trace[blockIdx.x * 4096 + 2048 + ti * 32 + wg * 16 + (slot)] = c_; __syncwarp(); } } while (0)
#else
#define TRK(slot)
#endif
#define TRM(slot) do { if ((threadIdx.x & 31) == 0) { long long c_; asm volatile("mov.u64 %0, %%globaltimer;" : "=l"(c_)); g_trace[blockIdx.x * 4096 + 4080 + (slot)] = c_; } } while (0)
#else
#define TRM(slot)
#define TRF(slot)
#define TRK(slot)
#endif

__device__ __forceinline__ void wgmma_ss_n256_a0b1(float (&d)[128], uint64_t da, uint64_t db, int sc) {
  asm volatile("{.reg .pred p; setp.ne.b32 p, %130, 0; wgmma.mma_async.sync.aligned.m64n256k16.f32.bf16.bf16 {%0,%1,%2,%3,%4,%5,%6,%7,%8,%9,%10,%11,%12,%13,%14,%15,%16,%17,%18,%19,%20,%21,%22,%23,%24,%25,%26,%27,%28,%29,%30,%31,%32,%33,%34,%35,%36,%37,%38,%39,%40,%41,%42,%43,%44,%45,%46,%47,%48,%49,%50,%51,%52,%53,%54,%55,%56,%57,%58,%59,%60,%61,%62,%63,%64,%65,%66,%67,%68,%69,%70,%71,%72,%73,%74,%75,%76,%77,%78,%79,%80,%81,%82,%83,%84,%85,%86,%87,%88,%89,%90,%91,%92,%93,%94,%95,%96,%97,%98,%99,%100,%101,%102,%103,%104,%105,%106,%107,%108,%109,%110,%111,%112,%113,%114,%115,%116,%117,%118,%119,%120,%121,%122,%123,%124,%125,%126,%127}, %128, %129, p, 1, 1, 0, 1;}"
    : "+f"(d[0]),"+f"(d[1]),"+f"(d[2]),"+f"(d[3]),"+f"(d[4]),"+f"(d[5]),"+f"(d[6]),"+f"(d[7]),"+f"(d[8]),"+f"(d[9]),"+f"(d[10]),"+f"(d[11]),"+f"(d[12]),"+f"(d[13]),"+f"(d[14]),"+f"(d[15]),"+f"(d[16]),"+f"(d[17]),"+f"(d[18]),"+f"(d[19]),"+f"(d[20]),"+f"(d[21]),"+f"(d[22]),"+f"(d[23]),"+f"(d[24]),"+f"(d[25]),"+f"(d[26]),"+f"(d[27]),"+f"(d[28]),"+f"(d[29]),"+f"(d[30]),"+f"(d[31]),"+f"(d[32]),"+f"(d[33]),"+f"(d[34]),"+f"(d[35]),"+f"(d[36]),"+f"(d[37]),"+f"(d[38]),"+f"(d[39]),"+f"(d[40]),"+f"(d[41]),"+f"(d[42]),"+f"(d[43]),"+f"(d[44]),"+f"(d[45]),"+f"(d[46]),"+f"(d[47]),"+f"(d[48]),"+f"(d[49]),"+f"(d[50]),"+f"(d[51]),"+f"(d[52]),"+f"(d[53]),"+f"(d[54]),"+f"(d[55]),"+f"(d[56]),"+f"(d[57]),"+f"(d[58]),"+f"(d[59]),"+f"(d[60]),"+f"(d[61]),"+f"(d[62]),"+f"(d[63]),"+f"(d[64]),"+f"(d[65]),"+f"(d[66]),"+f"(d[67]),"+f"(d[68]),"+f"(d[69]),"+f"(d[70]),"+f"(d[71]),"+f"(d[72]),"+f"(d[73]),"+f"(d[74]),"+f"(d[75]),"+f"(d[76]),"+f"(d[77]),"+f"(d[78]),"+f"(d[79]),"+f"(d[80]),"+f"(d[81]),"+f"(d[82]),"+f"(d[83]),"+f"(d[84]),"+f"(d[85]),"+f"(d[86]),"+f"(d[87]),"+f"(d[88]),"+f"(d[89]),"+f"(d[90]),"+f"(d[91]),"+f"(d[92]),"+f"(d[93]),"+f"(d[94]),"+f"(d[95]),"+f"(d[96]),"+f"(d[97]),"+f"(d[98]),"+f"(d[99]),"+f"(d[100]),"+f"(d[101]),"+f"(d[102]),"+f"(d[103]),"+f"(d[104]),"+f"(d[105]),"+f"(d[106]),"+f"(d[107]),"+f"(d[108]),"+f"(d[109]),"+f"(d[110]),"+f"(d[111]),"+f"(d[112]),"+f"(d[113]),"+f"(d[114]),"+f"(d[115]),"+f"(d[116]),"+f"(d[117]),"+f"(d[118]),"+f"(d[119]),"+f"(d[120]),"+f"(d[121]),"+f"(d[122]),"+f"(d[123]),"+f"(d[124]),"+f"(d[125]),"+f"(d[126]),"+f"(d[127])
    : "l"(da), "l"(db), "r"(sc));
}
__device__ __forceinline__ void wgmma_ss_n192_a0b1(float (&d)[96], uint64_t da, uint64_t db, int sc) {
  asm volatile("{.reg .pred p; setp.ne.b32 p, %98, 0; wgmma.mma_async.sync.aligned.m64n192k16.f32.bf16.bf16 {%0,%1,%2,%3,%4,%5,%6,%7,%8,%9,%10,%11,%12,%13,%14,%15,%16,%17,%18,%19,%20,%21,%22,%23,%24,%25,%26,%27,%28,%29,%30,%31,%32,%33,%34,%35,%36,%37,%38,%39,%40,%41,%42,%43,%44,%45,%46,%47,%48,%49,%50,%51,%52,%53,%54,%55,%56,%57,%58,%59,%60,%61,%62,%63,%64,%65,%66,%67,%68,%69,%70,%71,%72,%73,%74,%75,%76,%77,%78,%79,%80,%81,%82,%83,%84,%85,%86,%87,%88,%89,%90,%91,%92,%93,%94,%95}, %96, %97, p, 1, 1, 0, 1;}"
    : "+f"(d[0]),"+f"(d[1]),"+f"(d[2]),"+f"(d[3]),"+f"(d[4]),"+f"(d[5]),"+f"(d[6]),"+f"(d[7]),"+f"(d[8]),"+f"(d[9]),"+f"(d[10]),"+f"(d[11]),"+f"(d[12]),"+f"(d[13]),"+f"(d[14]),"+f"(d[15]),"+f"(d[16]),"+f"(d[17]),"+f"(d[18]),"+f"(d[19]),"+f"(d[20]),"+f"(d[21]),"+f"(d[22]),"+f"(d[23]),"+f"(d[24]),"+f"(d[25]),"+f"(d[26]),"+f"(d[27]),"+f"(d[28]),"+f"(d[29]),"+f"(d[30]),"+f"(d[31]),"+f"(d[32]),"+f"(d[33]),"+f"(d[34]),"+f"(d[35]),"+f"(d[36]),"+f"(d[37]),"+f"(d[38]),"+f"(d[39]),"+f"(d[40]),"+f"(d[41]),"+f"(d[42]),"+f"(d[43]),"+f"(d[44]),"+f"(d[45]),"+f"(d[46]),"+f"(d[47]),"+f"(d[48]),"+f"(d[49]),"+f"(d[50]),"+f"(d[51]),"+f"(d[52]),"+f"(d[53]),"+f"(d[54]),"+f"(d[55]),"+f"(d[56]),"+f"(d[57]),"+f"(d[58]),"+f"(d[59]),"+f"(d[60]),"+f"(d[61]),"+f"(d[62]),"+f"(d[63]),"+f"(d[64]),"+f"(d[65]),"+f"(d[66]),"+f"(d[67]),"+f"(d[68]),"+f"(d[69]),"+f"(d[70]),"+f"(d[71]),"+f"(d[72]),"+f"(d[73]),"+f"(d[74]),"+f"(d[75]),"+f"(d[76]),"+f"(d[77]),"+f"(d[78]),"+f"(d[79]),"+f"(d[80]),"+f"(d[81]),"+f"(d[82]),"+f"(d[83]),"+f"(d[84]),"+f"(d[85]),"+f"(d[86]),"+f"(d[87]),"+f"(d[88]),"+f"(d[89]),"+f"(d[90]),"+f"(d[91]),"+f"(d[92]),"+f"(d[93]),"+f"(d[94]),"+f"(d[95])
    : "l"(da), "l"(db), "r"(sc));
}
__device__ __forceinline__ void wgmma_rs_n64_b0(float (&d)[32], uint32_t a0, uint32_t a1, uint32_t a2, uint32_t a3, uint64_t db, int sc) {
  asm volatile("{.reg .pred p; setp.ne.b32 p, %37, 0; wgmma.mma_async.sync.aligned.m64n64k16.f32.bf16.bf16 {%0,%1,%2,%3,%4,%5,%6,%7,%8,%9,%10,%11,%12,%13,%14,%15,%16,%17,%18,%19,%20,%21,%22,%23,%24,%25,%26,%27,%28,%29,%30,%31}, {%32,%33,%34,%35}, %36, p, 1, 1, 0;}"
    : "+f"(d[0]),"+f"(d[1]),"+f"(d[2]),"+f"(d[3]),"+f"(d[4]),"+f"(d[5]),"+f"(d[6]),"+f"(d[7]),"+f"(d[8]),"+f"(d[9]),"+f"(d[10]),"+f"(d[11]),"+f"(d[12]),"+f"(d[13]),"+f"(d[14]),"+f"(d[15]),"+f"(d[16]),"+f"(d[17]),"+f"(d[18]),"+f"(d[19]),"+f"(d[20]),"+f"(d[21]),"+f"(d[22]),"+f"(d[23]),"+f"(d[24]),"+f"(d[25]),"+f"(d[26]),"+f"(d[27]),"+f"(d[28]),"+f"(d[29]),"+f"(d[30]),"+f"(d[31])
    : "r"(a0), "r"(a1), "r"(a2), "r"(a3), "l"(db), "r"(sc));
}
__device__ __forceinline__ void wgmma_ss_n128_a0b1(float (&d)[64], uint64_t da, uint64_t db, int sc) {
  asm volatile("{.reg .pred p; setp.ne.b32 p, %66, 0; wgmma.mma_async.sync.aligned.m64n128k16.f32.bf16.bf16 {%0,%1,%2,%3,%4,%5,%6,%7,%8,%9,%10,%11,%12,%13,%14,%15,%16,%17,%18,%19,%20,%21,%22,%23,%24,%25,%26,%27,%28,%29,%30,%31,%32,%33,%34,%35,%36,%37,%38,%39,%40,%41,%42,%43,%44,%45,%46,%47,%48,%49,%50,%51,%52,%53,%54,%55,%56,%57,%58,%59,%60,%61,%62,%63}, %64, %65, p, 1, 1, 0, 1;}"
    : "+f"(d[0]),"+f"(d[1]),"+f"(d[2]),"+f"(d[3]),"+f"(d[4]),"+f"(d[5]),"+f"(d[6]),"+f"(d[7]),"+f"(d[8]),"+f"(d[9]),"+f"(d[10]),"+f"(d[11]),"+f"(d[12]),"+f"(d[13]),"+f"(d[14]),"+f"(d[15]),"+f"(d[16]),"+f"(d[17]),"+f"(d[18]),"+f"(d[19]),"+f"(d[20]),"+f"(d[21]),"+f"(d[22]),"+f"(d[23]),"+f"(d[24]),"+f"(d[25]),"+f"(d[26]),"+f"(d[27]),"+f"(d[28]),"+f"(d[29]),"+f"(d[30]),"+f"(d[31]),"+f"(d[32]),"+f"(d[33]),"+f"(d[34]),"+f"(d[35]),"+f"(d[36]),"+f"(d[37]),"+f"(d[38]),"+f"(d[39]),"+f"(d[40]),"+f"(d[41]),"+f"(d[42]),"+f"(d[43]),"+f"(d[44]),"+f"(d[45]),"+f"(d[46]),"+f"(d[47]),"+f"(d[48]),"+f"(d[49]),"+f"(d[50]),"+f"(d[51]),"+f"(d[52]),"+f"(d[53]),"+f"(d[54]),"+f"(d[55]),"+f"(d[56]),"+f"(d[57]),"+f"(d[58]),"+f"(d[59]),"+f"(d[60]),"+f"(d[61]),"+f"(d[62]),"+f"(d[63])
    : "l"(da), "l"(db), "r"(sc));
}
__device__ __forceinline__ void wgmma_rs_n128_b0(float (&d)[64], uint32_t a0, uint32_t a1, uint32_t a2, uint32_t a3, uint64_t db, int sc) {
  asm volatile("{.reg .pred p; setp.ne.b32 p, %69, 0; wgmma.mma_async.sync.aligned.m64n128k16.f32.bf16.bf16 {%0,%1,%2,%3,%4,%5,%6,%7,%8,%9,%10,%11,%12,%13,%14,%15,%16,%17,%18,%19,%20,%21,%22,%23,%24,%25,%26,%27,%28,%29,%30,%31,%32,%33,%34,%35,%36,%37,%38,%39,%40,%41,%42,%43,%44,%45,%46,%47,%48,%49,%50,%51,%52,%53,%54,%55,%56,%57,%58,%59,%60,%61,%62,%63}, {%64,%65,%66,%67}, %68, p, 1, 1, 0;}"
    : "+f"(d[0]),"+f"(d[1]),"+f"(d[2]),"+f"(d[3]),"+f"(d[4]),"+f"(d[5]),"+f"(d[6]),"+f"(d[7]),"+f"(d[8]),"+f"(d[9]),"+f"(d[10]),"+f"(d[11]),"+f"(d[12]),"+f"(d[13]),"+f"(d[14]),"+f"(d[15]),"+f"(d[16]),"+f"(d[17]),"+f"(d[18]),"+f"(d[19]),"+f"(d[20]),"+f"(d[21]),"+f"(d[22]),"+f"(d[23]),"+f"(d[24]),"+f"(d[25]),"+f"(d[26]),"+f"(d[27]),"+f"(d[28]),"+f"(d[29]),"+f"(d[30]),"+f"(d[31]),"+f"(d[32]),"+f"(d[33]),"+f"(d[34]),"+f"(d[35]),"+f"(d[36]),"+f"(d[37]),"+f"(d[38]),"+f"(d[39]),"+f"(d[40]),"+f"(d[41]),"+f"(d[42]),"+f"(d[43]),"+f"(d[44]),"+f"(d[45]),"+f"(d[46]),"+f"(d[47]),"+f"(d[48]),"+f"(d[49]),"+f"(d[50]),"+f"(d[51]),"+f"(d[52]),"+f"(d[53]),"+f"(d[54]),"+f"(d[55]),"+f"(d[56]),"+f"(d[57]),"+f"(d[58]),"+f"(d[59]),"+f"(d[60]),"+f"(d[61]),"+f"(d[62]),"+f"(d[63])
    : "r"(a0), "r"(a1), "r"(a2), "r"(a3), "l"(db), "r"(sc));
}
__device__ __forceinline__ void wgmma_rs_n128_b1(float (&d)[64], uint32_t a0, uint32_t a1, uint32_t a2, uint32_t a3, uint64_t db, int sc) {
  asm volatile("{.reg .pred p; setp.ne.b32 p, %69, 0; wgmma.mma_async.sync.aligned.m64n128k16.f32.bf16.bf16 {%0,%1,%2,%3,%4,%5,%6,%7,%8,%9,%10,%11,%12,%13,%14,%15,%16,%17,%18,%19,%20,%21,%22,%23,%24,%25,%26,%27,%28,%29,%30,%31,%32,%33,%34,%35,%36,%37,%38,%39,%40,%41,%42,%43,%44,%45,%46,%47,%48,%49,%50,%51,%52,%53,%54,%55,%56,%57,%58,%59,%60,%61,%62,%63}, {%64,%65,%66,%67}, %68, p, 1, 1, 1;}"
    : "+f"(d[0]),"+f"(d[1]),"+f"(d[2]),"+f"(d[3]),"+f"(d[4]),"+f"(d[5]),"+f"(d[6]),"+f"(d[7]),"+f"(d[8]),"+f"(d[9]),"+f"(d[10]),"+f"(d[11]),"+f"(d[12]),"+f"(d[13]),"+f"(d[14]),"+f"(d[15]),"+f"(d[16]),"+f"(d[17]),"+f"(d[18]),"+f"(d[19]),"+f"(d[20]),"+f"(d[21]),"+f"(d[22]),"+f"(d[23]),"+f"(d[24]),"+f"(d[25]),"+f"(d[26]),"+f"(d[27]),"+f"(d[28]),"+f"(d[29]),"+f"(d[30]),"+f"(d[31]),"+f"(d[32]),"+f"(d[33]),"+f"(d[34]),"+f"(d[35]),"+f"(d[36]),"+f"(d[37]),"+f"(d[38]),"+f"(d[39]),"+f"(d[40]),"+f"(d[41]),"+f"(d[42]),"+f"(d[43]),"+f"(d[44]),"+f"(d[45]),"+f"(d[46]),"+f"(d[47]),"+f"(d[48]),"+f"(d[49]),"+f"(d[50]),"+f"(d[51]),"+f"(d[52]),"+f"(d[53]),"+f"(d[54]),"+f"(d[55]),"+f"(d[56]),"+f"(d[57]),"+f"(d[58]),"+f"(d[59]),"+f"(d[60]),"+f"(d[61]),"+f"(d[62]),"+f"(d[63])
    : "r"(a0), "r"(a1), "r"(a2), "r"(a3), "l"(db), "r"(sc));
}
__device__ __forceinline__ void wgmma_rs_n32_b0(float (&d)[16], uint32_t a0, uint32_t a1, uint32_t a2, uint32_t a3, uint64_t db, int sc) {
  asm volatile("{.reg .pred p; setp.ne.b32 p, %21, 0; wgmma.mma_async.sync.aligned.m64n32k16.f32.bf16.bf16 {%0,%1,%2,%3,%4,%5,%6,%7,%8,%9,%10,%11,%12,%13,%14,%15}, {%16,%17,%18,%19}, %20, p, 1, 1, 0;}"
    : "+f"(d[0]),"+f"(d[1]),"+f"(d[2]),"+f"(d[3]),"+f"(d[4]),"+f"(d[5]),"+f"(d[6]),"+f"(d[7]),"+f"(d[8]),"+f"(d[9]),"+f"(d[10]),"+f"(d[11]),"+f"(d[12]),"+f"(d[13]),"+f"(d[14]),"+f"(d[15])
    : "r"(a0), "r"(a1), "r"(a2), "r"(a3), "l"(db), "r"(sc));
}
__device__ __forceinline__ void wgmma_ss_n32_a1b0(float (&d)[16], uint64_t da, uint64_t db, int sc) {
  asm volatile("{.reg .pred p; setp.ne.b32 p, %18, 0; wgmma.mma_async.sync.aligned.m64n32k16.f32.bf16.bf16 {%0,%1,%2,%3,%4,%5,%6,%7,%8,%9,%10,%11,%12,%13,%14,%15}, %16, %17, p, 1, 1, 1, 0;}"
    : "+f"(d[0]),"+f"(d[1]),"+f"(d[2]),"+f"(d[3]),"+f"(d[4]),"+f"(d[5]),"+f"(d[6]),"+f"(d[7]),"+f"(d[8]),"+f"(d[9]),"+f"(d[10]),"+f"(d[11]),"+f"(d[12]),"+f"(d[13]),"+f"(d[14]),"+f"(d[15])
    : "l"(da), "l"(db), "r"(sc));
}
__device__ __forceinline__ void wgmma_ss_n40_a1b0(float (&d)[20], uint64_t da, uint64_t db, int sc) {
  asm volatile("{.reg .pred p; setp.ne.b32 p, %22, 0; wgmma.mma_async.sync.aligned.m64n40k16.f32.bf16.bf16 {%0,%1,%2,%3,%4,%5,%6,%7,%8,%9,%10,%11,%12,%13,%14,%15,%16,%17,%18,%19}, %20, %21, p, 1, 1, 1, 0;}"
    : "+f"(d[0]),"+f"(d[1]),"+f"(d[2]),"+f"(d[3]),"+f"(d[4]),"+f"(d[5]),"+f"(d[6]),"+f"(d[7]),"+f"(d[8]),"+f"(d[9]),"+f"(d[10]),"+f"(d[11]),"+f"(d[12]),"+f"(d[13]),"+f"(d[14]),"+f"(d[15]),"+f"(d[16]),"+f"(d[17]),"+f"(d[18]),"+f"(d[19])
    : "l"(da), "l"(db), "r"(sc));
}
__device__ __forceinline__ void wgmma_ss_n40_a1b1(float (&d)[20], uint64_t da, uint64_t db, int sc) {
  asm volatile("{.reg .pred p; setp.ne.b32 p, %22, 0; wgmma.mma_async.sync.aligned.m64n40k16.f32.bf16.bf16 {%0,%1,%2,%3,%4,%5,%6,%7,%8,%9,%10,%11,%12,%13,%14,%15,%16,%17,%18,%19}, %20, %21, p, 1, 1, 1, 1;}"
    : "+f"(d[0]),"+f"(d[1]),"+f"(d[2]),"+f"(d[3]),"+f"(d[4]),"+f"(d[5]),"+f"(d[6]),"+f"(d[7]),"+f"(d[8]),"+f"(d[9]),"+f"(d[10]),"+f"(d[11]),"+f"(d[12]),"+f"(d[13]),"+f"(d[14]),"+f"(d[15]),"+f"(d[16]),"+f"(d[17]),"+f"(d[18]),"+f"(d[19])
    : "l"(da), "l"(db), "r"(sc));
}
__device__ __forceinline__ void wgmma_rs_n40_b0(float (&d)[20], uint32_t a0, uint32_t a1, uint32_t a2, uint32_t a3, uint64_t db, int sc) {
  asm volatile("{.reg .pred p; setp.ne.b32 p, %25, 0; wgmma.mma_async.sync.aligned.m64n40k16.f32.bf16.bf16 {%0,%1,%2,%3,%4,%5,%6,%7,%8,%9,%10,%11,%12,%13,%14,%15,%16,%17,%18,%19}, {%20,%21,%22,%23}, %24, p, 1, 1, 0;}"
    : "+f"(d[0]),"+f"(d[1]),"+f"(d[2]),"+f"(d[3]),"+f"(d[4]),"+f"(d[5]),"+f"(d[6]),"+f"(d[7]),"+f"(d[8]),"+f"(d[9]),"+f"(d[10]),"+f"(d[11]),"+f"(d[12]),"+f"(d[13]),"+f"(d[14]),"+f"(d[15]),"+f"(d[16]),"+f"(d[17]),"+f"(d[18]),"+f"(d[19])
    : "r"(a0), "r"(a1), "r"(a2), "r"(a3), "l"(db), "r"(sc));
}
__device__ __forceinline__ void wgmma_ssz_n256_a0b1(float (&d)[128], uint64_t da, uint64_t db) {
  asm volatile("{.reg .pred p; setp.ne.b32 p, 0, 0; wgmma.mma_async.sync.aligned.m64n256k16.f32.bf16.bf16 {%0,%1,%2,%3,%4,%5,%6,%7,%8,%9,%10,%11,%12,%13,%14,%15,%16,%17,%18,%19,%20,%21,%22,%23,%24,%25,%26,%27,%28,%29,%30,%31,%32,%33,%34,%35,%36,%37,%38,%39,%40,%41,%42,%43,%44,%45,%46,%47,%48,%49,%50,%51,%52,%53,%54,%55,%56,%57,%58,%59,%60,%61,%62,%63,%64,%65,%66,%67,%68,%69,%70,%71,%72,%73,%74,%75,%76,%77,%78,%79,%80,%81,%82,%83,%84,%85,%86,%87,%88,%89,%90,%91,%92,%93,%94,%95,%96,%97,%98,%99,%100,%101,%102,%103,%104,%105,%106,%107,%108,%109,%110,%111,%112,%113,%114,%115,%116,%117,%118,%119,%120,%121,%122,%123,%124,%125,%126,%127}, %128, %129, p, 1, 1, 0, 1;}"
    : "=f"(d[0]),"=f"(d[1]),"=f"(d[2]),"=f"(d[3]),"=f"(d[4]),"=f"(d[5]),"=f"(d[6]),"=f"(d[7]),"=f"(d[8]),"=f"(d[9]),"=f"(d[10]),"=f"(d[11]),"=f"(d[12]),"=f"(d[13]),"=f"(d[14]),"=f"(d[15]),"=f"(d[16]),"=f"(d[17]),"=f"(d[18]),"=f"(d[19]),"=f"(d[20]),"=f"(d[21]),"=f"(d[22]),"=f"(d[23]),"=f"(d[24]),"=f"(d[25]),"=f"(d[26]),"=f"(d[27]),"=f"(d[28]),"=f"(d[29]),"=f"(d[30]),"=f"(d[31]),"=f"(d[32]),"=f"(d[33]),"=f"(d[34]),"=f"(d[35]),"=f"(d[36]),"=f"(d[37]),"=f"(d[38]),"=f"(d[39]),"=f"(d[40]),"=f"(d[41]),"=f"(d[42]),"=f"(d[43]),"=f"(d[44]),"=f"(d[45]),"=f"(d[46]),"=f"(d[47]),"=f"(d[48]),"=f"(d[49]),"=f"(d[50]),"=f"(d[51]),"=f"(d[52]),"=f"(d[53]),"=f"(d[54]),"=f"(d[55]),"=f"(d[56]),"=f"(d[57]),"=f"(d[58]),"=f"(d[59]),"=f"(d[60]),"=f"(d[61]),"=f"(d[62]),"=f"(d[63]),"=f"(d[64]),"=f"(d[65]),"=f"(d[66]),"=f"(d[67]),"=f"(d[68]),"=f"(d[69]),"=f"(d[70]),"=f"(d[71]),"=f"(d[72]),"=f"(d[73]),"=f"(d[74]),"=f"(d[75]),"=f"(d[76]),"=f"(d[77]),"=f"(d[78]),"=f"(d[79]),"=f"(d[80]),"=f"(d[81]),"=f"(d[82]),"=f"(d[83]),"=f"(d[84]),"=f"(d[85]),"=f"(d[86]),"=f"(d[87]),"=f"(d[88]),"=f"(d[89]),"=f"(d[90]),"=f"(d[91]),"=f"(d[92]),"=f"(d[93]),"=f"(d[94]),"=f"(d[95]),"=f"(d[96]),"=f"(d[97]),"=f"(d[98]),"=f"(d[99]),"=f"(d[100]),"=f"(d[101]),"=f"(d[102]),"=f"(d[103]),"=f"(d[104]),"=f"(d[105]),"=f"(d[106]),"=f"(d[107]),"=f"(d[108]),"=f"(d[109]),"=f"(d[110]),"=f"(d[111]),"=f"(d[112]),"=f"(d[113]),"=f"(d[114]),"=f"(d[115]),"=f"(d[116]),"=f"(d[117]),"=f"(d[118]),"=f"(d[119]),"=f"(d[120]),"=f"(d[121]),"=f"(d[122]),"=f"(d[123]),"=f"(d[124]),"=f"(d[125]),"=f"(d[126]),"=f"(d[127])
    : "l"(da), "l"(db));
}
__device__ __forceinline__ void wgmma_ssz_n128_a0b1(float (&d)[64], uint64_t da, uint64_t db) {
  asm volatile("{.reg .pred p; setp.ne.b32 p, 0, 0; wgmma.mma_async.sync.aligned.m64n128k16.f32.bf16.bf16 {%0,%1,%2,%3,%4,%5,%6,%7,%8,%9,%10,%11,%12,%13,%14,%15,%16,%17,%18,%19,%20,%21,%22,%23,%24,%25,%26,%27,%28,%29,%30,%31,%32,%33,%34,%35,%36,%37,%38,%39,%40,%41,%42,%43,%44,%45,%46,%47,%48,%49,%50,%51,%52,%53,%54,%55,%56,%57,%58,%59,%60,%61,%62,%63}, %64, %65, p, 1, 1, 0, 1;}"
    : "=f"(d[0]),"=f"(d[1]),"=f"(d[2]),"=f"(d[3]),"=f"(d[4]),"=f"(d[5]),"=f"(d[6]),"=f"(d[7]),"=f"(d[8]),"=f"(d[9]),"=f"(d[10]),"=f"(d[11]),"=f"(d[12]),"=f"(d[13]),"=f"(d[14]),"=f"(d[15]),"=f"(d[16]),"=f"(d[17]),"=f"(d[18]),"=f"(d[19]),"=f"(d[20]),"=f"(d[21]),"=f"(d[22]),"=f"(d[23]),"=f"(d[24]),"=f"(d[25]),"=f"(d[26]),"=f"(d[27]),"=f"(d[28]),"=f"(d[29]),"=f"(d[30]),"=f"(d[31]),"=f"(d[32]),"=f"(d[33]),"=f"(d[34]),"=f"(d[35]),"=f"(d[36]),"=f"(d[37]),"=f"(d[38]),"=f"(d[39]),"=f"(d[40]),"=f"(d[41]),"=f"(d[42]),"=f"(d[43]),"=f"(d[44]),"=f"(d[45]),"=f"(d[46]),"=f"(d[47]),"=f"(d[48]),"=f"(d[49]),"=f"(d[50]),"=f"(d[51]),"=f"(d[52]),"=f"(d[53]),"=f"(d[54]),"=f"(d[55]),"=f"(d[56]),"=f"(d[57]),"=f"(d[58]),"=f"(d[59]),"=f"(d[60]),"=f"(d[61]),"=f"(d[62]),"=f"(d[63])
    : "l"(da), "l"(db));
}


__device__ __forceinline__ void wg_fence() { asm volatile("wgmma.fence.sync.aligned;" ::: "memory"); }
__device__ __forceinline__ void wg_commit() { asm volatile("wgmma.commit_group.sync.aligned;" ::: "memory"); }
template <int N> __device__ __forceinline__ void wg_wait() { asm volatile("wgmma.wait_group.sync.aligned %0;" ::"n"(N) : "memory"); }
template <int N> __device__ __forceinline__ void fence_regs(float (&d)[N]) {
#pragma unroll
  for (int i = 0; i < N; i++) asm volatile("" : "+f"(d[i])::"memory");
}
template <int N> __device__ __forceinline__ void fence_regs(uint32_t (&d)[N]) {
#pragma unroll
  for (int i = 0; i < N; i++) asm volatile("" : "+r"(d[i])::"memory");
}
__device__ __forceinline__ uint64_t mk_desc(uint32_t lo, uint32_t hi) {
  uint64_t d;
  asm("mov.b64 %0, {%1,%2};" : "=l"(d) : "r"(lo), "r"(hi));
  return d;
}
constexpr uint32_t DHI_SW128 = (1024u >> 4) | (1u << 30);
__device__ __forceinline__ uint32_t desc_lo(uint32_t addr, uint32_t lbo) { return ((addr & 0x3FFFF) >> 4) | ((lbo >> 4) << 16); }

__device__ __forceinline__ void mbar_init(uint32_t bar, uint32_t cnt) { asm volatile("mbarrier.init.shared::cta.b64 [%0], %1;" ::"r"(bar), "r"(cnt) : "memory"); }
__device__ __forceinline__ uint32_t mbar_try(uint32_t bar, uint32_t par) {
  uint32_t ok;
  asm volatile("{.reg .pred p; mbarrier.try_wait.parity.shared::cta.b64 p, [%1], %2; selp.u32 %0, 1, 0, p;}" : "=r"(ok) : "r"(bar), "r"(par) : "memory");
  return ok;
}
__device__ __noinline__ void mbar_wait_slow(uint32_t bar, uint32_t par) {
  for (int i = 0; i < (1 << 22); i++)
    if (mbar_try(bar, par)) return;
  __trap();
}
__device__ __forceinline__ void mbar_wait(uint32_t bar, uint32_t par) {
  asm volatile(
      "{\n.reg .pred p;\n.reg .u32 c;\n"
      "mbarrier.try_wait.parity.shared::cta.b64 p, [%0], %1;\n"
      "@p bra DONE;\n"
      "mov.u32 c, 0;\n"
      "LOOP:\n"
      "mbarrier.try_wait.parity.shared::cta.b64 p, [%0], %1;\n"
      "@p bra DONE;\n"
      "add.u32 c, c, 1;\n"
      "setp.lt.u32 p, c, 4000000;\n"
      "@p bra LOOP;\n"
      "trap;\n"
      "DONE:\n}" ::"r"(bar), "r"(par) : "memory");
}
__device__ __forceinline__ void mbar_wait2(uint32_t b0, uint32_t p0, uint32_t b1, uint32_t p1) {
  asm volatile(
      "{\n.reg .pred p, q;\n.reg .u32 c;\n"
      "mov.u32 c, 0;\n"
      "LOOP:\n"
      "mbarrier.try_wait.parity.shared::cta.b64 p, [%0], %1;\n"
      "mbarrier.try_wait.parity.shared::cta.b64 q, [%2], %3;\n"
      "and.pred p, p, q;\n"
      "@p bra DONE;\n"
      "add.u32 c, c, 1;\n"
      "setp.lt.u32 p, c, 4000000;\n"
      "@p bra LOOP;\n"
      "trap;\n"
      "DONE:\n}" ::"r"(b0), "r"(p0), "r"(b1), "r"(p1) : "memory");
}
__device__ __forceinline__ void mbar_wait_cl(uint32_t bar, uint32_t par) {
  asm volatile(
      "{\n.reg .pred p;\n.reg .u32 c;\n"
      "mbarrier.try_wait.parity.acquire.cluster.shared::cta.b64 p, [%0], %1;\n"
      "@p bra DONE;\n"
      "mov.u32 c, 0;\n"
      "LOOP:\n"
      "mbarrier.try_wait.parity.acquire.cluster.shared::cta.b64 p, [%0], %1;\n"
      "@p bra DONE;\n"
      "add.u32 c, c, 1;\n"
      "setp.lt.u32 p, c, 4000000;\n"
      "@p bra LOOP;\n"
      "trap;\n"
      "DONE:\n}" ::"r"(bar), "r"(par) : "memory");
}
__device__ __forceinline__ void mbar_arrive(uint32_t bar) { asm volatile("mbarrier.arrive.shared::cta.b64 _, [%0];" ::"r"(bar) : "memory"); }
__device__ __forceinline__ void mbar_arrive_cl(uint32_t bar) { asm volatile("mbarrier.arrive.shared::cluster.b64 _, [%0];" ::"r"(bar) : "memory"); }
__device__ __forceinline__ void mbar_expect(uint32_t bar, uint32_t bytes) { asm volatile("mbarrier.arrive.expect_tx.shared::cta.b64 _, [%0], %1;" ::"r"(bar), "r"(bytes) : "memory"); }
__device__ __forceinline__ void mbar_expect_cl(uint32_t bar, uint32_t bytes) { asm volatile("mbarrier.arrive.expect_tx.shared::cluster.b64 _, [%0], %1;" ::"r"(bar), "r"(bytes) : "memory"); }
__device__ __forceinline__ uint32_t mapa(uint32_t addr, uint32_t rank) {
  uint32_t r;
  asm("mapa.shared::cluster.u32 %0, %1, %2;" : "=r"(r) : "r"(addr), "r"(rank));
  return r;
}
__device__ __forceinline__ void st_async32(uint32_t addr, uint32_t v, uint32_t bar) {
  asm volatile("st.async.shared::cluster.mbarrier::complete_tx::bytes.b32 [%0], %1, [%2];" ::"r"(addr), "r"(v), "r"(bar) : "memory");
}
__device__ __forceinline__ void st_async64(uint32_t addr, uint32_t a, uint32_t b, uint32_t bar) {
  asm volatile("st.async.shared::cluster.mbarrier::complete_tx::bytes.v2.b32 [%0], {%1,%2}, [%3];" ::"r"(addr), "r"(a), "r"(b), "r"(bar) : "memory");
}
__device__ __forceinline__ void st_async128(uint32_t addr, uint32_t a, uint32_t b, uint32_t c, uint32_t d, uint32_t bar) {
  asm volatile("st.async.shared::cluster.mbarrier::complete_tx::bytes.v4.b32 [%0], {%1,%2,%3,%4}, [%5];" ::"r"(addr), "r"(a), "r"(b), "r"(c), "r"(d), "r"(bar) : "memory");
}
__device__ __forceinline__ void bar_sync(int id, int n) { asm volatile("bar.sync %0, %1;" ::"r"(id), "r"(n) : "memory"); }
__device__ __forceinline__ void bar_arrive(int id, int n) { asm volatile("bar.arrive %0, %1;" ::"r"(id), "r"(n) : "memory"); }
__device__ __forceinline__ void cluster_sync() { asm volatile("barrier.cluster.arrive.aligned;\nbarrier.cluster.wait.aligned;" ::: "memory"); }
__device__ __forceinline__ bool elect() {
  uint32_t p;
  asm volatile("{.reg .pred q; elect.sync _|q, 0xffffffff; selp.u32 %0, 1, 0, q;}" : "=r"(p));
  return p != 0;
}
__device__ __forceinline__ void fence_async_smem() { asm volatile("fence.proxy.async.shared::cta;" ::: "memory"); }
__device__ __forceinline__ void fence_async_all() { asm volatile("fence.proxy.async;" ::: "memory"); }
__device__ __forceinline__ void tma2d(uint32_t dst, const CUtensorMap* m, int c0, int c1, uint32_t bar) {
  asm volatile("cp.async.bulk.tensor.2d.shared::cluster.global.mbarrier::complete_tx::bytes [%0], [%1, {%2,%3}], [%4];" ::"r"(dst), "l"(m), "r"(c0), "r"(c1), "r"(bar) : "memory");
}
__device__ __forceinline__ void tma2d_mc(uint32_t dst, const CUtensorMap* m, int c0, int c1, uint32_t bar, uint16_t mask) {
  asm volatile("cp.async.bulk.tensor.2d.shared::cluster.global.mbarrier::complete_tx::bytes.multicast::cluster [%0], [%1, {%2,%3}], [%4], %5;" ::"r"(dst), "l"(m), "r"(c0), "r"(c1), "r"(bar), "h"(mask) : "memory");
}
__device__ __forceinline__ void tma3d(uint32_t dst, const CUtensorMap* m, int c0, int c1, int c2, uint32_t bar) {
  asm volatile("cp.async.bulk.tensor.3d.shared::cluster.global.mbarrier::complete_tx::bytes [%0], [%1, {%2,%3,%4}], [%5];" ::"r"(dst), "l"(m), "r"(c0), "r"(c1), "r"(c2), "r"(bar) : "memory");
}
__device__ __forceinline__ void tma3d_mc(uint32_t dst, const CUtensorMap* m, int c0, int c1, int c2, uint32_t bar, uint16_t mask) {
  asm volatile("cp.async.bulk.tensor.3d.shared::cluster.global.mbarrier::complete_tx::bytes.multicast::cluster [%0], [%1, {%2,%3,%4}], [%5], %6;" ::"r"(dst), "l"(m), "r"(c0), "r"(c1), "r"(c2), "r"(bar), "h"(mask) : "memory");
}
__device__ __forceinline__ uint32_t ld_acquire(const unsigned* p) {
  uint32_t v;
  asm volatile("ld.acquire.gpu.global.u32 %0, [%1];" : "=r"(v) : "l"(p) : "memory");
  return v;
}
__device__ __forceinline__ uint32_t pack_bf16(float lo, float hi) {
  uint32_t r;
  asm("cvt.rn.bf16x2.f32 %0, %1, %2;" : "=r"(r) : "f"(hi), "f"(lo));
  return r;
}
__device__ __forceinline__ float ex2(float x) {
  float y;
  asm("ex2.approx.ftz.f32 %0, %1;" : "=f"(y) : "f"(x));
  return y;
}
__device__ __forceinline__ float rcp(float x) {
  float y;
  asm("rcp.approx.ftz.f32 %0, %1;" : "=f"(y) : "f"(x));
  return y;
}
__device__ __forceinline__ void stg128(void* p, uint32_t a, uint32_t b, uint32_t c, uint32_t d) {
  asm volatile("st.global.v4.b32 [%0], {%1,%2,%3,%4};" ::"l"(p), "r"(a), "r"(b), "r"(c), "r"(d) : "memory");
}
__device__ __forceinline__ void sts128(uint32_t a, uint32_t x, uint32_t y, uint32_t z, uint32_t w) {
  asm volatile("st.shared.v4.b32 [%0], {%1,%2,%3,%4};" ::"r"(a), "r"(x), "r"(y), "r"(z), "r"(w) : "memory");
}
__device__ __forceinline__ void stsm4(uint32_t a, uint32_t r0, uint32_t r1, uint32_t r2, uint32_t r3) {
  asm volatile("stmatrix.sync.aligned.m8n8.x4.shared.b16 [%0], {%1,%2,%3,%4};" ::"r"(a), "r"(r0), "r"(r1), "r"(r2), "r"(r3) : "memory");
}
__device__ __forceinline__ void arrive_elect(uint32_t bar) {
  asm volatile("{.reg .pred q; elect.sync _|q, 0xffffffff; @q mbarrier.arrive.shared::cta.b64 _, [%0];}" ::"r"(bar) : "memory");
}
__device__ __forceinline__ void sched_fence(uint32_t v) { asm volatile("{.reg .pred p; setp.eq.u32 p, %0, 0; @p trap;}" ::"r"(v) : "memory"); }
template <int V> struct IC { static constexpr int value = V; };
template <int A, int B, class F> __device__ __forceinline__ void static_for(F&& f) {
  if constexpr (A < B) {
    f(IC<A>());
    static_for<A + 1, B>(f);
  }
}
__device__ __forceinline__ uint32_t lds32(uint32_t a) {
  uint32_t v;
  asm volatile("ld.shared.b32 %0, [%1];" : "=r"(v) : "r"(a) : "memory");
  return v;
}

constexpr int MAXTASK = 256 + 256 + 200;
constexpr int T_KV = 0, T_FA = 1, T_OA = 2, T_OB = 3, T_MA = 4, T_MB = 5;
constexpr uint32_t TASK_END = 0xFFFF;
constexpr int NCL = 34;
struct MainParams {
  CUtensorMap ckv, wuk, wuv, ax, wq, scr, woa, wob, scr_st, out_st, woa2, wob2;
  uint32_t ntask;
  uint16_t tasks[MAXTASK];
};

constexpr int M_GR = 16384, M_NG = 12;
constexpr int M_STG = M_GR * M_NG;
constexpr int M_BAR = M_STG + 32768;
constexpr int M_FULL = M_BAR, M_EMPTY = M_BAR + 64, M_TFULL = M_BAR + 128, M_TEMPTY = M_BAR + 160, M_EPI = M_BAR + 192, M_SFREE = M_BAR + 224, M_GO = M_BAR + 240,
              M_TSLOT = M_BAR + 256;
constexpr int M_SMEM = M_BAR + 512 + 1024;
constexpr int OX_TARGET = 64;

#ifndef M_DELAY
#define M_DELAY 0
#endif
#ifndef PF_ON
#define PF_ON 0
#endif
#ifndef ST_ROWS
#define ST_ROWS 16
#endif
#ifndef ST_DEPTH
#define ST_DEPTH 1
#endif
#ifndef KV_SKEW
#define KV_SKEW 7
#endif
#ifndef FM_NJ
#define FM_NJ 2
#endif
#ifndef Q_SKEW
#define Q_SKEW 6
#endif
struct Ring {
  uint32_t e, g;
  __device__ __forceinline__ uint32_t take(int z) {
    if (g + z > M_NG) g = 0;
    const uint32_t r = g;
    g += z;
    return r;
  }
  __device__ __forceinline__ uint32_t bar() const { return (e & 7) * 8; }
  __device__ __forceinline__ uint32_t par() const { return (e >> 3) & 1; }
};
__device__ __forceinline__ int task_entries(int type, int p) { return type == T_KV ? 9 : type == T_FA ? 9 + 2 * (2 * p + 2) : 65; }
__device__ __forceinline__ int entry_size(int type, int it) { return type == T_FA || (type == T_KV && it == 8) || type >= T_MA ? 2 : 3; }

__device__ __forceinline__ void need_flag(uint32_t& v, int bit, const unsigned* flag, unsigned target) {
  for (int it = 0; !((__ballot_sync(0xffffffffu, v >= target) >> bit) & 1); it++) {
    if (it > (1 << 21)) __trap();
    if (it) __nanosleep(40);
    v = ld_acquire(flag);
  }
}

constexpr float SM_C = 0.08838834764831845f * 1.4426950408889634f;
template <int NJ> __device__ __forceinline__ void softmax_max(const float (&s)[64], float& m0, float& m1, float& a0, float& a1, float& c0, float& c1) {
  float x0 = fmaxf(s[0], s[4]), y0 = fmaxf(s[1], s[5]), x1 = fmaxf(s[2], s[6]), y1 = fmaxf(s[3], s[7]);
#pragma unroll
  for (int j = 2; j < NJ; j++) {
    x0 = fmaxf(x0, s[4 * j]);
    y0 = fmaxf(y0, s[4 * j + 1]);
    x1 = fmaxf(x1, s[4 * j + 2]);
    y1 = fmaxf(y1, s[4 * j + 3]);
  }
  x0 = fmaxf(x0, y0);
  x1 = fmaxf(x1, y1);
  x0 = fmaxf(x0, __shfl_xor_sync(0xffffffffu, x0, 1));
  x1 = fmaxf(x1, __shfl_xor_sync(0xffffffffu, x1, 1));
  x0 = fmaxf(x0, __shfl_xor_sync(0xffffffffu, x0, 2));
  x1 = fmaxf(x1, __shfl_xor_sync(0xffffffffu, x1, 2));
  const float n0 = fmaxf(m0, x0), n1 = fmaxf(m1, x1);
  a0 = ex2((m0 - n0) * SM_C);
  a1 = ex2((m1 - n1) * SM_C);
  m0 = n0;
  m1 = n1;
  c0 = -n0 * SM_C;
  c1 = -n1 * SM_C;
}
template <int J0, int J1> __device__ __forceinline__ void softmax_exp(const float (&s)[64], uint32_t (&p)[32], float c0, float c1, float (&t)[4]) {
#pragma unroll
  for (int j = J0; j < J1; j++) {
    const float e0 = ex2(fmaf(s[4 * j], SM_C, c0)), e1 = ex2(fmaf(s[4 * j + 1], SM_C, c0));
    const float e2 = ex2(fmaf(s[4 * j + 2], SM_C, c1)), e3 = ex2(fmaf(s[4 * j + 3], SM_C, c1));
    p[2 * j] = pack_bf16(e0, e1);
    p[2 * j + 1] = pack_bf16(e2, e3);
    if (j == 0) { t[0] = e0; t[1] = e1; t[2] = e2; t[3] = e3; }
    else { t[0] += e0; t[1] += e1; t[2] += e2; t[3] += e3; }
  }
}
template <int I0, int I1> __device__ __forceinline__ void fence_part(uint32_t (&d)[32]) {
#pragma unroll
  for (int i = I0; i < I1; i++) asm volatile("" : "+r"(d[i])::"memory");
}
template <int J0, int J1, int N> __device__ __forceinline__ void stage_tile(const float (&d)[N], uint32_t a, float f0, float f1) {
#pragma unroll
  for (int j = J0; j < J1; j += 2)
    stsm4((a ^ (((j - J0) & 7) << 4)) + ((j - J0) >> 3) * 8192, pack_bf16(d[4 * j] * f0, d[4 * j + 1] * f0), pack_bf16(d[4 * j + 2] * f1, d[4 * j + 3] * f1),
          pack_bf16(d[4 * j + 4] * f0, d[4 * j + 5] * f0), pack_bf16(d[4 * j + 6] * f1, d[4 * j + 7] * f1));
}
template <int J0, int J1> __device__ __forceinline__ void causal_mask(float (&s)[64], int lim0) {
#pragma unroll
  for (int j = J0; j < J1; j++) {
    if (8 * j > lim0) s[4 * j] = -INFINITY;
    if (8 * j + 1 > lim0) s[4 * j + 1] = -INFINITY;
    if (8 * j > lim0 + 8) s[4 * j + 2] = -INFINITY;
    if (8 * j + 1 > lim0 + 8) s[4 * j + 3] = -INFINITY;
  }
}

__global__ void __cluster_dims__(2, 1, 1) __launch_bounds__(384, 1) main_kernel(const __grid_constant__ MainParams P) {
  extern __shared__ uint8_t smem_raw[];
  const uint32_t sb = ((uint32_t)__cvta_generic_to_shared(smem_raw) + 1023u) & ~1023u;
  const int warp = __shfl_sync(0xffffffffu, threadIdx.x >> 5, 0), lane = threadIdx.x & 31;
  uint32_t rank;
  asm("mov.u32 %0, %%cluster_ctarank;" : "=r"(rank));
  rank = __shfl_sync(0xffffffffu, rank, 0);
#ifdef DEV_TRACE
  if (threadIdx.x == 0) { long long c; asm volatile("mov.u64 %0, %%globaltimer;" : "=l"(c)); g_trace[blockIdx.x * 4096 + 4090] = c; }
#endif
  const uint32_t cluster = blockIdx.x >> 1;
  static_assert(M_EMPTY == M_FULL + 64 && M_TFULL == M_FULL + 128 && M_TEMPTY == M_FULL + 160 && M_EPI == M_FULL + 192 && M_SFREE == M_FULL + 224, "barriers");
  if (warp == 8 && elect()) {
    if (M_DELAY) __nanosleep(M_DELAY);
#pragma unroll 1
    for (int i = 0; i < 4; i++) {
      const uint32_t st = sb + i * 3 * M_GR, fb = sb + M_FULL + 8 * i;
      mbar_init(fb, 1);
      mbar_expect(fb, 49152);
      tma2d(st, &P.ckv, i * 64, (cluster & 7) * 256 + rank * 128, fb);
      tma3d(st + 16384, &P.wuk, 0, i * 64, (cluster >> 3) * 2, fb);
      tma3d(st + 32768, &P.wuv, 0, i * 64, (cluster >> 3) * 2, fb);
    }
    asm volatile("fence.mbarrier_init.release.cluster;" ::: "memory");
  }
  const uint32_t task0 = cluster;
  if (warp >= 1 && warp < 8 && elect()) {
    const uint32_t b = sb + M_FULL + 32 * warp, cnt = (warp & 14) == 2 ? 16 : warp == 5 ? 22 : warp == 6 ? 4 : 1;
#pragma unroll
    for (int i = 0; i < 4; i++) mbar_init(b + 8 * i, cnt);
    asm volatile("fence.mbarrier_init.release.cluster;" ::: "memory");
  }
  __syncwarp();
  if (warp == 8) TRM(5);
  asm volatile("barrier.cluster.arrive.relaxed.aligned;" ::: "memory");
  auto started = [&]() { asm volatile("barrier.cluster.wait.aligned;" ::: "memory"); };
  const uint32_t tempty0 = mapa(sb + M_TEMPTY, 0);
  auto read_task = [&](int ti) -> uint32_t {
    if (ti == 0) return task0;
    mbar_wait(sb + M_TFULL + 8 * ((ti - 1) & 3), ((ti - 1) >> 2) & 1);
    return __shfl_sync(0xffffffffu, lds32(sb + M_TSLOT + 4 * ((ti - 1) & 3)), 0);
  };
  auto free_task = [&](int ti) {
    if (ti > 0 && lane == 0) mbar_arrive_cl(tempty0 + 8 * ((ti - 1) & 3));
  };

  if (warp >= 8) {
    asm volatile("setmaxnreg.dec.sync.aligned.u32 40;");
    if (warp == 8) {
      if (lane >= 3 && lane < 12) asm volatile("prefetch.tensormap [%0];" ::"l"(&P.ckv + lane) : "memory");
      __syncwarp();
      started();
      TRM(4);
      Ring r{0, 0};
      uint32_t lin = 0;
      uint32_t mypos = 0, mypar = 2;
      const uint32_t myempty = sb + M_EMPTY + 8 * (lane & 7);
      auto alloc = [&](int z, uint32_t& fb) -> uint32_t {
        if (r.g + z > M_NG) lin += M_NG - r.g;
        const uint32_t st = sb + r.take(z) * M_GR;
        const uint32_t need = mypar < 2 && lin + z - mypos > M_NG;
        for (int it = 0;; it++) {
          uint32_t ok;
          asm volatile("{.reg .pred p, q; setp.eq.u32 q, %3, 0; mov.pred p, q; @!q mbarrier.try_wait.parity.shared::cta.b64 p, [%1], %2; selp.u32 %0, 1, 0, p;}"
                       : "=r"(ok) : "r"(myempty), "r"(mypar), "r"(need) : "memory");
          if (__all_sync(0xffffffffu, ok)) break;
          if (it > 4000000) __trap();
        }
        mypar = need ? 2 : mypar;
        if (lane == (r.e & 7)) { mypos = lin; mypar = r.par(); }
        lin += z;
        fb = sb + M_FULL + r.bar();
        r.e++;
        return st;
      };
      auto go = [&]() { if (rank == 0) arrive_elect(sb + M_GO); };
      for (int ti = 0;; ti++) {
        const uint32_t task = read_task(ti);
        free_task(ti);
        if (task == TASK_END) break;
        const int type = task >> 12, nn = (task >> 8) & 15, h = (task >> 3) & 31, p = task & 7;
        uint32_t fb, fv = 0;
        if (type == T_KV) {
          const CUtensorMap* w = rank ? &P.wuv : &P.wuk;
          const int row = p * 256 + rank * 128;
#pragma unroll 1
          for (int k = 0; k < 512; k += 64) {
            const uint32_t st = alloc(3, fb);
            if ((ti > 0 || k >= 256) && elect()) {
              mbar_expect(fb, 49152);
              tma2d(st, &P.ckv, k, row, fb);
              tma3d_mc(st + 16384 + rank * 16384, w, 0, k, h * 2, fb, 3);
            }
            if (k == 384) go();
            if (PF_ON && ti == 0 && h < 4 && k == 192 && elect()) {
              asm volatile("cp.async.bulk.prefetch.tensor.3d.L2.global [%0, {0,%1,%2}];" ::"l"(w), "r"(p * 64), "r"((h + 4) * 2) : "memory");
              if (h == 0) asm volatile("cp.async.bulk.prefetch.tensor.3d.L2.global [%0, {0,%1,%2}];" ::"l"(w), "r"(p * 64), "r"(16) : "memory");
            }
            if (PF_ON && ti == 1 && h < 8 && k >= 192 && elect()) {
              const int c = (k - 192) / 32 + rank;
              if (c < 9) asm volatile("cp.async.bulk.prefetch.tensor.2d.L2.global [%0, {%1,%2}];" ::"l"(&P.ax), "r"(c * 64), "r"(p * 256 + (h & 3) * 64) : "memory");
              if (k == 192) asm volatile("cp.async.bulk.prefetch.tensor.2d.L2.global [%0, {%1,%2}];" ::"l"(&P.wq), "r"((h & 3) * 128 + rank * 64), "r"(p * 64) : "memory");
            }
            __syncwarp();
          }
          alloc(2, fb);
          arrive_elect(fb);
        } else if (type == T_FA) {
          const unsigned* flag = g_sync + SY_KV + h * 8 + (lane & 7);
          asm volatile("ld.relaxed.gpu.global.u32 %0, [%1];" : "=r"(fv) : "l"(flag) : "memory");
          const int r0 = p * 256 + rank * 64, r1 = p * 256 + 192 - rank * 64, col = h * 128 + rank * 64;
#pragma unroll 1
          for (int k = 0; k < 576; k += 64) {
            const uint32_t st = alloc(2, fb);
            if (elect()) {
              mbar_expect(fb, 32768);
              tma2d(st, &P.ax, k, r0, fb);
              tma2d(st + 8192, &P.ax, k, r1, fb);
              tma2d_mc(st + 16384 + rank * 8192, &P.wq, col, k, fb, 3);
            }
          }
          auto kv = [&](int row) {
            const uint32_t st = alloc(2, fb);
            if (elect()) {
              mbar_expect(fb, 32768);
              tma2d_mc(st + rank * 16384, &P.scr, col, row, fb, 3);
            }
          };
          need_flag(fv, p, flag, 4);
          kv((2 * p + 1) * 128);
#pragma unroll 1
          for (int j = 2 * p; j >= 0; j--) {
            need_flag(fv, j >> 1, flag, 4);
            if (j == 0) go();
            kv(j * 128);
            kv(SEQ + (j + 1) * 128);
          }
          kv(SEQ);
        } else {
          const int part = type & 1;
          const unsigned* flag = g_sync + (part ? SY_OX + 2 * p + 1 : SY_CTX + p * 32 + lane);
          const unsigned target = part ? OX_TARGET : 4;
          const int row = (2 + part) * SEQ + p * 256 + rank * 128;
          const int nch = type >= T_MA ? 2 : 3;
          const CUtensorMap* w = &P.woa + part + (type >= T_MA ? 4 : 0);
#pragma unroll 1
          for (int k = 0; k < HDALL; k += 64) {
            need_flag(fv, k >> 7, flag, target);
            const uint32_t st = alloc(nch, fb);
            if (elect()) {
              mbar_expect(fb, 16384 + nch * 8192);
              tma2d(st, &P.scr, k, row, fb);
              tma3d_mc(st + 16384 + rank * nch * 4096, w, 0, k + rank * 32, nn * nch, fb, 3);
            }
            if (k == HDALL - 192) go();
          }
          alloc(nch, fb);
          arrive_elect(fb);
        }
      }
    } else if (warp == 9) {
      started();
      TRM(0);
      if (rank == 0) {
        for (int ti = 0;; ti++) {
          uint32_t q = 0;
          mbar_wait(sb + M_GO, ti & 1);
          if (lane == 0) q = atomicAdd(&g_sync[SY_Q], 1u);
          q = __shfl_sync(0xffffffffu, q, 0);
          if (ti == 0 && q < 100000) TRM(1);
          const uint32_t t = q < P.ntask ? (uint32_t)P.tasks[q] : TASK_END;
          if (ti == 0 && t < 100000) TRM(2);
          mbar_wait(sb + M_TEMPTY + 8 * (ti & 3), ((ti >> 2) & 1) ^ 1);
          if (lane < 2) {
            const uint32_t b = mapa(sb + M_TFULL + 8 * (ti & 3), lane);
            mbar_expect_cl(b, 4);
            st_async32(mapa(sb + M_TSLOT + 4 * (ti & 3), lane), t, b);
          }
          __syncwarp();
          if (t == TASK_END) break;
        }
      }
    } else {
      const int wg = warp - 10;
      const uint32_t emptyx = mapa(sb + M_EMPTY, lane & 1);
      Ring r{0, 0};
      int lead = wg;
      started();
      for (int ti = 0;; ti++) {
        const int sl = ti & 1;
        const uint32_t task = read_task(ti);
        const int type = task >> 12, nn = (task >> 8) & 15, h = (task >> 3) & 31, p = task & 7;
        if (task != TASK_END) {
          const int nit = task_entries(type, p);
          uint32_t st = 0;
          for (int it = 0; it < nit; it++) st = r.take(entry_size(type, it));
          r.e += nit - 1;
          int row = p * 256 + rank * 128 + wg * 64;
          if (type == T_FA) {
            row = 2 * SEQ + p * 256 + (lead ? 3 - (int)rank : (int)rank) * 64;
            lead ^= 1;
          }
          mbar_wait(sb + M_EPI + 8 * (sl * 2 + wg), (ti >> 1) & 1);
          auto store = [&](const CUtensorMap* m, uint32_t src, int r0, int c0, int n32, bool fast = true) {
            if (lane == 0) {
#pragma unroll 1
              for (int i = 0; i < n32 * (32 / ST_ROWS); i++) {
                asm volatile("cp.async.bulk.tensor.2d.global.shared::cta.bulk_group [%0, {%1,%2}], [%3];" ::"l"(m), "r"((c0 + i / (64 / ST_ROWS)) * 64), "r"(r0 + i % (64 / ST_ROWS) * ST_ROWS), "r"(src + i * ST_ROWS * 128) : "memory");
                asm volatile("cp.async.bulk.commit_group;" ::: "memory");
                if (fast) asm volatile("cp.async.bulk.wait_group.read %0;" ::"n"(ST_DEPTH) : "memory");
                else asm volatile("cp.async.bulk.wait_group.read 0;" ::: "memory");
              }
              asm volatile("cp.async.bulk.wait_group.read 0;" ::: "memory");
            }
            __syncwarp();
          };
          if (type != T_FA) {
            if (type == T_KV) store(&P.scr_st, sb + st * M_GR + wg * 16384, SEQ + row, h * 2, 4);
            else if (type < T_MA) store(&P.out_st, sb + st * M_GR + wg * 24576, row, (type & 1) * 9 + nn * 3, 6);
            else store(&P.out_st, sb + st * M_GR + wg * 16384, row, (type & 1) * 9 + nn * 2, 4);
            if (lane < 2) asm volatile("mbarrier.arrive.shared::cluster.b64 _, [%0], 4;" ::"r"(emptyx + r.bar()) : "memory");
          }
          r.e++;
          if (type <= T_FA) store(&P.scr_st, sb + M_STG + wg * 16384, row, h * 2, 4, false);
          if (lane == 0) mbar_arrive(sb + M_SFREE + 8 * wg);
          if (lane == 0) {
            asm volatile("cp.async.bulk.wait_group 0;" ::: "memory");
            if (type <= T_FA) {
              __threadfence();
              atomicAdd(type == T_KV ? &g_sync[SY_KV + h * 8 + p] : &g_sync[SY_CTX + p * 32 + h], 1u);
            }
          }
        }
        __syncwarp();
        free_task(ti);
        if (task == TASK_END) break;
      }
    }
    __syncwarp();
    cluster_sync();
    if (threadIdx.x == 288) TRE(256 + blockIdx.x);
    if (warp == 9) {
      uint32_t old = 0;
      if (lane == 0) {
        __threadfence();
        old = atomicAdd(&g_sync[SY_EXIT], 1u);
        __threadfence();
      }
      if (__shfl_sync(0xffffffffu, old, 0) == gridDim.x - 1) {
        asm volatile("griddepcontrol.wait;" ::: "memory");
        for (int i = lane; i < SY_N; i += 32) g_sync[i] = 0;
      }
    }
  } else {
    asm volatile("setmaxnreg.inc.sync.aligned.u32 232;");
    if (warp == 0) TRM(3);
    const int wg = warp >> 2, w4 = warp & 3, g = lane >> 2, t4 = lane & 3;
    const uint32_t emptyx = mapa(sb + M_EMPTY, lane & 1);
    Ring r{0, 0};
    int lead = wg;
    auto release = [&](uint32_t bar) {
      if (lane < 2) mbar_arrive_cl(emptyx + bar);
    };
    auto acquire = [&](int z, uint32_t& bar) -> uint32_t {
      bar = r.bar();
      mbar_wait(sb + M_FULL + bar, r.par());
      r.e++;
      return sb + r.take(z) * M_GR;
    };
    const uint32_t sa = (w4 * 16 + ((lane >> 3) & 1) * 8 + (lane & 7)) * 128 + (((lane >> 4) ^ (lane & 7)) << 4);
    uint32_t ntask = task0;
    started();
    for (int ti = 0;; ti++) {
      const int sl = ti & 1;
      const uint32_t task = ntask;
      if (task == TASK_END) break;
      auto next_task = [&]() { ntask = read_task(ti + 1); free_task(ti + 1); };
      const int type = task >> 12, p = task & 7;
#ifdef DEV_TRACE
      if (w4 == 0 && lane == 0 && ti < 250) { long long c; asm volatile("mov.u64 %0, %%globaltimer;" : "=l"(c)); g_trace[blockIdx.x * 4096 + ti * 8 + wg * 4] = c; g_trace[blockIdx.x * 4096 + ti * 8 + wg * 4 + 2] = task; g_trace[blockIdx.x * 4096 + ti * 8 + wg * 4 + 3] = clock64(); }
#endif
      if (type == T_KV) {
        float acc[128];
        uint32_t prev;
        TRK(0);
        {
          const uint32_t st = acquire(3, prev);
          TRK(1);
          if (ti == 0 && warp == 0) TRM(6);
          const uint32_t a = desc_lo(st + wg * 8192, 16), b = desc_lo(st + 16384, 8192);
          wg_fence();
          wgmma_ssz_n256_a0b1(acc, mk_desc(a, DHI_SW128), mk_desc(b, DHI_SW128));
#pragma unroll
          for (int kk = 1; kk < 4; kk++) wgmma_ss_n256_a0b1(acc, mk_desc(a + kk * 2, DHI_SW128), mk_desc(b + kk * 128, DHI_SW128), 1);
          wg_commit();
        }
#pragma unroll 1
        for (int kb = 1; kb < 8; kb++) {
          uint32_t bar;
          const uint32_t st = acquire(3, bar);
          TRK(1 + kb);
          const uint32_t a = desc_lo(st + wg * 8192, 16), b = desc_lo(st + 16384, 8192);
          if (KV_SKEW < 8 && kb == KV_SKEW && !lead) {
            wg_wait<0>();
            release(prev);
            bar_sync(5, 256);
          }
          wg_fence();
#pragma unroll
          for (int kk = 0; kk < 4; kk++) wgmma_ss_n256_a0b1(acc, mk_desc(a + kk * 2, DHI_SW128), mk_desc(b + kk * 128, DHI_SW128), 1);
          wg_commit();
          if (KV_SKEW < 8 && kb == 7 && lead) bar_arrive(5, 256);
          if (KV_SKEW < 8 && kb == KV_SKEW && !lead) { prev = bar; continue; }
          wg_wait<1>();
          release(prev);
          prev = bar;
        }
        if (ti == 0 && warp == 0) TRM(7);
        TRK(9);
        next_task();
        uint32_t bar;
        const uint32_t st = acquire(2, bar);
        TRK(10);
        mbar_wait(sb + M_SFREE + 8 * wg, (ti & 1) ^ 1);
        TRK(11);
        wg_wait<0>();
        release(prev);
        fence_regs(acc);
        TRK(12);
        stage_tile<16, 32>(acc, st + wg * 16384 + sa, 1.f, 1.f);
        stage_tile<0, 16>(acc, sb + M_STG + wg * 16384 + sa, 1.f, 1.f);
        TRK(13);
        fence_async_smem();
        __syncwarp();
        arrive_elect(sb + M_EPI + 8 * (sl * 2 + wg));
      } else if (type == T_FA) {
        const int lng = lead;
        lead ^= 1;
        const int grp = lng ? 3 - (int)rank : (int)rank;
        const int n = 2 * p + 1 + lng;
        float s[64], o[64];
        uint32_t pr[32], q[32];
        TRF(0);
        {
          uint32_t prev;
          {
            const uint32_t st = acquire(2, prev);
            const uint32_t a = desc_lo(st + lng * 8192, 16), b = desc_lo(st + 16384, 8192);
            wg_fence();
            wgmma_ssz_n128_a0b1(s, mk_desc(a, DHI_SW128), mk_desc(b, DHI_SW128));
#pragma unroll
            for (int kk = 1; kk < 4; kk++) wgmma_ss_n128_a0b1(s, mk_desc(a + kk * 2, DHI_SW128), mk_desc(b + kk * 128, DHI_SW128), 1);
            wg_commit();
          }
#pragma unroll 1
          for (int kb = 1; kb < 9; kb++) {
            uint32_t bar;
            if (kb == 1) TRF(8);
            if (kb == 5) TRF(9);
            const uint32_t st = acquire(2, bar);
            const uint32_t a = desc_lo(st + lng * 8192, 16), b = desc_lo(st + 16384, 8192);
            const bool hold = kb == Q_SKEW && !lng;
            if (hold) {
              wg_wait<0>();
              release(prev);
              bar_sync(5, 256);
            }
            wg_fence();
#pragma unroll
            for (int kk = 0; kk < 4; kk++) wgmma_ss_n128_a0b1(s, mk_desc(a + kk * 2, DHI_SW128), mk_desc(b + kk * 128, DHI_SW128), 1);
            wg_commit();
            if (Q_SKEW < 9 && kb == 8 && lng) bar_arrive(5, 256);
            if (hold) { prev = bar; continue; }
            wg_wait<1>();
            release(prev);
            prev = bar;
          }
#pragma unroll
          for (int i = 0; i < 64; i++) o[i] = 0.f;
          wg_wait<0>();
          release(prev);
          fence_regs(s);
#pragma unroll
          for (int i = 0; i < 32; i++) q[i] = pack_bf16(s[2 * i], s[2 * i + 1]);
        }
        TRF(1);
        const int lim0 = (grp & 1) * 64 + w4 * 16 + g - 2 * t4;
        float m0 = -INFINITY, m1 = -INFINITY, l0 = 0.f, l1 = 0.f;
        auto issue_s = [&](uint32_t st) {
          const uint32_t b = desc_lo(st, 16);
#pragma unroll
          for (int kk = 0; kk < 8; kk++) wgmma_rs_n128_b0(s, q[4 * kk], q[4 * kk + 1], q[4 * kk + 2], q[4 * kk + 3], mk_desc(b + (kk >> 2) * 1024 + (kk & 3) * 2, DHI_SW128), kk);
          wg_commit();
        };
        auto issue_pv = [&](uint32_t st) {
          const uint32_t b = desc_lo(st, 16384);
#pragma unroll
          for (int kk = 0; kk < 8; kk++) {
            wgmma_rs_n128_b1(o, pr[4 * kk], pr[4 * kk + 1], pr[4 * kk + 2], pr[4 * kk + 3], mk_desc(b + kk * 128, DHI_SW128), 1);
            if (kk == 1 || kk == 3 || kk == 7) wg_commit();
          }
        };
        auto skip = [&]() {
          uint32_t bar;
          acquire(2, bar);
          release(bar);
        };
        const bool half = !(grp & 1);
        float t[4];
        auto first = [&]() {
          float a0, a1, c0, c1;
          uint32_t kb;
          const uint32_t kst = acquire(2, kb);
          if (!lng) bar_sync(1 + wg, 256);
          fence_regs(q);
          fence_regs(s);
          if (half) {
            const uint32_t b = desc_lo(kst, 16);
            wg_fence();
#pragma unroll
            for (int kk = 0; kk < 8; kk++) wgmma_rs_n64_b0(reinterpret_cast<float(&)[32]>(s), q[4 * kk], q[4 * kk + 1], q[4 * kk + 2], q[4 * kk + 3], mk_desc(b + (kk >> 2) * 1024 + (kk & 3) * 2, DHI_SW128), kk);
            wg_commit();
            bar_arrive(2 - wg, 256);
            wg_wait<0>();
            fence_regs(s);
            causal_mask<0, 8>(s, lim0);
          } else {
            wg_fence();
            issue_s(kst);
            bar_arrive(2 - wg, 256);
            wg_wait<0>();
            fence_regs(s);
            causal_mask<8, 16>(s, lim0);
          }
          release(kb);
          TRF(2);
          softmax_max<FM_NJ>(s, m0, m1, a0, a1, c0, c1);
          softmax_exp<0, 8>(s, pr, c0, c1, t);
          if (half) {
#pragma unroll
            for (int i = 16; i < 32; i++) pr[i] = 0;
          } else {
            softmax_exp<8, 16>(s, pr, c0, c1, t);
          }
        };
        auto block = [&]() {
          const uint32_t kb = r.bar(), kp = r.par(), kst = sb + r.take(2) * M_GR;
          r.e++;
          const uint32_t vb = r.bar(), vp = r.par(), vst = sb + r.take(2) * M_GR;
          r.e++;
          mbar_wait2(sb + M_FULL + kb, kp, sb + M_FULL + vb, vp);
          fence_regs(o);
          fence_regs(pr);
          fence_regs(s);
          bar_sync(1 + wg, 256);
          wg_fence();
          issue_s(kst);
          issue_pv(vst);
          bar_arrive(2 - wg, 256);
          wg_wait<3>();
          release(kb);
          fence_regs(s);
          const float d0 = -m0 * SM_C, d1 = -m1 * SM_C;
          wg_wait<2>();
          fence_part<0, 8>(pr);
          softmax_exp<0, 4>(s, pr, d0, d1, t);
          fence_part<0, 8>(pr);
          sched_fence(kst);
          wg_wait<1>();
          fence_part<8, 16>(pr);
          softmax_exp<4, 8>(s, pr, d0, d1, t);
          fence_part<8, 16>(pr);
          sched_fence(vst);
          wg_wait<0>();
          release(vb);
          fence_regs(o);
          fence_part<16, 32>(pr);
          softmax_exp<8, 16>(s, pr, d0, d1, t);
        };
        auto check = [&](bool hlf) {
          if (__builtin_expect(__any_sync(0xffffffffu, !((t[0] + t[1]) + (t[2] + t[3]) < 1.8446744e19f)), 0)) {
            float a0, a1, c0, c1;
            if (hlf) {
#pragma unroll
              for (int i = 32; i < 64; i++) s[i] = -INFINITY;
            }
            softmax_max<16>(s, m0, m1, a0, a1, c0, c1);
            l0 *= a0;
            l1 *= a1;
#pragma unroll
            for (int i = 0; i < 16; i++) { o[4 * i] *= a0; o[4 * i + 1] *= a0; o[4 * i + 2] *= a1; o[4 * i + 3] *= a1; }
            softmax_exp<0, 16>(s, pr, c0, c1, t);
          }
          l0 += t[0] + t[1];
          l1 += t[2] + t[3];
        };
        if (!lng) skip();
        first();
        check(half);
        if (!lng) skip();
        TRF(3);
#pragma unroll 1
        for (int j = 1; j < n; j++) {
          if (j == n - 1) TRF(4);
          block();
          check(false);
        }
        TRF(5);
        uint32_t vb;
        const uint32_t vst = acquire(2, vb);
        fence_regs(o);
        fence_regs(pr);
        if (!lng) bar_sync(1 + wg, 256);
        wg_fence();
        issue_pv(vst);
        l0 += __shfl_xor_sync(0xffffffffu, l0, 1);
        l1 += __shfl_xor_sync(0xffffffffu, l1, 1);
        l0 += __shfl_xor_sync(0xffffffffu, l0, 2);
        l1 += __shfl_xor_sync(0xffffffffu, l1, 2);
        const float i0 = rcp(l0), i1 = rcp(l1);
        next_task();
        mbar_wait(sb + M_SFREE + 8 * wg, (ti & 1) ^ 1);
        wg_wait<0>();
        release(vb);
        fence_regs(o);
        fence_regs(pr);
        TRF(6);
        stage_tile<0, 16>(o, sb + M_STG + wg * 16384 + sa, i0, i1);
        fence_async_smem();
        __syncwarp();
        arrive_elect(sb + M_EPI + 8 * (sl * 2 + wg));
        TRF(7);
      } else if (type >= T_MA) {
        float acc[64];
#pragma unroll
        for (int i = 0; i < 64; i++) acc[i] = 0.f;
        uint32_t prev = 0;
        for (int kb = 0; kb < 64; kb++) {
          uint32_t bar;
          const uint32_t st = acquire(2, bar);
          const uint32_t a = desc_lo(st + wg * 8192, 16), b = desc_lo(st + 16384, 4096);
          wg_fence();
#pragma unroll
          for (int kk = 0; kk < 4; kk++) wgmma_ss_n128_a0b1(acc, mk_desc(a + kk * 2, DHI_SW128), mk_desc(b + (kk >> 1) * 512 + (kk & 1) * 128, DHI_SW128), kk | kb);
          wg_commit();
          if (kb > 0) { wg_wait<1>(); release(prev); }
          prev = bar;
        }
        next_task();
        uint32_t bar;
        const uint32_t st = acquire(2, bar);
        mbar_wait(sb + M_SFREE + 8 * wg, (ti & 1) ^ 1);
        wg_wait<0>();
        release(prev);
        fence_regs(acc);
        stage_tile<0, 16>(acc, st + wg * 16384 + sa, 1.f, 1.f);
        fence_async_smem();
        __syncwarp();
        arrive_elect(sb + M_EPI + 8 * (sl * 2 + wg));
      } else {
        float acc[96];
#pragma unroll
        for (int i = 0; i < 96; i++) acc[i] = 0.f;
        uint32_t prev = 0;
        for (int kb = 0; kb < 64; kb++) {
          uint32_t bar;
          const uint32_t st = acquire(3, bar);
          const uint32_t a = desc_lo(st + wg * 8192, 16), b = desc_lo(st + 16384, 4096);
          wg_fence();
#pragma unroll
          for (int kk = 0; kk < 4; kk++) wgmma_ss_n192_a0b1(acc, mk_desc(a + kk * 2, DHI_SW128), mk_desc(b + (kk >> 1) * 768 + (kk & 1) * 128, DHI_SW128), kk | kb);
          wg_commit();
          if (kb > 0) { wg_wait<1>(); release(prev); }
          prev = bar;
        }
        next_task();
        uint32_t bar;
        const uint32_t st = acquire(3, bar);
        mbar_wait(sb + M_SFREE + 8 * wg, (ti & 1) ^ 1);
        wg_wait<0>();
        release(prev);
        fence_regs(acc);
        stage_tile<0, 24>(acc, st + wg * 24576 + sa, 1.f, 1.f);
        fence_async_smem();
        __syncwarp();
        arrive_elect(sb + M_EPI + 8 * (sl * 2 + wg));
      }
#ifdef DEV_TRACE
      if (w4 == 0 && lane == 0 && ti < 250) { long long c; asm volatile("mov.u64 %0, %%globaltimer;" : "=l"(c)); g_trace[blockIdx.x * 4096 + ti * 8 + wg * 4 + 1] = c; }
#endif
    }
    cluster_sync();
  }
}

typedef CUresult (*EncodeFn)(CUtensorMap*, CUtensorMapDataType, cuuint32_t, void*, const cuuint64_t*, const cuuint64_t*, const cuuint32_t*,
                             const cuuint32_t*, CUtensorMapInterleave, CUtensorMapSwizzle, CUtensorMapL2promotion, CUtensorMapFloatOOBfill);

void map2d(EncodeFn enc, CUtensorMap* m, const void* p, int rows, int cols, int boxr) {
  cuuint64_t gd[2] = {(cuuint64_t)cols, (cuuint64_t)rows}, gs[1] = {(cuuint64_t)cols * 2};
  cuuint32_t bx[2] = {64, (cuuint32_t)boxr}, es[2] = {1, 1};
  enc(m, CU_TENSOR_MAP_DATA_TYPE_BFLOAT16, 2, (void*)p, gd, gs, bx, es, CU_TENSOR_MAP_INTERLEAVE_NONE, CU_TENSOR_MAP_SWIZZLE_128B,
      CU_TENSOR_MAP_L2_PROMOTION_L2_256B, CU_TENSOR_MAP_FLOAT_OOB_FILL_NONE);
}
void map3d(EncodeFn enc, CUtensorMap* m, const void* p, int rows, int cols, int boxr, int nch) {
  cuuint64_t gd[3] = {64, (cuuint64_t)rows, (cuuint64_t)cols / 64}, gs[2] = {(cuuint64_t)cols * 2, 128};
  cuuint32_t bx[3] = {64, (cuuint32_t)boxr, (cuuint32_t)nch}, es[3] = {1, 1, 1};
  enc(m, CU_TENSOR_MAP_DATA_TYPE_BFLOAT16, 3, (void*)p, gd, gs, bx, es, CU_TENSOR_MAP_INTERLEAVE_NONE, CU_TENSOR_MAP_SWIZZLE_128B,
      CU_TENSOR_MAP_L2_PROMOTION_L2_256B, CU_TENSOR_MAP_FLOAT_OOB_FILL_NONE);
}

#ifndef R_KR
#define R_KR 24
#endif
#ifndef R_VR
#define R_VR 9
#endif
constexpr int R_NS = 36 - R_KR;
constexpr int R_WQ = 0, R_WK = R_WQ + R_NS * 2048, R_WV = R_WK + R_NS * 2048;
constexpr int R_OS = 102 * 1024;
constexpr int R_RS = 103 * 1024;
static_assert(R_WV + (36 - R_VR) * 2048 <= R_OS, "weights");
constexpr int R_HC = 9216, R_H = 114 * 1024, R_HM = R_H + 4096;
__host__ __device__ constexpr int hoff(int c) { return (c < 8 ? 1 + (c >> 1) + 4 * (c & 1) : 0) * R_HC; }
constexpr int R_PS = R_H + 9 * R_HC;
constexpr int R_GS = 1056, R_HS = 12288, R_QS = 201 * 1024;
static_assert(R_PS + 5120 <= R_QS, "layout");
constexpr int R_BAR = R_QS + 2 * R_HS;
static_assert(3 * 73728 <= R_BAR, "prologue staging");
constexpr int RB_MEM = R_BAR  , RB_RS = R_BAR + 40, RB_QK = R_BAR + 48, RB_XF = R_BAR + 88  , RB_QXL = R_BAR + 104, RB_W = R_BAR + 112  ;
constexpr int RB_TF = R_BAR + 128  , RB_TE = R_BAR + 224  , RB_TR = R_BAR + 256, RB_SEL = R_BAR + 272  ;
constexpr int R_SMEM = R_BAR + 320;
static_assert(R_SMEM <= 232448, "smem");
constexpr int QK_TX = 2048 + 8 * R_GS;
constexpr int NB_P1 = 1, NB_P3 = 2, NB_PM = 3, NB_O = 4, NB_PX = 5, NB_RD = 6, NB_S = 7, NB_O2 = 8;
static_assert(R_NS >= 9 && R_NS <= 18, "R_KR");
__host__ __device__ constexpr int nsm(int c) { return c < R_NS - 9 ? 2 : 1; }
__host__ __device__ constexpr int sm0(int c) { return c < R_NS - 9 ? 2 * c : c + R_NS - 9; }
__host__ __device__ constexpr bool qk_in_reg(int k) { return (k & 3) >= nsm(k >> 2); }
__host__ __device__ constexpr int qk_slot(int k) { return qk_in_reg(k) ? k - sm0((k >> 2) + 1) : sm0(k >> 2) + (k & 3); }
__host__ __device__ constexpr int qk_step(int slot, bool reg) {
  for (int k = 0; k < 36; k++)
    if (qk_in_reg(k) == reg && qk_slot(k) == slot) return k;
  return -1;
}
#ifndef B_SEQ
#define B_SEQ "qkqkqkqkQkqkKqkq|QKQKQKqkQkqKqkQkqKqkQkqKqkQkqKqkQkqKqkQkqKqkQkqKqkQkqKqk"
#endif
__host__ __device__ constexpr int seq_count(char c, int n) {
  int r = 0;
  for (int i = 0; i < n; i++) r += B_SEQ[i] == c;
  return r;
}
static_assert(sizeof(B_SEQ) == 74 && seq_count('q', 73) == R_KR && seq_count('k', 73) == R_KR && seq_count('Q', 73) == R_NS && seq_count('K', 73) == R_NS, "B_SEQ");
#ifndef V_N1
#define V_N1 10
#endif
#ifndef V_PER
#define V_PER 3
#endif
#ifndef V_K0
#define V_K0 11
#endif
#ifndef QX_AFTER
#define QX_AFTER 2
#endif
#ifndef P1_PRE
#define P1_PRE 2
#endif
#ifndef B_DELAY
#define B_DELAY 0
#endif
#ifndef PUB_REL
#define PUB_REL 0
#endif
#ifndef PF_V
#define PF_V 0
#endif
#ifndef PF_MAIN
#define PF_MAIN 0
#endif
#ifndef PRE_EARLY
#define PRE_EARLY 1
#endif
#ifndef P3_EARLY
#define P3_EARLY 0
#endif
#ifndef B_SKIP
#define B_SKIP 0
#endif
#ifndef V_SKIP
#define V_SKIP 0
#endif
#ifndef PACK_AT
#define PACK_AT 0
#endif
#ifndef P3_F
#define P3_F 3
#endif
#ifndef POLL_STAG
#define POLL_STAG 80
#endif
#ifndef POLL_DELAY
#define POLL_DELAY 160
#endif
__host__ __device__ constexpr bool v_in_reg(int k) { return k >= V_K0 && (k - V_K0) % V_PER == 0 && (k - V_K0) / V_PER < R_VR; }
__host__ __device__ constexpr int v_nreg_before(int k) { return k <= V_K0 ? 0 : ((k - V_K0 + V_PER - 1) / V_PER < R_VR ? (k - V_K0 + V_PER - 1) / V_PER : R_VR); }
__host__ __device__ constexpr int v_slot(int k) { return v_in_reg(k) ? (k - V_K0) / V_PER : k - v_nreg_before(k); }
static_assert(V_K0 + (R_VR - 1) * V_PER < 36, "Wv split");

struct RmtParams {
  CUtensorMap wq, wk, wv, wo, x, mem, ox, ox64, wo3;
  const __nv_bfloat16 *ckv, *wuk, *wuv;
  uint32_t* out;
};
constexpr int XCH_CL = 96, XCH_SLOT = 4 * XCH_CL;
__device__ uint32_t g_xch[65 * 2048];
#ifndef XCH_NP
#define XCH_NP 6
#endif
#ifndef XCH_SEL
#define XCH_SEL 1
#endif
__device__ __forceinline__ uint32_t* xch_other(uint32_t* p) { return (uint32_t*)((uint64_t)p ^ 4096); }
#ifdef DEV_TRACE
__device__ long long g_trace_b[64 * 4096];
#ifndef TR_S0
#define TR_S0 24
#endif
#ifndef TR_MASK
#define TR_MASK 0xffffffffu
#endif
#define TRW(slot, w) do { if (((TR_MASK >> (slot)) & 1) && w4 == (w) && s >= TR_S0 && s < TR_S0 + 16) { uint32_t c_; asm volatile("mov.u32 %0, %%clock;" : "=r"(c_)::"memory"); sts32(sb + R_QS + R_GS + ((s >> 3) & 1) * R_HS + (s & 7) * 128 + (slot) * 4, c_); } } while (0)
#else
#define TRW(slot, w)
#endif
#define TRB(slot) TRW(slot, 0)
#ifdef DEV_TRACE
#ifndef TRG_MASK
#define TRG_MASK 0x41
#endif
#define TRT(slot, w) do { if (warp == (w) && (threadIdx.x & 31) == 0) { long long c_; asm volatile("mov.u64 %0, %%globaltimer;" : "=l"(c_)); g_trace_b[bid * 4096 + 2200 + (slot)] = c_; } } while (0)
#define TRG(slot) do { if (((slot) >= 16 || ((TRG_MASK >> (slot)) & 1)) && (threadIdx.x & 127) == 0) { long long c_; asm volatile("mov.u64 %0, %%globaltimer;" : "=l"(c_)); g_trace_b[bid * 4096 + 2048 + (slot)] = c_; if ((slot) < 8) g_trace_b[bid * 4096 + 2056 + (slot)] = clock64(); } } while (0)
#else
#define TRG(slot)
#define TRT(slot, w)
#endif

__device__ __forceinline__ void ldsm4(uint32_t (&r)[4], uint32_t a) {
  asm volatile("ldmatrix.sync.aligned.m8n8.x4.shared.b16 {%0,%1,%2,%3}, [%4];" : "=r"(r[0]), "=r"(r[1]), "=r"(r[2]), "=r"(r[3]) : "r"(a) : "memory");
}
__device__ __forceinline__ void ldsm4t(uint32_t (&r)[4], uint32_t a) {
  asm volatile("ldmatrix.sync.aligned.m8n8.x4.trans.shared.b16 {%0,%1,%2,%3}, [%4];" : "=r"(r[0]), "=r"(r[1]), "=r"(r[2]), "=r"(r[3]) : "r"(a) : "memory");
}
__device__ __forceinline__ void stsm4t(uint32_t a, uint32_t r0, uint32_t r1, uint32_t r2, uint32_t r3) {
  asm volatile("stmatrix.sync.aligned.m8n8.x4.trans.shared.b16 [%0], {%1,%2,%3,%4};" ::"r"(a), "r"(r0), "r"(r1), "r"(r2), "r"(r3) : "memory");
}
__device__ __forceinline__ void stsm2t(uint32_t a, uint32_t r0, uint32_t r1) {
  asm volatile("stmatrix.sync.aligned.m8n8.x2.trans.shared.b16 [%0], {%1,%2};" ::"r"(a), "r"(r0), "r"(r1) : "memory");
}
__device__ __forceinline__ void mma16816(float (&c)[4], const uint32_t (&a)[4], uint32_t b0, uint32_t b1) {
  asm volatile("mma.sync.aligned.m16n8k16.row.col.f32.bf16.bf16.f32 {%0,%1,%2,%3}, {%4,%5,%6,%7}, {%8,%9}, {%0,%1,%2,%3};"
               : "+f"(c[0]), "+f"(c[1]), "+f"(c[2]), "+f"(c[3])
               : "r"(a[0]), "r"(a[1]), "r"(a[2]), "r"(a[3]), "r"(b0), "r"(b1));
}
__device__ __forceinline__ void sts32(uint32_t a, uint32_t v) { asm volatile("st.shared.b32 [%0], %1;" ::"r"(a), "r"(v) : "memory"); }
__device__ __forceinline__ uint2 lds64(uint32_t a) {
  uint2 v;
  asm volatile("ld.shared.v2.b32 {%0,%1}, [%2];" : "=r"(v.x), "=r"(v.y) : "r"(a) : "memory");
  return v;
}
__device__ __forceinline__ float4 lds128f(uint32_t a) {
  float4 v;
  asm volatile("ld.shared.v4.f32 {%0,%1,%2,%3}, [%4];" : "=f"(v.x), "=f"(v.y), "=f"(v.z), "=f"(v.w) : "r"(a) : "memory");
  return v;
}
__device__ __forceinline__ uint4 ld_relaxed128(const uint32_t* p) {
  uint4 v;
  asm volatile("ld.relaxed.gpu.global.v4.u32 {%0,%1,%2,%3}, [%4];" : "=r"(v.x), "=r"(v.y), "=r"(v.z), "=r"(v.w) : "l"(p) : "memory");
  return v;
}
__device__ __forceinline__ void st_relaxed32(uint32_t* p, uint32_t v) { asm volatile("st.relaxed.gpu.global.u32 [%0], %1;" ::"l"(p), "r"(v) : "memory"); }

__device__ __forceinline__ void mma1688(float (&c)[4], uint32_t a0, uint32_t a1, uint32_t b0) {
  asm volatile("mma.sync.aligned.m16n8k8.row.col.f32.bf16.bf16.f32 {%0,%1,%2,%3}, {%4,%5}, {%6}, {%0,%1,%2,%3};"
               : "+f"(c[0]), "+f"(c[1]), "+f"(c[2]), "+f"(c[3])
               : "r"(a0), "r"(a1), "r"(b0));
}
__device__ __forceinline__ uint2 ld_relaxed64(const uint32_t* p) {
  uint2 v;
  asm volatile("{.reg .b64 t; ld.relaxed.gpu.global.b64 t, [%2]; mov.b64 {%0,%1}, t;}" : "=r"(v.x), "=r"(v.y) : "l"(p) : "memory");
  return v;
}
__device__ __forceinline__ void st_relaxed64(uint32_t* p, uint32_t a, uint32_t b) { asm volatile("{.reg .b64 t; mov.b64 t, {%1,%2}; st.relaxed.gpu.global.b64 [%0], t;}" ::"l"(p), "r"(a), "r"(b) : "memory"); }

__device__ __forceinline__ void mma16816z(float (&c)[4], const uint32_t (&a)[4], uint32_t b0, uint32_t b1) {
  asm volatile("mma.sync.aligned.m16n8k16.row.col.f32.bf16.bf16.f32 {%0,%1,%2,%3}, {%4,%5,%6,%7}, {%8,%9}, {0f00000000,0f00000000,0f00000000,0f00000000};"
               : "=f"(c[0]), "=f"(c[1]), "=f"(c[2]), "=f"(c[3])
               : "r"(a[0]), "r"(a[1]), "r"(a[2]), "r"(a[3]), "r"(b0), "r"(b1));
}
template <int NB> __device__ __forceinline__ uint2 xch_reduce(uint32_t a, int key, uint32_t* dst, uint32_t tag) {
  uint32_t m[NB][4];
  float c[2][4];
#pragma unroll
  for (int j = 0; j < NB; j++) ldsm4t(m[j], a ^ (j << 5));
#pragma unroll
  for (int j = 0; j < NB; j++) {
    const uint32_t one = key == j ? 0x3f803f80u : 0u;
    if (j < 2) mma16816z(c[j], m[j], one, one);
    else mma16816(c[j & 1], m[j], one, one);
  }
  const uint2 o = make_uint2((__float_as_uint(c[0][0] + c[1][0]) & ~1u) | tag, __float_as_uint(c[0][2] + c[1][2]));
  if (XCH_SEL) st_relaxed64(xch_other(dst), o.x, o.y);
  st_relaxed64(dst, o.x, o.y);
  return o;
}
__device__ __forceinline__ uint32_t xch_sum(const uint2 (&v)[4]) {
  return pack_bf16((__uint_as_float(v[0].x) + __uint_as_float(v[1].x)) + (__uint_as_float(v[2].x) + __uint_as_float(v[3].x)),
                   (__uint_as_float(v[0].y) + __uint_as_float(v[1].y)) + (__uint_as_float(v[2].y) + __uint_as_float(v[3].y)));
}
__device__ __forceinline__ void xch_probe(uint2 (&v)[4], const uint32_t* x, int cl) {
#pragma unroll
  for (int c = 0; c < 4; c++)
    asm volatile("{.reg .pred p; .reg .b64 t; setp.ne.s32 p, %3, %4; mov.b64 t, {%0,%1}; @p ld.relaxed.gpu.global.b64 t, [%2]; mov.b64 {%0,%1}, t;}"
                 : "+r"(v[c].x), "+r"(v[c].y) : "l"(x + c * XCH_CL), "r"(cl), "r"(c) : "memory");
}
__device__ __forceinline__ uint32_t xch_bad(const uint2 (&v)[4]) {
  uint32_t bad;
  asm("{.reg .b32 t; lop3.b32 t, %1, %2, %3, 0x7e; lop3.b32 %0, t, %4, %3, 0xf6;}" : "=r"(bad) : "r"(v[0].x), "r"(v[1].x), "r"(v[2].x), "r"(v[3].x));
  return bad;
}
template <bool TWO> __device__ __forceinline__ uint32_t xch_poll(const uint32_t* x, int cl, uint2 o, const uint32_t* x2, uint2 o2, uint32_t& r2) {
  uint2 v[4] = {o, o, o, o}, w[4] = {o2, o2, o2, o2};
  uint32_t r;
#pragma unroll 1
  for (int it = 0;; it++) {
    xch_probe(v, x, cl);
    if (TWO) xch_probe(w, x2, cl);
    if (it > (1 << 20)) __trap();
    uint32_t bad = xch_bad(v);
    if (TWO) { bad |= xch_bad(w); r2 = xch_sum(w); }
    r = xch_sum(v);
    if (!__any_sync(0xffffffffu, bad & 1)) break;
  }
  return r;
}
constexpr uint32_t CTA1 = 1u << 24;
template <int NSEND, int NPRE> struct XSend {
  uint32_t d[NPRE], b[NPRE];
  static __device__ constexpr uint32_t off(int i) { return ((2 * i + 2 * i / NSEND) & (NSEND - 1)) * CTA1; }
  __device__ __forceinline__ XSend(uint32_t dst, uint32_t bar) {
#pragma unroll
    for (int i = 0; i < NPRE; i++) { d[i] = dst ^ off(i); b[i] = bar ^ off(i); }
    fence_regs(d);
    fence_regs(b);
  }
  __device__ __forceinline__ void send(uint32_t v) {
    asm volatile("" : "+r"(d[0]), "+r"(b[0]));
#pragma unroll
    for (int i = 0; i < NSEND; i++) st_async32(i < NPRE ? d[i] : d[0] ^ off(i), v, i < NPRE ? b[i] : b[0] ^ off(i));
  }
};
__device__ __forceinline__ uint32_t mbar_try_addr(uint32_t bar, uint32_t par, uint32_t good) {
  uint32_t r;
  asm volatile("{.reg .pred p; .reg .b32 t; mbarrier.try_wait.parity.shared::cta.b64 p, [%1], %2; xor.b32 t, %3, 16; selp.b32 %0, %3, t, p;}" : "=r"(r) : "r"(bar), "r"(par), "r"(good) : "memory");
  return r;
}

#ifdef DEV_TRACE
__device__ __noinline__ void trace_sync() {
  if (threadIdx.x == 0) {
    uint32_t g0, g1, c_;
    asm volatile("mov.u32 %0, %%globaltimer_lo;" : "=r"(g0));
    do { asm volatile("mov.u32 %0, %%globaltimer_lo;" : "=r"(g1)); asm volatile("mov.u32 %0, %%clock;" : "=r"(c_)); } while ((g1 >> 10) == (g0 >> 10));
    g_trace_b[(int)blockIdx.x * 4096 + 2160] = g1; g_trace_b[(int)blockIdx.x * 4096 + 2161] = c_;
  }
}
#endif
template <bool MASK>
__device__ __forceinline__ void rmt_softmax_row(const float (&d)[20], int u, int lim, uint32_t pax, uint32_t pam) {
  constexpr float C = 0.08838834764831845f * 1.4426950408889634f;
  float v[10];
#pragma unroll
  for (int j = 0; j < 5; j++) {
    v[2 * j] = (!MASK || j == 4 || 2 * j <= lim) ? d[4 * j + 2 * u] : -INFINITY;
    v[2 * j + 1] = (!MASK || j == 4 || 2 * j + 1 <= lim) ? d[4 * j + 2 * u + 1] : -INFINITY;
  }
  float m = fmaxf(fmaxf(fmaxf(v[0], v[1]), fmaxf(v[2], v[3])), fmaxf(fmaxf(fmaxf(v[4], v[5]), fmaxf(v[6], v[7])), fmaxf(v[8], v[9])));
  m = fmaxf(m, __shfl_xor_sync(0xffffffffu, m, 1));
  m = fmaxf(m, __shfl_xor_sync(0xffffffffu, m, 2));
  const float mc = -m * C;
#pragma unroll
  for (int i = 0; i < 10; i++) v[i] = ex2(fmaf(v[i], C, mc));
  float l = ((v[0] + v[1]) + (v[2] + v[3])) + (((v[4] + v[5]) + (v[6] + v[7])) + (v[8] + v[9]));
  l += __shfl_xor_sync(0xffffffffu, l, 1);
  l += __shfl_xor_sync(0xffffffffu, l, 2);
  const float inv = rcp(l);
  sts128(pax, pack_bf16(v[0] * inv, v[1] * inv), pack_bf16(v[2] * inv, v[3] * inv), pack_bf16(v[4] * inv, v[5] * inv), pack_bf16(v[6] * inv, v[7] * inv));
  sts32(pam, pack_bf16(v[8] * inv, v[9] * inv));
}

__global__ void __launch_bounds__(256, 1) rmt_kernel(const __grid_constant__ RmtParams P) {
  extern __shared__ __align__(1024) uint8_t smem_rmt[];
  const uint32_t sb = (uint32_t)__cvta_generic_to_shared(smem_rmt);
  const int warp = __shfl_sync(0xffffffffu, threadIdx.x >> 5, 0);
  const int lane = __shfl_sync(0xffffffffu, threadIdx.x & 31, threadIdx.x & 31);
  const int w4 = warp & 3, g = lane >> 2, t4 = lane & 3, rho = lane & 7, li = lane >> 3;
  uint32_t rank;
  asm("mov.u32 %0, %%cluster_ctarank;" : "=r"(rank));
  constexpr int ST_O = R_WV, ST_Q = ST_O + 73728, ST_K = ST_Q + R_KR * 2048, ST_V0 = R_OS, ST_V1 = ST_K + R_KR * 2048 - 6 * 2048;
  static_assert(ST_V0 + 6 * 2048 <= R_H && ST_V0 + 6 * 2048 <= ST_Q && ST_V1 + R_VR * 2048 <= R_BAR, "staging");

#ifdef DEV_SYNC
  trace_sync();
#endif
  if (threadIdx.x == 0) {
    if ((sb & 1023) || mapa(sb, 15) != (mapa(sb, 0) ^ (15 * CTA1))) __trap();
    for (int i = 0; i < 6; i++) mbar_init(sb + RB_MEM + 8 * i, 1);
    mbar_init(sb + RB_QK, 5); mbar_init(sb + RB_XF, 1); mbar_init(sb + RB_XF + 8, 1); mbar_init(sb + RB_QXL, 4); mbar_init(sb + RB_W, 1); mbar_init(sb + RB_W + 8, 1);
    asm volatile("fence.mbarrier_init.release.cluster;" ::: "memory");
    mbar_expect(sb + RB_W, 2 * 73728);
    mbar_expect(sb + RB_W + 8, 73728);
  }
  if (threadIdx.x == 32) TRE(blockIdx.x);
  asm volatile("griddepcontrol.launch_dependents;");
  const int cl = blockIdx.x >> 4;
  __syncthreads();
  const int bid = cl * 16 + rank, c0 = bid * 64;
  if (warp == 0) TRG(0);
  auto prefetch_main = [&]() {
    asm volatile("cp.async.bulk.prefetch.L2.global [%0], 4096;" ::"l"(P.ckv + (bid * 8 + warp) * 2048) : "memory");
    asm volatile("cp.async.bulk.prefetch.L2.global [%0], 1280;" ::"l"(P.wuk + (bid * 8 + warp) * HDALL) : "memory");
    asm volatile("cp.async.bulk.prefetch.L2.global [%0], 1280;" ::"l"(P.wuv + (bid * 8 + warp) * HDALL) : "memory");
  };
  if (PF_MAIN == 1 && elect()) prefetch_main();
  __syncwarp();
  if (B_DELAY > 0) __nanosleep(B_DELAY);
  if (elect()) {
    for (int i = warp; i < 9; i += 8) tma2d(sb + ST_O + i * 8192, &P.wo, i * 64, c0, sb + RB_W + 8);
    if (warp == 1 && bid < 27) asm volatile("cp.async.bulk.prefetch.tensor.2d.L2.global [%0, {%1,%2}];" ::"l"(bid < 18 ? &P.x : &P.mem), "r"(bid % 9 * 64), "r"(bid / 9 % 2 * 32) : "memory");
    for (int k = warp; k < 36; k += 8) {
      const int o = qk_slot(k) * 2048;
      tma2d(sb + (qk_in_reg(k) ? ST_Q : R_WQ) + o, &P.wq, c0, k * 16, sb + RB_W);
      tma2d(sb + (qk_in_reg(k) ? ST_K : R_WK) + o, &P.wk, c0, k * 16, sb + RB_W);
    }
    if (PF_V) for (int i = warp; i < 36; i += 8) asm volatile("cp.async.bulk.prefetch.tensor.2d.L2.global [%0, {%1,%2}];" ::"l"(&P.wv), "r"(c0), "r"(i * 16) : "memory");
    if (PF_MAIN == 2) prefetch_main();
  }
  __syncwarp();
  uint32_t wa = sb + ((li >> 1) * 8 + rho) * 128 + (((2 * w4 + (li & 1)) ^ rho) << 4);
  uint32_t la = sb + rho * 128 + ((li ^ rho) << 4);
  int ln = lane;
  if (warp == 0) TRG(1);
  uint32_t* xb = (uint32_t*)(((uint64_t)g_xch + 8191) & ~8191ull) + (rank * 4 + w4) * 2048;

  if (warp < 4) {
    if (elect()) {
#pragma unroll
      for (int i = 0; i < 4; i++) mbar_init(sb + RB_TF + 32 * w4 + 8 * i, w4 == 3 ? 4 : 1);
      if (w4 == 0) {
        mbar_init(sb + RB_TR, 1);
        mbar_expect(sb + RB_TR, 49152);
      }
      asm volatile("fence.mbarrier_init.release.cluster;" ::: "memory");
      if (XCH_SEL) {
        st_relaxed32(xb + 2 * XCH_SLOT + cl * 32, 0u);
        st_relaxed32(xb + 2 * XCH_SLOT + cl * 32 + 1024, 0u);
        sts32(sb + RB_SEL + 8 * w4, ~0u);
        sts32(sb + RB_SEL + 8 * w4 + 4, ~0u);
      }
    }
    __syncwarp();
    mbar_wait(sb + RB_W, 0);
    if (warp == 0) TRG(2);
    uint32_t wq[R_KR][4], wk[R_KR][4];
#pragma unroll
    for (int k = 0; k < R_KR; k++) { ldsm4t(wq[k], wa + ST_Q + k * 2048); ldsm4t(wk[k], wa + ST_K + k * 2048); }
    fence_async_smem();
    bar_sync(NB_P3, 256);
    asm volatile("barrier.cluster.arrive.relaxed.aligned;" ::: "memory");
    if (w4 < 2 && elect()) {
      mbar_expect(sb + RB_XF + 8 * w4, 9 * 4096);
      for (int i = 0; i < 9; i++) tma2d(sb + R_H + hoff(i) + w4 * 5120, &P.x, i * 64, w4 * 32, sb + RB_XF + 8 * w4);
    }
    if (w4 == 3 && elect()) {
      mbar_expect(sb + RB_QK, QK_TX);
      for (int i = 0; i < 5; i++) mbar_expect(sb + RB_MEM + 8 * i, i < 4 ? 2048 : 1024);
      for (int i = 0; i < 9; i++) tma2d(sb + R_HM + hoff(i), &P.mem, i * 64, 0, sb + RB_MEM + 8 * (i >> 1));
    }
    if (w4 == 2) sts128(sb + R_PS + (8 + lane) * 128 + ((5 ^ rho) << 4), 0u, 0u, 0u, 0u);
    __syncwarp();
    uint32_t qm = __shfl_sync(0xffffffffu, sb + R_QS + (rank & 1) * R_HS + (w4 * 16 + g) * 16 + t4 * 4, lane);
    const uint32_t peer = mapa(sb, rank ^ 1) - sb;

    uint32_t aq[P1_PRE][4], ak[P1_PRE][4];
    auto preload = [&]() {
#pragma unroll
      for (int i = 0; i < P1_PRE; i++) { ldsm4t(aq[i], wa + R_WQ + i * 2048); ldsm4t(ak[i], wa + R_WK + i * 2048); }
    };
    auto chain = [&](int s) {
      const bool LAST = s == 63;
      float cq[2][4], ck[2][4];
      for (;;) {
        uint32_t b[3][4];
        if (!PRE_EARLY) preload();
        mbar_wait(sb + RB_MEM, s & 1);
        TRB(0);
        uint32_t lb = la, bad = 0;
        ldsm4(b[0], lb + R_HM + hoff(0));
        ldsm4(b[1], (lb ^ 64) + R_HM + hoff(0));
#pragma unroll
        for (int hc = 0; hc < 18; hc++) {
          if (hc + 2 < 18) {
            if ((hc & 3) == 2) { lb = mbar_try_addr(sb + RB_MEM + 8 * ((hc + 2) >> 2), s & 1, la); bad |= lb ^ la; }
            ldsm4(b[(hc + 2) % 3], ((hc & 1) ? (lb ^ 64) : lb) + R_HM + hoff((hc + 2) >> 1));
          }
#pragma unroll
          for (int j = 0; j < 2; j++) {
            const int k = 2 * hc + j, sl = qk_slot(k);
            if (qk_in_reg(k)) {
              mma16816(cq[j], wq[sl], b[hc % 3][2 * j], b[hc % 3][2 * j + 1]);
              mma16816(ck[j], wk[sl], b[hc % 3][2 * j], b[hc % 3][2 * j + 1]);
            } else {
              static_assert(nsm(0) == 2, "first two steps come from shared memory");
              if (hc == 0) {
                mma16816z(cq[j], aq[j], b[0][2 * j], b[0][2 * j + 1]);
                mma16816z(ck[j], ak[j], b[0][2 * j], b[0][2 * j + 1]);
              } else {
                mma16816(cq[j], aq[sl % P1_PRE], b[hc % 3][2 * j], b[hc % 3][2 * j + 1]);
                mma16816(ck[j], ak[sl % P1_PRE], b[hc % 3][2 * j], b[hc % 3][2 * j + 1]);
              }
              if (sl + P1_PRE < R_NS) { ldsm4t(aq[sl % P1_PRE], wa + R_WQ + (sl + P1_PRE) * 2048); ldsm4t(ak[sl % P1_PRE], wa + R_WK + (sl + P1_PRE) * 2048); }
            }
          }
        }
        if (!__any_sync(0xffffffffu, bad)) break;
#pragma unroll 1
        for (int i = 1; i < 5; i++) mbar_wait(sb + RB_MEM + 8 * i, s & 1);
        if (PRE_EARLY) preload();
      }
      const uint32_t q0 = pack_bf16(cq[0][0] + cq[1][0], cq[0][1] + cq[1][1]), q1 = pack_bf16(cq[0][2] + cq[1][2], cq[0][3] + cq[1][3]);
      const uint32_t k0 = pack_bf16(ck[0][0] + ck[1][0], ck[0][1] + ck[1][1]), k1 = pack_bf16(ck[0][2] + ck[1][2], ck[0][3] + ck[1][3]);
      const uint32_t qp = qm + peer, bp = sb + RB_QK + peer;
      st_async32(qp, q0, bp);
      st_async32(qp + 128, q1, bp);
      st_async32(qp + 10 * R_GS, k0, bp);
      st_async32(qp + 10 * R_GS + 128, k1, bp);
      sts32(qm, q0);
      sts32(qm + 128, q1);
      sts32(qm + 10 * R_GS, k0);
      sts32(qm + 10 * R_GS + 128, k1);
      bar_arrive(NB_P1, 256);
      fence_async_smem();
      __syncwarp();
      arrive_elect(sb + RB_QK);
      TRB(1);
      float d[20];
#pragma unroll
      for (int i = 0; i < 20; i++) d[i] = 0.f;
      constexpr uint32_t HI = R_GS >> 4;
      const uint32_t qd = desc_lo(sb + R_QS, 128);
      mbar_wait(sb + RB_QK, s & 1);
      TRB(16);
      wg_fence();
#pragma unroll
      for (int k = 0; k < 8; k++) wgmma_ss_n40_a1b1(d, mk_desc(qd + (k >> 2) * (R_HS >> 4) + (k & 3) * 16, HI), mk_desc(qd + (k >> 2) * (R_HS >> 4) + (k & 3) * 16 + 6 * HI, HI), k != 0);
      wg_commit();
      bar_arrive(NB_S, 256);
      if (LAST) asm volatile("barrier.cluster.arrive.relaxed.aligned;" ::: "memory");
      const int ln = (qm >> 2) & 31, tt = ln & 3;
      if (w4 == 0) {
        const int gg = ln >> 2;
        const uint32_t pa = sb + R_PS + gg * 128;
        const uint32_t pax = pa + ((tt ^ gg) << 4), pam = pa + ((4 ^ gg) << 4) + tt * 4;
        wg_wait<0>();
        fence_regs(d);
        TRB(17);
        rmt_softmax_row<false>(d, 0, 0, pax, pam);
        bar_arrive(NB_PM, 160);
        TRB(18);
      } else if (w4 < 3) {
        const int tq = (ln & 24) + 4 * (w4 - 1) + ((ln >> 2) & 1), r7 = tq & 7;
        const uint32_t pa = sb + R_PS + (8 + tq) * 128;
        wg_wait<0>();
        fence_regs(d);
        rmt_softmax_row<true>(d, 0, tq - 8 * tt, pa + ((tt ^ r7) << 4), pa + ((4 ^ r7) << 4) + tt * 4);
        rmt_softmax_row<true>(d, 1, tq + 2 - 8 * tt, pa + 256 + ((tt ^ r7 ^ 2) << 4), pa + 256 + ((6 ^ r7) << 4) + tt * 4);
        fence_async_smem();
        bar_arrive(NB_PX, 192);
        TRW(15, 1);
      } else {
#ifdef DEV_END
        if ((s & ~8) == 0 && ln == 0) TRE((s ? 388 : 192) + blockIdx.x);
#endif
        if (!LAST) {
          if (ln < 7) mbar_expect(sb + RB_MEM + 8 * ln, ln == 6 ? QK_TX : ln == 5 ? 9216 : ln == 4 ? 1024 : 2048);
          if (ln == 11 && s < 62) mbar_expect(sb + RB_XF + 8 * (s & 1), 9 * 4096);
          __syncwarp();
        }
        wg_wait<0>();
        fence_regs(d);
      }
    };
    auto bulk = [&](int s) {
      const bool FIRST = s < 0;
      float dq[16], dk[16];
#pragma unroll
      for (int i = 0; i < 16; i++) dq[i] = dk[i] = 0.f;
      mbar_wait(sb + RB_XF + 8 * ((s + 1) & 1), ((s + 1) >> 1) & 1);
      const uint32_t hd = desc_lo(sb + R_H + ((s + 1) & 1) * 5120, 16), wd = desc_lo(sb + R_WQ, 16);
      auto bdesc = [&](int k) { return mk_desc(hd + (hoff(k >> 2) >> 4) + (k & 3) * 2, DHI_SW128); };
      const uint32_t qx = qm + 2 * R_GS + (qm & 12) * (R_GS / 4 - 1);
      if (XCH_SEL && (uint32_t)s < XCH_NP && elect()) {
        uint32_t v, *p = (uint32_t*)(((uint64_t)g_xch + 8191) & ~8191ull) + (rank * 4 + w4) * 2048 + 2 * XCH_SLOT + cl * 32 + (s & 1) * 1024;
        const uint32_t a = sb + RB_SEL + 8 * w4 + 4 * (s & 1), t0 = clock();
        asm volatile("atom.relaxed.gpu.global.add.u32 %0, [%1], 1;" : "=r"(v) : "l"(p) : "memory");
        if (v >= XCH_NP) __trap();
        sts32(a, min(lds32(a), (uint32_t)clock() - t0));
      }
      __syncwarp();
      if (s == 60 && w4 < 2) asm volatile("prefetch.tensormap [%0];" ::"l"(&P.ox64 + w4) : "memory");
      if (!FIRST) bar_sync(NB_P3, 256);
      TRB(2);
      wg_fence();
      static_for<0, 73 - B_SKIP>([&](auto i_) {
        constexpr int i = decltype(i_)::value;
        constexpr char c = B_SEQ[i];
        constexpr int r = seq_count(c, i), nq = seq_count('q', i) + seq_count('Q', i), nk = seq_count('k', i) + seq_count('K', i);
        if constexpr (c == 'q') wgmma_rs_n32_b0(dq, wq[r][0], wq[r][1], wq[r][2], wq[r][3], bdesc(qk_step(r, true)), nq != 0);
        if constexpr (c == 'k') wgmma_rs_n32_b0(dk, wk[r][0], wk[r][1], wk[r][2], wk[r][3], bdesc(qk_step(r, true)), nk != 0);
        if constexpr (c == 'Q') wgmma_ss_n32_a1b0(dq, mk_desc(wd + r * 128, DHI_SW128), bdesc(qk_step(r, false)), nq != 0);
        if constexpr (c == 'K') wgmma_ss_n32_a1b0(dk, mk_desc(wd + (R_NS + r) * 128, DHI_SW128), bdesc(qk_step(r, false)), nk != 0);
        if constexpr (c == '|') {
          if (!FIRST) bar_sync(NB_RD, 256);
          TRB(6);
        }
      });
      wg_commit();
      if (FIRST) asm volatile("barrier.cluster.wait.aligned;" ::: "memory");
      if (PRE_EARLY) preload();
      wg_wait<0>();
      fence_regs(dq);
      fence_regs(dk);
      TRB(3);
#pragma unroll
      for (int r = 0; r < 2; r++) {
        sts128(qx + r * 128, pack_bf16(dq[2 * r], dq[2 * r + 1]), pack_bf16(dq[4 + 2 * r], dq[5 + 2 * r]), pack_bf16(dq[8 + 2 * r], dq[9 + 2 * r]), pack_bf16(dq[12 + 2 * r], dq[13 + 2 * r]));
        sts128(qx + 4 * R_GS + r * 128, pack_bf16(dk[2 * r], dk[2 * r + 1]), pack_bf16(dk[4 + 2 * r], dk[5 + 2 * r]), pack_bf16(dk[8 + 2 * r], dk[9 + 2 * r]), pack_bf16(dk[12 + 2 * r], dk[13 + 2 * r]));
      }
      __syncwarp();
      arrive_elect(sb + RB_QXL);
      TRB(4);
    };
    TRG(3);
#pragma unroll 1
    for (int s = -1; s < 63;) {
      asm volatile("" : "+r"(wa), "+r"(la), "+r"(qm));
      bulk(s);
      s++;
#ifdef DEV_TRS
      TRG(16 + s);
#endif
      chain(s);
    }
#ifdef DEV_TRACE
    bar_sync(NB_S, 256);
    for (int i = threadIdx.x; i < 16 * 32; i += 128) g_trace_b[bid * 4096 + i] = lds32(sb + R_QS + R_GS + ((i >> 8) ^ 1) * R_HS + (i & 255) * 4);
#endif
  } else {
    uint32_t wo[9][4][4], wv[R_VR][4];
    mbar_wait(sb + RB_W + 8, 0);
#pragma unroll
    for (int i = 0; i < 9; i++) {
      const int T = i < 8 ? 8 * (i >> 1) + 2 * w4 + (i & 1) : 32 + 2 * (w4 & 1) + (w4 >> 1);
      const int quad = i < 8 ? (g >> 2) * 2 + (g & 1) : g & 3, odd = i < 8 ? (g >> 1) & 1 : g >> 2;
      const uint32_t a = sb + ST_O + (T >> 2) * 8192 + t4 * 256 + (quad & 1) * 8;
      const uint32_t ch = (T & 3) * 2 + (quad >> 1), sel = odd ? 0x7632 : 0x5410;
      const uint32_t a0 = a + ((ch ^ (2 * t4)) << 4), a1 = a + 128 + ((ch ^ (2 * t4 + 1)) << 4);
#pragma unroll
      for (int k = 0; k < 8; k++) {
        const uint2 x = lds64(a0 + k * 1024), y = lds64(a1 + k * 1024);
        wo[i][k >> 1][(k & 1) * 2] = __byte_perm(x.x, y.x, sel);
        wo[i][k >> 1][(k & 1) * 2 + 1] = __byte_perm(x.y, y.y, sel);
      }
    }
    fence_async_smem();
    bar_arrive(NB_P3, 256);
    bar_sync(NB_O, 128);
    if (w4 == 0 && elect()) mbar_expect(sb + RB_W + 8, 73728);
    if (elect())
      for (int k = w4; k < 36; k += 4) {
        const int sl = v_slot(k);
        tma2d(sb + (v_in_reg(k) ? (sl < 6 ? ST_V0 : ST_V1) : R_WV) + sl * 2048, &P.wv, c0, k * 16, sb + RB_W + 8);
      }
    __syncwarp();
    mbar_wait(sb + RB_W + 8, 1);
#pragma unroll
    for (int r = 0; r < R_VR; r++) ldsm4t(wv[r], wa + (r < 6 ? ST_V0 : ST_V1) + r * 2048);
    fence_async_smem();
    asm volatile("barrier.cluster.arrive.relaxed.aligned;" ::: "memory");
    const uint32_t sb0 = mapa(sb, 0), tok = rank & 7;
    uint32_t rsb = mapa(sb + RB_RS, (w4 & 1) * 8 + 2 * t4);
    const uint32_t rrow = rank ^ ((t4 & 1) << 3) ^ (t4 & 2), nrow = rank ^ ((t4 & 1) << 2);
    uint32_t rsA = rsb + (R_RS - RB_RS) + rrow * 128 + (((w4 >> 1) * 64 + g * 8) ^ ((rrow & 7) << 4));
    uint32_t rsN = rsb + (R_RS + 8192 - RB_RS) + nrow * 64 + (((w4 >> 1) * 32 + g * 4) ^ (((nrow >> 1) & 3) << 4));
    const uint32_t cp = 16 * (t4 >> 1) + 8 * ((g >> 1) & 1) + 4 * (t4 & 1) + 2 * (g >> 2) + (g & 1);
    uint32_t agd = sb0 + R_HM + tok * 128 + hoff(2 * w4 + (cp >> 4)) + ((((rank >> 3) * 4 + ((cp & 15) >> 2)) ^ tok) << 4) + (cp & 3) * 4;
    xb += lane * 2;
    uint32_t vx[8];
#pragma unroll
    for (int i = 0; i < 8; i++) vx[i] = 0;

    auto step = [&](int s) {
      const bool FIRST = s < 0, LAST = s == 63, MID = !FIRST && !LAST;
      const int par = (s + 1) & 1;
      float d[20];
#pragma unroll
      for (int i = 0; i < 20; i++) d[i] = 0.f;
      if (XCH_SEL && s == XCH_NP) {
        const uint2 t = lds64(sb + RB_SEL + 8 * w4);
        if (t.y < t.x) xb += 1024;
      }
      if (!LAST) mbar_wait(sb + RB_XF + 8 * par, ((s + 1) >> 1) & 1);
      const uint32_t hd = desc_lo(sb + R_H + par * 4096, 16), vd = desc_lo(sb + R_WV, 16);
      if (!FIRST) {
        if (w4 == 0) {
          mbar_wait(sb + RB_QXL, s & 1);
          mbar_wait(sb + RB_MEM + QX_AFTER * 8, s & 1);
          fence_async_smem();
          if (elect()) {
            const uint32_t src = sb + R_QS + (rank & 1) * R_HS + 2 * R_GS, dst = mapa(src, rank ^ 1), bar = mapa(sb + RB_QK, rank ^ 1), cut = 256 + rank * 512;
            asm volatile("cp.async.bulk.shared::cluster.shared::cta.mbarrier::complete_tx::bytes [%0], [%1], %2, [%3];" ::"r"(dst + cut), "r"(src + cut), "r"(8 * R_GS - cut), "r"(bar) : "memory");
            asm volatile("cp.async.bulk.shared::cluster.shared::cta.mbarrier::complete_tx::bytes [%0], [%1], %2, [%3];" ::"r"(dst), "r"(src), "r"(cut), "r"(bar) : "memory");
          }
          __syncwarp();
          TRW(7, 0);
        }
#pragma unroll
        for (int i = 0; i < 5; i++) { mbar_wait(sb + RB_MEM + 8 * i, s & 1); if (i == 4) TRW(30, 2); }
        fence_async_smem();
        bar_sync(NB_P1, 256);
      }
      wg_fence();
#pragma unroll
      for (int k = 0; k < 36; k++) {
        if (k >= 36 - V_SKIP) continue;
        if (k == V_N1 && !FIRST) bar_sync(NB_S, 256);
        const uint64_t db = mk_desc(hd + (hoff(k >> 2) >> 4) + (k & 3) * 2, DHI_SW128);
        if (v_in_reg(k)) wgmma_rs_n40_b0(d, wv[v_slot(k)][0], wv[v_slot(k)][1], wv[v_slot(k)][2], wv[v_slot(k)][3], db, 1);
        else wgmma_ss_n40_a1b0(d, mk_desc(vd + v_slot(k) * 128, DHI_SW128), db, k != 0);
      }
      wg_commit();
      TRB(8);
      uint32_t vm0, vm1, vn[8];
      auto pack_v = [&]() {
#pragma unroll
        for (int i = 0; i < 8; i++) vn[i] = par ? pack_bf16(d[2 * i + 4], d[2 * i + 5]) : pack_bf16(d[2 * i], d[2 * i + 1]);
      };
      if (MID) {
        float o[4] = {0.f, 0.f, 0.f, 0.f};
        uint32_t b0[4], b1[4];
        bar_sync(NB_PM, 160);
        ldsm4(b0, la + R_PS);
        ldsm4(b1, (la ^ 64) + R_PS);
        {
          const uint32_t x0[4] = {vx[0], vx[1], vx[2], vx[3]}, x1[4] = {vx[4], vx[5], vx[6], vx[7]};
          float o2[4] = {0.f, 0.f, 0.f, 0.f};
          wg_wait<0>();
          fence_regs(d);
          TRB(9);
          mma16816(o, x0, b0[0], b0[1]);
          mma16816(o2, x1, b0[2], b0[3]);
          vm0 = par ? pack_bf16(d[0], d[1]) : pack_bf16(d[16], d[17]);
          vm1 = par ? pack_bf16(d[2], d[3]) : pack_bf16(d[18], d[19]);
          float o3[4] = {0.f, 0.f, 0.f, 0.f};
          mma1688(o3, vm0, vm1, b1[0]);
          stsm2t(wa + R_OS, pack_bf16(o[0] + o2[0] + o3[0], o[1] + o2[1] + o3[1]), pack_bf16(o[2] + o2[2] + o3[2], o[3] + o2[3] + o3[3]));
        }
        if (PACK_AT == 1) { pack_v(); fence_regs(vn); }
        bar_sync(NB_O, 128);
        TRB(11);
        ldsm4(b0, la + R_OS);
        ldsm4(b1, (la ^ 64) + R_OS);
        auto send = [&](int j, const float (&c0_)[4], const float (&c1_)[4]) {
          st_async64(rsA + j * 2048, pack_bf16(c0_[0], c0_[2]), pack_bf16(c1_[0], c1_[2]), rsb);
          st_async64(rsA + j * 2048 + CTA1, pack_bf16(c0_[1], c0_[3]), pack_bf16(c1_[1], c1_[3]), rsb + CTA1);
        };
        auto tile = [&](float (&c)[4], int i, int k) {
          if (k == 0) mma16816z(c, wo[i][0], b0[0], b0[1]);
          else mma16816(c, wo[i][k], k < 2 ? b0[2 * k] : b1[2 * k - 4], k < 2 ? b0[2 * k + 1] : b1[2 * k - 3]);
        };
        {
          float c[4][4];
          mma16816z(c[0], wo[0][0], b0[0], b0[1]);
          mma16816z(c[1], wo[1][0], b0[0], b0[1]);
          mma16816z(c[2], wo[0][2], b1[0], b1[1]);
          mma16816z(c[3], wo[1][2], b1[0], b1[1]);
          mma16816(c[0], wo[0][1], b0[2], b0[3]);
          mma16816(c[1], wo[1][1], b0[2], b0[3]);
          mma16816(c[2], wo[0][3], b1[2], b1[3]);
          mma16816(c[3], wo[1][3], b1[2], b1[3]);
          if (PACK_AT == 0) pack_v();
#pragma unroll
          for (int i = 0; i < 4; i++) { c[0][i] += c[2][i]; c[1][i] += c[3][i]; }
          send(0, c[0], c[1]);
          if (PACK_AT == 0) fence_regs(vn);
        }
        if (P3_F & 1) sched_fence(rsb);
        TRB(13);
        {
          float c[3][4];
#pragma unroll
          for (int k = 0; k < 4; k++) { tile(c[0], 8, k); tile(c[1], 2, k); tile(c[2], 3, k); }
          st_async32(rsN, pack_bf16(c[0][0], c[0][2]), rsb);
          st_async32(rsN + CTA1, pack_bf16(c[0][1], c[0][3]), rsb + CTA1);
          send(1, c[1], c[2]);
        }
        if (P3_F & 2) sched_fence(la);
        {
          float c[4][4];
#pragma unroll
          for (int k = 0; k < 4; k++)
#pragma unroll
            for (int i = 0; i < 4; i++) tile(c[i], 4 + i, k);
          if (P3_EARLY == 1) { sched_fence(rsA); bar_arrive(NB_P3, 256); }
          send(2, c[0], c[1]);
          send(3, c[2], c[3]);
          if (P3_EARLY == 2) bar_arrive(NB_P3, 256);
        }
        TRB(12);
      } else {
        if (LAST) bar_sync(NB_PM, 160);
        wg_wait<0>();
        fence_regs(d);
        if (LAST) asm volatile("barrier.cluster.arrive.relaxed.aligned;" ::: "memory");
        vm0 = pack_bf16(d[16], d[17]);
        vm1 = pack_bf16(d[18], d[19]);
        pack_v();
      }
      if (FIRST) {
        asm volatile("barrier.cluster.wait.aligned;" ::: "memory");
        TRG(7);
      } else {
        float e[16];
#pragma unroll
        for (int i = 0; i < 16; i++) e[i] = 0.f;
        uint32_t z0 = 0, z1 = 0;
        asm volatile("" : "+r"(z0), "+r"(z1), "+r"(vm0), "+r"(vm1));
        const uint32_t pd = desc_lo(sb + R_PS + 1024, 16);
        fence_regs(vx);
        bar_sync(NB_PX, 192);
        wg_fence();
        wgmma_rs_n32_b0(e, vx[0], vx[1], vx[2], vx[3], mk_desc(pd, DHI_SW128), 0);
        wgmma_rs_n32_b0(e, vx[4], vx[5], vx[6], vx[7], mk_desc(pd + 2, DHI_SW128), 1);
        wgmma_rs_n32_b0(e, vm0, vm1, z0, z1, mk_desc(pd + 4, DHI_SW128), 1);
        wg_commit();
        if (!P3_EARLY && !LAST) bar_arrive(NB_P3, 256);
        wg_wait<0>();
        fence_regs(e);
        fence_regs(vx);
        bar_sync(NB_O, 128);
        stsm4t(wa + R_PS + 1024, pack_bf16(e[0], e[1]), pack_bf16(e[2], e[3]), pack_bf16(e[4], e[5]), pack_bf16(e[6], e[7]));
        stsm4t(wa + R_PS + 3072, pack_bf16(e[8], e[9]), pack_bf16(e[10], e[11]), pack_bf16(e[12], e[13]), pack_bf16(e[14], e[15]));
        TRB(14);
      }
      auto store_x = [&]() {
        fence_async_smem();
        if (w4 == 2) bar_sync(NB_O2, 128); else bar_arrive(NB_O2, 128);
        if (w4 == 2 && elect()) {
          asm volatile("cp.async.bulk.tensor.2d.global.shared::cta.bulk_group [%0, {%1,%2}], [%3];" ::"l"(&P.ox), "r"(c0), "r"(3 * SEQ + s * 32), "r"(sb + R_PS + 1024) : "memory");
          asm volatile("cp.async.bulk.commit_group;" ::: "memory");
        }
        __syncwarp();
      };
      if (MID) {
        const uint32_t tag = ((s >> 1) & 1) ^ 1;
        uint32_t* x = xb + (s & 1) * XCH_SLOT;
        uint32_t* xw = x + cl * XCH_CL;
        const int src = (ln & 7) + (ln >> 4) * 8, hf = (ln >> 3) & 1;
        const uint32_t ra = sb + R_RS + w4 * 2048 + src * 128 + ((hf ^ (ln & 7)) << 4);
        auto delay = [&](uint32_t t0) {
          while ((uint32_t)clock() - t0 < POLL_DELAY + w4 * POLL_STAG) {}
        };
        uint32_t rn;
        const uint32_t agb = sb0 + RB_MEM + 8 * w4 + (uint32_t)(ln >> 5);
        if (w4 == 3) {
          const int cn = 8 * (ln & 1) + (ln >> 2), no = 64 + 2 * (cn - ln);
          const uint32_t rb = sb + R_RS + 8192 + src * 64 + ((hf ^ ((ln >> 1) & 3)) << 4);
          mbar_wait(sb + RB_RS, s & 1);
          const uint2 o = xch_reduce<4>(ra, ln >> 3, xw, tag);
          const uint2 on = xch_reduce<2>(rb, hf, xw + no, tag);
          const uint32_t t0 = clock();
          bar_arrive(NB_RD, 256);
          TRW(27, 3);
          store_x();
          const uint32_t off = (ln & 2) * 4 * CTA1;
          const uint32_t agn = sb0 + R_HM + tok * 128 + hoff(8) + ((((rank >> 3) * 4 + (cn >> 2)) ^ tok) << 4) + (cn & 3) * 4;
          XSend<16, 6> xs(agd, agb);
          delay(t0);
          const uint32_t r = xch_poll<true>(x, cl, o, x + no, on, rn);
          TRW(28, 3);
          xs.send(r);
          XSend<8, 1>(agn ^ off, (agb + 8) ^ off).send(rn);
          TRW(22, 3);
        } else {
          mbar_wait(sb + RB_RS, s & 1);
          TRB(19);
          const uint2 o = xch_reduce<4>(ra, ln >> 3, xw, tag);
          const uint32_t t0 = clock();
          bar_arrive(NB_RD, 256);
          TRB(25);
          store_x();
          if (w4 == 1 && rank < 9 && s < 62 && elect()) {
            tma2d_mc(sb + R_H + hoff(rank) + (s & 1) * 5120, &P.x, rank * 64, (s + 2) * 32, sb + RB_XF + 8 * (s & 1), 0xffff);
            asm volatile("cp.async.bulk.prefetch.tensor.2d.L2.global [%0, {%1,%2}];" ::"l"(&P.x), "r"(rank * 64), "r"(min(s + 3 + cl, 63) * 32) : "memory");
          }
          __syncwarp();
          XSend<16, 12> xs(agd, agb);
          delay(t0);
          asm volatile("cp.async.bulk.wait_group.read 0;" ::: "memory");
          const uint32_t r = xch_poll<false>(x, cl, o, x, o, rn);
          TRB(26); TRW(10, 1); TRW(20, 2);
          xs.send(r);
          TRB(21); TRW(23, 1); TRW(24, 2);
          if (w4 == 2 && ((s & 3) == 3 || s == 61)) {
            asm volatile("cp.async.bulk.wait_group 0;" ::: "memory");
#if PUB_REL
            asm volatile("{.reg .pred q; elect.sync _|q, 0xffffffff; @q red.release.gpu.global.add.u32 [%0], 1;}" ::"l"(&g_sync[SY_OX + (s >> 2)]) : "memory");
#else
            asm volatile("{.reg .pred q; elect.sync _|q, 0xffffffff; @q red.relaxed.gpu.global.add.u32 [%0], 1;}" ::"l"(&g_sync[SY_OX + (s >> 2)]) : "memory");
#endif
          }
        }
      }
#pragma unroll
      for (int i = 0; i < 8; i++) vx[i] = vn[i];
    };
    TRG(5);
#pragma unroll 1
    for (int s = -1; s < 64; s++) {
      asm volatile("" : "+r"(wa), "+r"(la), "+r"(rsb), "+r"(rsA), "+r"(rsN), "+r"(agd), "+r"(ln), "+l"(xb));
      step(s);
    }
    if (threadIdx.x == 128) TRE(64 + blockIdx.x);
    fence_async_smem();
    bar_sync(NB_O2, 128);
    if (w4 == 2) {
      if (elect()) {
        asm volatile("cp.async.bulk.tensor.2d.global.shared::cta.bulk_group [%0, {%1,%2}], [%3];" ::"l"(&P.ox), "r"(c0), "r"(3 * SEQ + 63 * 32), "r"(sb + R_PS + 1024) : "memory");
        asm volatile("cp.async.bulk.commit_group;" ::: "memory");
        asm volatile("cp.async.bulk.wait_group 0;" ::: "memory");
#if PUB_REL
        asm volatile("red.release.gpu.global.add.u32 [%0], 1;" ::"l"(&g_sync[SY_OX + 16]) : "memory");
#else
        asm volatile("red.relaxed.gpu.global.add.u32 [%0], 1;" ::"l"(&g_sync[SY_OX + 16]) : "memory");
#endif
      }
      __syncwarp();
    }
    {
      uint32_t* z = xb + XCH_SLOT + cl * XCH_CL;
      st_relaxed64(z, 0u, 0u);
      st_relaxed32(z + 64 - ln, 0u);
      if (XCH_SEL) { st_relaxed64(xch_other(z), 0u, 0u); st_relaxed32(xch_other(z + 64 - ln), 0u); }
    }
#ifdef DEV_TRACE
    bar_sync(NB_S, 256);
#endif
  }
  {
    uint32_t rank, cl, sb, warp;
    asm volatile("mov.u32 %0, %%cluster_ctarank;" : "=r"(rank));
    asm volatile("{.reg .b32 t; mov.u32 t, %%ctaid.x; shr.u32 %0, t, 4;}" : "=r"(cl));
    asm volatile("{.reg .b64 t; cvta.to.shared.u64 t, %1; cvt.u32.u64 %0, t;}" : "=r"(sb) : "l"(smem_rmt));
    asm volatile("{.reg .b32 t; mov.u32 t, %%tid.x; shr.u32 t, t, 5; shfl.sync.idx.b32 %0, t, 0, 31, -1;}" : "=r"(warp));
    const int w4 = warp & 3;
    const int lane = threadIdx.x & 31, wg = warp >> 2, u = rank >> 1, blk = cl == 3 ? 12 + (rank & 1) : 14 + (rank & 1), nn = min(cl, 2u);
    constexpr int T_E = 40960, T_R = 4 * T_E;
    auto load_w = [&](int kb) {
      const uint32_t fb = sb + RB_TF + 8 * (kb & 3);
      mbar_expect(fb, 24576);
      tma3d_mc(sb + (kb & 3) * T_E + 16384 + (rank & 1) * 12288, &P.wo3, 0, u * 512 + kb * 64 + (rank & 1) * 32, nn * 3, fb, 3 << (rank & 14));
    };
    auto load_a = [&](int kb, int h) {
      const uint32_t fb = sb + RB_TF + 32 + 32 * h + 8 * (kb & 3);
      mbar_expect(fb, 8192);
      tma2d(sb + (kb & 3) * T_E + h * 8192, &P.ox64, u * 512 + kb * 64, 3 * SEQ + blk * 128 + h * 64, fb);
    };
    const uint32_t te = mapa(sb + RB_TE, (rank & 14) + (lane & 1));
    const uint32_t ra = mapa(sb + T_R + u * 6144 + ((lane ^ u) << 4), 2 * warp + (rank & 1)), rb = mapa(sb + RB_TR, 2 * warp + (rank & 1));
    const int r = lane & 7, m = lane >> 3, g = lane >> 2;
    const uint32_t la = sb + T_R + r * 6144 + wg * 3072 + (m >> 1) * 512;
    uint32_t* out = P.out + (blk * 128 + u * 16 + 2 * w4 + 8 * (g & 1)) * DM + DM / 2 + nn * 96 + wg * 48 + (g >> 1) * 4 + (lane & 3);
    float acc[96];
#pragma unroll
    for (int i = 0; i < 96; i++) acc[i] = 0.f;
    if (w4 == 0 && elect())
      for (int it = 0; ld_acquire(g_sync + SY_OX + blk + (blk == 15 ? wg : 0)) < OX_TARGET; it++)
        if (it > (1 << 22)) __trap();
    __syncwarp();
    asm volatile("barrier.cluster.wait.aligned;\nbarrier.cluster.arrive.relaxed.aligned;" ::: "memory");
    TRT(0, 0);
    if (w4 == 0 && elect()) {
#pragma unroll 1
      for (int kb = 0; kb < 4; kb++) {
        if (wg == 0) load_w(kb);
        load_a(kb, wg);
      }
    }
    __syncwarp();
    TRT(1, 4);
#pragma unroll 1
    for (int kb = 0; kb < 8; kb++) {
      const uint32_t st = sb + (kb & 3) * T_E, a = desc_lo(st + wg * 8192, 16), b = desc_lo(st + 16384, 4096);
      mbar_wait2(sb + RB_TF + 8 * (kb & 3), kb >> 2, sb + RB_TF + 32 + 32 * wg + 8 * (kb & 3), kb >> 2);
      if (kb == 0) TRT(2, 4);
      wg_fence();
#pragma unroll
      for (int kk = 0; kk < 4; kk++) wgmma_ss_n192_a0b1(acc, mk_desc(a + kk * 2, DHI_SW128), mk_desc(b + (kk >> 1) * 768 + (kk & 1) * 128, DHI_SW128), 1);
      wg_commit();
      wg_wait<1>();
      if (kb >= 1 && kb <= 4) {
        if (w4 == 0 && lane < 2) mbar_arrive_cl(te + 8 * (kb - 1));
        if (warp == 4) {
          mbar_wait(sb + RB_TE + 8 * (kb - 1), 0);
          if (elect()) { load_w(kb + 3); load_a(kb + 3, 0); load_a(kb + 3, 1); }
        }
        __syncwarp();
      }
    }
    asm volatile("barrier.cluster.wait.aligned;" ::: "memory");
    wg_wait<0>();
    fence_regs(acc);
    TRT(3, 4);
#pragma unroll
    for (int j = 0; j < 12; j++) {
      const int o = 16 * (j >> 1) + (j & 1);
      st_async128(ra + j * 512, pack_bf16(acc[o], acc[o + 2]), pack_bf16(acc[o + 4], acc[o + 6]), pack_bf16(acc[o + 8], acc[o + 10]), pack_bf16(acc[o + 12], acc[o + 14]), rb);
    }
    TRT(4, 4);
    mbar_wait(sb + RB_TR, 0);
    asm volatile("barrier.cluster.arrive.relaxed.aligned;" ::: "memory");
    TRT(5, 0);
#pragma unroll 1
    for (int J = 0; J < 3; J++) {
      float c[2][4];
      uint32_t v[4][4];
#pragma unroll
      for (int j = 0; j < 4; j++) ldsm4t(v[j], la + J * 1024 + (((8 * w4 + 4 * (m & 1) + j) ^ r) << 4));
#pragma unroll
      for (int j = 0; j < 4; j++) {
        const uint32_t b0 = g == 2 * j ? 0x3f803f80u : 0u, b1 = g == 2 * j + 1 ? 0x3f803f80u : 0u;
        if (j < 2) mma16816z(c[j], v[j], b0, b1);
        else mma16816(c[j & 1], v[j], b0, b1);
      }
      out[J * 16] = pack_bf16(c[0][0] + c[1][0], c[0][1] + c[1][1]);
      out[J * 16 + DM] = pack_bf16(c[0][2] + c[1][2], c[0][3] + c[1][3]);
    }
    TRT(6, 0);
    if (warp == 0) TRG(6);
    asm volatile("barrier.cluster.wait.aligned;" ::: "memory");
  }
  if (threadIdx.x == 96) TRE(128 + blockIdx.x);
}

void rmt_setup() {
  cudaFuncSetAttribute(rmt_kernel, cudaFuncAttributeMaxDynamicSharedMemorySize, R_SMEM);
  cudaFuncSetAttribute(rmt_kernel, cudaFuncAttributeNonPortableClusterSizeAllowed, 1);
}
void rmt_launch(EncodeFn enc, void* const* d_in, void* scr, void* out) {
  RmtParams R;
  map2d(enc, &R.wq, d_in[8], DM, HDALL, 16);
  map2d(enc, &R.wk, d_in[9], DM, HDALL, 16);
  map2d(enc, &R.wv, d_in[10], DM, HDALL, 16);
  map2d(enc, &R.wo, d_in[11], HDALL, DM, 64);
  map2d(enc, &R.x, d_in[6], SEQ, DM, 32);
  map2d(enc, &R.mem, d_in[7], 8, DM, 8);
  map2d(enc, &R.ox, scr, 4 * SEQ, HDALL, 32);
  cudaLaunchConfig_t cfg = {};
  map2d(enc, &R.ox64, scr, 4 * SEQ, HDALL, 64);
  map3d(enc, &R.wo3, d_in[11], HDALL, DM, 32, 3);
  R.out = (uint32_t*)out;
  R.ckv = (const __nv_bfloat16*)d_in[1]; R.wuk = (const __nv_bfloat16*)d_in[3]; R.wuv = (const __nv_bfloat16*)d_in[4];
  cfg.gridDim = dim3(64);
  cfg.blockDim = dim3(256);
  cfg.dynamicSmemBytes = R_SMEM;
  cfg.stream = cudaStreamPerThread;
  cudaLaunchAttribute at[1];
  at[0].id = cudaLaunchAttributeClusterDimension;
  at[0].val.clusterDim.x = 16;
  at[0].val.clusterDim.y = 1;
  at[0].val.clusterDim.z = 1;
  cfg.attrs = at;
  cfg.numAttrs = 1;
  cudaLaunchKernelEx(&cfg, rmt_kernel, R);
}


const uint16_t h_order[] = {
    4096, 4097, 34, 35, 36, 37, 38, 39, 40, 41, 42, 43, 44, 45, 46, 47, 48, 49, 50, 51,
    52, 53, 54, 55, 56, 57, 58, 59, 60, 61, 62, 63, 64, 65, 66, 67, 68, 69, 70, 71,
    4103, 4102, 4101, 4100, 4099, 4098, 72, 73, 74, 75, 76, 77, 78, 79, 4111, 4110, 4109, 4108, 4107, 4106,
    80, 81, 82, 83, 84, 85, 86, 87, 4119, 4118, 4117, 4116, 4115, 4114, 88, 89, 90, 91, 92, 93,
    94, 95, 4127, 4126, 4125, 4124, 4123, 4122, 96, 97, 98, 99, 100, 101, 102, 103, 4135, 4134, 4133, 4132,
    4131, 4130, 104, 105, 106, 107, 108, 109, 110, 111, 4143, 4142, 4141, 4140, 4139, 4138, 112, 113, 114, 115,
    116, 117, 118, 119, 4151, 4150, 4149, 4148, 4147, 4146, 120, 121, 122, 123, 124, 125, 126, 127, 4159, 4158,
    4157, 4156, 4155, 4154, 128, 129, 130, 131, 132, 133, 134, 135, 4167, 4166, 4165, 4164, 4163, 4162, 136, 137,
    138, 12288, 12544, 12800, 139, 140, 141, 142, 159, 4175, 4173, 4172, 4171, 4170, 144, 143, 4174, 145, 146, 148,
    149, 150, 151, 4180, 4182, 4181, 4183, 4178, 155, 154, 4196, 153, 156, 152, 157, 158, 4179, 147, 4191, 4190,
    4189, 4187, 4188, 4186, 161, 162, 168, 163, 165, 164, 166, 167, 4199, 4198, 4194, 4197, 4195, 160, 4219, 12801,
    12545, 169, 4210, 170, 171, 174, 4206, 4207, 172, 177, 4205, 173, 4228, 4203, 4204, 179, 181, 187, 4215, 182,
    176, 183, 199, 4212, 178, 4214, 4213, 184, 185, 4211, 205, 20738, 188, 189, 4221, 191, 186, 4222, 12289, 190,
    4220, 4218, 4202, 192, 193, 194, 180, 195, 196, 197, 4231, 202, 4229, 4230, 4226, 200, 4227, 201, 20994, 203,
    4223, 206, 175, 20482, 215, 204, 4239, 4234, 4238, 4237, 4236, 4243, 4251, 4235, 208, 209, 210, 211, 212, 207,
    213, 214, 4246, 4245, 4242, 198, 4244, 216, 217, 218, 221, 219, 220, 222, 230, 223, 4255, 4247, 4254, 4253,
    4252, 225, 4250, 224, 242, 20739, 228, 227, 232, 4260, 4263, 226, 4262, 4261, 4298, 229, 12803, 4259, 4258, 237,
    233, 234, 235, 236, 238, 231, 252, 4271, 4287, 4285, 4268, 4282, 4267, 4266, 240, 241, 243, 244, 246, 245,
    247, 250, 4278, 4277, 4185, 4276, 4290, 4295, 12802, 4275, 4145, 248, 4300, 4308, 4284, 253, 255, 4279, 254, 4270,
    4310, 4326, 4292, 4104, 4315, 4319, 4309, 4274, 251, 4323, 4161, 4314, 4301, 4351, 4293, 20483, 249, 4330, 12292, 4291,
    4335, 4349, 4299, 4307, 4311, 20995, 239, 4316, 4286, 4233, 4318, 4317, 4331, 12548, 12804, 4112, 4269, 4342, 4294, 4306,
    8706, 4201, 4302, 4129, 4283, 4340, 4343, 4105, 4303, 4347, 4327, 4348, 4208, 4341, 4338, 4350, 4322, 4121, 4128, 4346,
    4333, 4325, 4120, 4324, 4332, 4144, 4200, 4334, 4153, 4241, 4192, 4136, 4232, 4328, 4176, 4152, 4113, 8450, 4193, 4137,
    4313, 4289, 4329, 4209, 4249, 4224, 4184, 4257, 4160, 4280, 4169, 4240, 4256, 4168, 4177, 4272, 4217, 4339, 8710, 8193,
    4225, 8455, 8192, 8197, 8196, 8454, 8449, 12549, 8711, 12805, 8448, 8704, 8451, 8708, 8195, 8705, 12293, 8194, 8199, 8707,
    8709, 8452, 8453, 8198, 4273, 4305, 4288, 4216, 4248, 4281, 4296, 4265, 4264, 4297, 20998, 20742, 20486, 4312, 4321, 4304,
    4337, 4320, 4345, 4336, 4344,
};
int build_tasks(uint16_t* t) {
  int n = 0;
#ifdef DEV_ORDER
  if (const char* fn = getenv("ORDER")) {
    FILE* f = fopen(fn, "r");
    int v;
    while (fscanf(f, "%d", &v) == 1) t[n++] = v;
    fclose(f);
    return n;
  }
#endif
  static_assert(sizeof(h_order) / 2 <= MAXTASK, "tasks");
  for (; n < (int)(sizeof(h_order) / 2); n++) t[n] = h_order[n];
  return n;
}

}

extern "C" void kernel_launch(void* const* d_in, const int* in_sizes, int n_in, void* d_out, int out_size) {
  (void)in_sizes; (void)n_in; (void)out_size;
  static EncodeFn enc = nullptr;
  static void* scr = nullptr;
  if (!enc) {
    cudaDriverEntryPointQueryResult q;
    cudaGetDriverEntryPoint("cuTensorMapEncodeTiled", (void**)&enc, cudaEnableDefault, &q);
    cudaGetSymbolAddress(&scr, g_scr);
    cudaFuncSetAttribute(main_kernel, cudaFuncAttributeMaxDynamicSharedMemorySize, M_SMEM);
    rmt_setup();
  }
  rmt_launch(enc, d_in, scr, d_out);

  MainParams P;
  map2d(enc, &P.ckv, d_in[1], SEQ, 512, 128);
  map3d(enc, &P.wuk, d_in[3], 512, HDALL, 64, 2);
  map3d(enc, &P.wuv, d_in[4], 512, HDALL, 64, 2);
  map2d(enc, &P.ax, d_in[0], SEQ, DM, 64);
  map2d(enc, &P.wq, d_in[2], DM, HDALL, 64);
  map2d(enc, &P.scr, scr, 4 * SEQ, HDALL, 128);
  map3d(enc, &P.woa, d_in[5], HDALL, DM, 32, 3);
  map3d(enc, &P.wob, d_in[11], HDALL, DM, 32, 3);
  map2d(enc, &P.scr_st, scr, 4 * SEQ, HDALL, ST_ROWS);
  map2d(enc, &P.out_st, d_out, SEQ, 2 * DM, ST_ROWS);
  map3d(enc, &P.woa2, d_in[5], HDALL, DM, 32, 2);
  map3d(enc, &P.wob2, d_in[11], HDALL, DM, 32, 2);
  P.ntask = build_tasks(P.tasks);

  cudaLaunchConfig_t cfg = {};
  cfg.gridDim = dim3(2 * NCL);
  cfg.blockDim = dim3(384);
  cfg.dynamicSmemBytes = M_SMEM;
  cfg.stream = cudaStreamPerThread;
  cudaLaunchAttribute at[1];
  at[0].id = cudaLaunchAttributeProgrammaticStreamSerialization;
  at[0].val.programmaticStreamSerializationAllowed = 1;
  cfg.attrs = at;
  cfg.numAttrs = 1;
#ifdef DEV_SERIAL
  cfg.numAttrs = 0;
#endif
  cudaLaunchKernelEx(&cfg, main_kernel, P);
}
```
